```python
import torch

def _softmax(x, axis=-1):
    return torch.softmax(x, dim=axis)

def _gelu(x):
    return torch.nn.functional.gelu(x, approximate='tanh')

def _silu(x):
    return torch.nn.functional.silu(x)

def _sigmoid(x):
    return torch.sigmoid(x)

def _layernorm(x, axis=-1, eps=1e-05):
    m = x.mean(dim=axis, keepdim=True)
    v = x.var(dim=axis, keepdim=True, unbiased=False)
    return (x - m) / torch.sqrt(v + eps)

def _scatter_add(tgt, idx, src, axis=0):
    return tgt.clone().index_add_(axis, idx, src)

def _segment_sum(src, seg, n):
    out = torch.zeros((n,) + src.shape[1:], dtype=src.dtype)
    return out.index_add_(0, seg, src)

def _pad(x, pw):
    flat = tuple((v for pair in reversed(pw) for v in pair))
    return torch.nn.functional.pad(x, flat)
kernel_name = 'interleave_layers__memory_aug_recurrent_mem_tr__spectral_gfnet__prompt'

def setup_inputs():

    _w = lambda a: (lambda t: t.to(torch.bfloat16) if t.is_floating_point() else t)(torch.as_tensor(a))

    def _A_setup():
        B, S, Dm = (1, 2048, 640)
        H, Dh = (32, 128)
        M, seg = (8, 32)
        seg = min(seg, S)
        S = S // seg * seg
        return {'x': _w((lambda *s: torch.randn(*s, dtype=torch.bfloat16) * 0.05)(B, S, Dm)), 'mem0': _w((lambda *s: torch.randn(*s, dtype=torch.bfloat16) * 0.2)(B, M, Dm)), 'Wq': _w((lambda *s: torch.randn(*s, dtype=torch.bfloat16) * 1.6)(Dm, H, Dh) * Dm ** (-0.5)), 'Wk': _w((lambda *s: torch.randn(*s, dtype=torch.bfloat16) * 1.6)(Dm, H, Dh) * Dm ** (-0.5)), 'Wv': _w((lambda *s: torch.randn(*s, dtype=torch.bfloat16) * 0.2)(Dm, H, Dh) * Dm ** (-0.5)), 'Wo': _w((lambda *s: torch.randn(*s, dtype=torch.bfloat16) * 0.2)(H, Dh, Dm) * (H * Dh) ** (-0.5)), 'seg_len': seg}
    _A_in = _A_setup()

    def _B_setup():
        B, S, D = (1, 2048, 640)
        Df = D // 2 + 1
        return {'x': _w((lambda *s: torch.randn(*s, dtype=torch.bfloat16) * 0.05)(B, S, D)), 'w_r': _w((lambda *s: torch.randn(*s, dtype=torch.bfloat16) * 0.4)(S, Df) * 0.02), 'w_i': _w((lambda *s: torch.randn(*s, dtype=torch.bfloat16) * 0.4)(S, Df) * 0.02)}
    _B_in = _B_setup()
    return {'A_x': _A_in['x'], 'A_mem0': _A_in['mem0'], 'A_Wq': _A_in['Wq'], 'A_Wk': _A_in['Wk'], 'A_Wv': _A_in['Wv'], 'A_Wo': _A_in['Wo'], 'A_seg_len': _A_in['seg_len'], 'B_x': _B_in['x'], 'B_w_r': _B_in['w_r'], 'B_w_i': _B_in['w_i']}

def reference(A_x, A_mem0, A_Wq, A_Wk, A_Wv, A_Wo, A_seg_len, B_x, B_w_r, B_w_i):

    def _A_ref(x, mem0, Wq, Wk, Wv, Wo, seg_len):
        B, S, Dm = x.shape
        H, Dh = (Wq.shape[1], Wq.shape[2])
        M = mem0.shape[1]
        scale = Dh ** (-0.5)
        n_seg = S // seg_len
        L = M + seg_len
        idx = torch.arange(L)
        mask = (idx[:, None] < M) | (idx[:, None] >= idx[None, :])
        mem = mem0
        outs = []
        for s in range(n_seg):
            xs = x[:, s * seg_len:(s + 1) * seg_len, :].clone()
            h = torch.concatenate([mem, xs], axis=1)
            q = torch.einsum('btd,dhe->bhte', h, Wq)
            k = torch.einsum('btd,dhe->bhte', h, Wk)
            v = torch.einsum('btd,dhe->bhte', h, Wv)
            scores = torch.einsum('bhqe,bhke->bhqk', q, k) * scale
            scores = torch.where(mask[None, None], scores, -1000000000.0)
            p = _softmax(scores, axis=-1)
            o = torch.einsum('bhqk,bhke->bhqe', p, v)
            o = torch.einsum('bhte,hed->btd', o, Wo)
            mem = o[:, :M, :].clone()
            outs.append(o[:, M:, :])
        return torch.concatenate(outs, axis=1)

    def _B_ref(x, w_r, w_i):
        B, S, D = x.shape
        X = (lambda x, axes=(-2, -1): torch.fft.rfft2(x.float(), dim=axes))(x, axes=(-2, -1))
        W = w_r + 1j * w_i
        X = X * W
        y = (lambda x, s, axes=(-2, -1): torch.fft.irfft2(x, s=s, dim=axes).to(torch.bfloat16))(X, (S, D), axes=(-2, -1))
        return y
    x = A_x
    x = x + _A_ref(_layernorm(x, axis=-1), A_mem0, A_Wq, A_Wk, A_Wv, A_Wo, A_seg_len)
    x = x + _B_ref(_layernorm(x, axis=-1), B_w_r, B_w_i)
    x = x + _A_ref(_layernorm(x, axis=-1), A_mem0, A_Wq, A_Wk, A_Wv, A_Wo, A_seg_len)
    x = x + _B_ref(_layernorm(x, axis=-1), B_w_r, B_w_i)
    return x
```

```cpp
#include <cuda_runtime.h>
#include <cuda_bf16.h>
#include <cuda_fp16.h>
#include <cuda.h>
#include <stdint.h>

typedef __nv_bfloat16 bf16;
#define DEVINL __device__ __forceinline__

__device__ __align__(1024) bf16 g_xn[2048 * 640];
__device__ __align__(1024) bf16 g_x[2048 * 640];
__device__ __align__(1024) char g_kv[64 * 32 * 16384];
__device__ __align__(1024) char g_kvm[64 * 32 * 4096];
__device__ __align__(1024) bf16 g_o[2048 * 4096];
__device__ __align__(1024) bf16 g_part[4 * 2048 * 640];
__device__ __align__(1024) uint32_t g_y[320 * 2048];
__device__ __align__(1024) uint32_t g_wt[321 * 2048];
__device__ __align__(1024) float2 g_tw[15 * 128 + 15 * 8];
__device__ __align__(4096) char g_comm[4 << 20];
constexpr int F_KV = 0, F_KM = 1024, F_O = F_KM + 2048, F_ROLE = F_O + 128, F_LAYER = F_ROLE + 64;
__device__ __align__(1024) uint32_t g_flags[2 * F_LAYER];
__device__ uint32_t g_side[256];

#define POLL_LIMIT (1 << 17)
DEVINL uint32_t smem_u32(const void* p) { return (uint32_t)__cvta_generic_to_shared(p); }
DEVINL uint32_t mapa(uint32_t a, uint32_t r) { uint32_t o; asm volatile("mapa.shared::cluster.u32 %0, %1, %2;" : "=r"(o) : "r"(a), "r"(r)); return o; }
DEVINL uint32_t clk() { uint32_t v; asm volatile("{.reg .b64 w; mov.u64 w, %%clock64; cvt.u32.u64 %0, w;}" : "=r"(v)::"memory"); return v; }
DEVINL void mbar_init(uint32_t bar, uint32_t cnt) { asm volatile("mbarrier.init.shared::cta.b64 [%0], %1;" ::"r"(bar), "r"(cnt) : "memory"); }
DEVINL void mbar_arrive(uint32_t bar) { asm volatile("mbarrier.arrive.shared::cta.b64 _, [%0];" ::"r"(bar) : "memory"); }
DEVINL void mbar_arrive_remote(uint32_t bar) { asm volatile("mbarrier.arrive.shared::cluster.b64 _, [%0];" ::"r"(bar) : "memory"); }
DEVINL void mbar_arrive_tx(uint32_t bar, uint32_t tx) { asm volatile("mbarrier.arrive.expect_tx.shared::cta.b64 _, [%0], %1;" ::"r"(bar), "r"(tx) : "memory"); }
DEVINL void mbar_wait(uint32_t bar, uint32_t ph) {
  asm volatile("{.reg .pred p,q; .reg .b32 c; mov.b32 c, 0;\n"
               "W0: add.u32 c,c,1; setp.lt.u32 q,c,0x100000; mbarrier.try_wait.parity.shared::cta.b64 p, [%0], %1; not.pred p,p; and.pred p,p,q; @p bra W0;}" ::"r"(bar), "r"(ph) : "memory");
}
DEVINL void bar_sync(int id, int n) { asm volatile("bar.sync %0, %1;" ::"r"(id), "r"(n) : "memory"); }
DEVINL void bar_arrive(int id, int n) { asm volatile("bar.arrive %0, %1;" ::"r"(id), "r"(n) : "memory"); }
DEVINL void cluster_sync() { asm volatile("barrier.cluster.arrive.release.aligned; barrier.cluster.wait.acquire.aligned;" ::: "memory"); }
DEVINL void tma_2d(uint32_t dst, const CUtensorMap* tm, int c0, int c1, uint32_t bar) {
  asm volatile("cp.async.bulk.tensor.2d.shared::cluster.global.mbarrier::complete_tx::bytes [%0], [%1, {%2, %3}], [%4];" ::"r"(dst), "l"(tm), "r"(c0), "r"(c1), "r"(bar) : "memory");
}
DEVINL void tma_2d_mc(uint32_t dst, const CUtensorMap* tm, int c0, int c1, uint32_t bar) {
  asm volatile("cp.async.bulk.tensor.2d.shared::cluster.global.mbarrier::complete_tx::bytes.multicast::cluster [%0], [%1, {%2, %3}], [%4], %5;" ::"r"(dst), "l"(tm), "r"(c0), "r"(c1), "r"(bar), "h"((uint16_t)3) : "memory");
}
DEVINL void bulk_g2s(uint32_t dst, const void* src, uint32_t bytes, uint32_t bar) {
  asm volatile("cp.async.bulk.shared::cluster.global.mbarrier::complete_tx::bytes [%0], [%1], %2, [%3];" ::"r"(dst), "l"(src), "r"(bytes), "r"(bar) : "memory");
}
DEVINL void fence_proxy_async() { asm volatile("fence.proxy.async;" ::: "memory"); }
DEVINL void ldsm4t(uint32_t* r, uint32_t a) { asm volatile("ldmatrix.sync.aligned.m8n8.x4.trans.shared.b16 {%0,%1,%2,%3}, [%4];" : "=r"(r[0]), "=r"(r[1]), "=r"(r[2]), "=r"(r[3]) : "r"(a) : "memory"); }
DEVINL void stsm4(uint32_t a, uint32_t r0, uint32_t r1, uint32_t r2, uint32_t r3) { asm volatile("stmatrix.sync.aligned.m8n8.x4.shared.b16 [%0], {%1,%2,%3,%4};" ::"r"(a), "r"(r0), "r"(r1), "r"(r2), "r"(r3) : "memory"); }
DEVINL void mma16816(float* d, const uint32_t* a, uint32_t b0, uint32_t b1) {
  asm volatile("mma.sync.aligned.m16n8k16.row.col.f32.bf16.bf16.f32 {%0,%1,%2,%3}, {%4,%5,%6,%7}, {%8,%9}, {%0,%1,%2,%3};"
               : "+f"(d[0]), "+f"(d[1]), "+f"(d[2]), "+f"(d[3]) : "r"(a[0]), "r"(a[1]), "r"(a[2]), "r"(a[3]), "r"(b0), "r"(b1));
}
DEVINL void mma16816z(float* d, const uint32_t* a, uint32_t b0, uint32_t b1) {
  asm volatile("mma.sync.aligned.m16n8k16.row.col.f32.bf16.bf16.f32 {%0,%1,%2,%3}, {%4,%5,%6,%7}, {%8,%9}, {%10,%10,%10,%10};"
               : "=f"(d[0]), "=f"(d[1]), "=f"(d[2]), "=f"(d[3]) : "r"(a[0]), "r"(a[1]), "r"(a[2]), "r"(a[3]), "r"(b0), "r"(b1), "f"(0.f));
}
DEVINL void mma1688z(float* d, uint32_t a0, uint32_t a1, uint32_t b0) {
  asm volatile("mma.sync.aligned.m16n8k8.row.col.f32.bf16.bf16.f32 {%0,%1,%2,%3}, {%4,%5}, {%6}, {%7,%7,%7,%7};"
               : "=f"(d[0]), "=f"(d[1]), "=f"(d[2]), "=f"(d[3]) : "r"(a0), "r"(a1), "r"(b0), "f"(0.f));
}
DEVINL uint32_t movm(uint32_t a) { uint32_t r; asm volatile("movmatrix.sync.aligned.m8n8.trans.b16 %0, %1;" : "=r"(r) : "r"(a)); return r; }
DEVINL uint32_t pack_bf16(float lo, float hi) { uint32_t r; asm("cvt.rn.bf16x2.f32 %0, %1, %2;" : "=r"(r) : "f"(hi), "f"(lo)); return r; }
DEVINL uint32_t pack_f16(float lo, float hi) { uint32_t r; asm("cvt.rn.f16x2.f32 %0, %1, %2;" : "=r"(r) : "f"(hi), "f"(lo)); return r; }
DEVINL float bf_lo(uint32_t w) { return __uint_as_float(w << 16); }
DEVINL float bf_hi(uint32_t w) { return __uint_as_float(w & 0xffff0000u); }
DEVINL uint32_t hadd2bf(uint32_t a, uint32_t b) { uint32_t r; asm("add.rn.bf16x2 %0, %1, %2;" : "=r"(r) : "r"(a), "r"(b)); return r; }
DEVINL uint32_t lds32(uint32_t a) { uint32_t v; asm volatile("ld.shared.u32 %0, [%1];" : "=r"(v) : "r"(a) : "memory"); return v; }
DEVINL uint2 lds64(uint32_t a) { uint2 v; asm volatile("ld.shared.v2.u32 {%0,%1}, [%2];" : "=r"(v.x), "=r"(v.y) : "r"(a) : "memory"); return v; }
DEVINL uint4 lds128(uint32_t a) { uint4 v; asm volatile("ld.shared.v4.u32 {%0,%1,%2,%3}, [%4];" : "=r"(v.x), "=r"(v.y), "=r"(v.z), "=r"(v.w) : "r"(a) : "memory"); return v; }
DEVINL void sts32(uint32_t a, uint32_t v) { asm volatile("st.shared.u32 [%0], %1;" ::"r"(a), "r"(v) : "memory"); }
DEVINL void sts64(uint32_t a, uint32_t x, uint32_t y) { asm volatile("st.shared.v2.u32 [%0], {%1,%2};" ::"r"(a), "r"(x), "r"(y) : "memory"); }
DEVINL void sts128(uint32_t a, uint4 v) { asm volatile("st.shared.v4.u32 [%0], {%1,%2,%3,%4};" ::"r"(a), "r"(v.x), "r"(v.y), "r"(v.z), "r"(v.w) : "memory"); }
DEVINL void stasync64(uint32_t a, uint32_t x, uint32_t y, uint32_t bar) { asm volatile("st.async.weak.shared::cluster.mbarrier::complete_tx::bytes.v2.b32 [%0], {%1,%2}, [%3];" ::"r"(a), "r"(x), "r"(y), "r"(bar) : "memory"); }
DEVINL uint4 ldg_rlx128(const void* p) { uint4 v; asm volatile("{.reg .b64 a,b; ld.relaxed.gpu.global.v2.b64 {a,b}, [%4]; mov.b64 {%0,%1}, a; mov.b64 {%2,%3}, b;}" : "=r"(v.x), "=r"(v.y), "=r"(v.z), "=r"(v.w) : "l"(p) : "memory"); return v; }
DEVINL uint2 ldg_rlx64(const void* p) { uint2 v; asm volatile("ld.relaxed.gpu.global.v2.u32 {%0,%1}, [%2];" : "=r"(v.x), "=r"(v.y) : "l"(p) : "memory"); return v; }
DEVINL void stg_rlx64(void* p, uint32_t x, uint32_t y) { asm volatile("{.reg .b64 a; mov.b64 a, {%1,%2}; st.relaxed.gpu.global.b64 [%0], a;}" ::"l"(p), "r"(x), "r"(y) : "memory"); }
DEVINL void stg_rlx32(void* p, uint32_t x) { asm volatile("st.relaxed.gpu.global.u32 [%0], %1;" ::"l"(p), "r"(x) : "memory"); }
DEVINL uint4 ldg_cg128(const void* p) { uint4 v; asm volatile("ld.global.cg.v4.u32 {%0,%1,%2,%3}, [%4];" : "=r"(v.x), "=r"(v.y), "=r"(v.z), "=r"(v.w) : "l"(p) : "memory"); return v; }
DEVINL uint32_t ldg_cg32(const void* p) { uint32_t v; asm volatile("ld.global.cg.u32 %0, [%1];" : "=r"(v) : "l"(p) : "memory"); return v; }
DEVINL void flag_wait(const uint32_t* p, uint32_t want) {
  uint32_t v; int n = 0;
  do { asm volatile("ld.acquire.gpu.global.u32 %0, [%1];" : "=r"(v) : "l"(p) : "memory"); if (v >= want) break; __nanosleep(40); } while (++n < POLL_LIMIT);
}
DEVINL void flag_add(uint32_t* p) { asm volatile("fence.acq_rel.gpu; red.relaxed.gpu.global.add.u32 [%0], 1;" ::"l"(p) : "memory"); }
DEVINL float ex2(float x) { float y; asm("ex2.approx.ftz.f32 %0, %1;" : "=f"(y) : "f"(x)); return y; }
DEVINL float rcp(float x) { float y; asm("rcp.approx.ftz.f32 %0, %1;" : "=f"(y) : "f"(x)); return y; }
DEVINL uint32_t opaque(uint32_t x) { return __shfl_sync(~0u, x, threadIdx.x & 31); }
DEVINL uint32_t launder(uint32_t x) { asm volatile("" : "+r"(x)); return x; }
DEVINL void pdl_wait() { asm volatile("griddepcontrol.wait;" ::: "memory"); }
DEVINL void pdl_launch() { asm volatile("griddepcontrol.launch_dependents;" ::: "memory"); }
constexpr float SM_SCALE = 0.08838834764831845f * 1.4426950408889634f;

struct ArgsA {
  const bf16* mem0; char* comm; uint32_t* flags; const bf16* wr; const bf16* wi;
  int layer; int ta[3], tb[3];
};

#define VP 4
#define HELD 0x2557
#define PRE 4
#define VPRE 4
#define R0 5
#define TRK 60
#define W1D 120
constexpr int C_WV = 0;
constexpr int C_WO = 81920;
constexpr int C_KV = 163840;
constexpr int C_M  = C_KV + 24576;
constexpr int C_QK = C_M + 10240;
constexpr int C_VP = C_QK + 4096;
constexpr int C_S  = C_VP + 4096;
constexpr int C_O  = C_S + 2048;
constexpr int C_R  = C_O + 2048;
constexpr int S_BAR = 229376;
constexpr int S_END = S_BAR + 256;
enum { BAR_M1 = 1, BAR_QK = 2, BAR_O = 3, BAR_H = 4, BAR_X = 5, BAR_M2 = 6, BAR_W = 7  , BAR_E = 9 };
constexpr int B_W = 0, B_S = 8, B_V = 16, B_KV = 24;
constexpr int G2_OFF = 0x130000, TS_OFF = 0x11000;

#define SCHED(x, c) asm volatile("{.reg .pred p; setp.eq.u32 p, %0, %1; @p exit;}" ::"r"(x), "r"(0x7fff0001u + 2 * (c)) : "memory")
DEVINL uint32_t g1page(uint32_t L) { L = ((L & 7) | ((L & 24) << 2)) << 1; return (L | (__popc(L & 0xb2) & 1)) << 12; }
DEVINL void spin_until(uint32_t t) {
  asm volatile("{.reg .pred p; .reg .b32 c; .reg .b64 w;\nS0: mov.u64 w, %%clock64; cvt.u32.u64 c, w; sub.s32 c, c, %0; setp.lt.s32 p, c, 0; @p bra S0;}" ::"r"(t) : "memory");
}
DEVINL void gedge(uint32_t& G, uint32_t& C, uint32_t z) {
  asm volatile("{.reg .pred p,q; .reg .b64 w; .reg .b32 g0,c0,d;\n mov.u64 w, %%globaltimer; cvt.u32.u64 g0, w; add.u32 g0,g0,%2; mov.u64 w, %%clock64; cvt.u32.u64 c0, w;\n"
               "E0: mov.u64 w, %%globaltimer; cvt.u32.u64 %0, w; mov.u64 w, %%clock64; cvt.u32.u64 %1, w; sub.u32 d,%1,c0; setp.lt.u32 q,d,200; setp.eq.and.u32 p,%0,g0,q; @p bra E0;}"
               : "=r"(G), "=r"(C) : "r"(z) : "memory");
}
DEVINL uint32_t pack_tag(float lo, float hi, uint32_t tg) {
  const uint32_t w = pack_bf16(lo, __uint_as_float(tg | 0x3F800000u)), a = __float_as_uint(hi) + (tg ^ 0x10000u); uint32_t r;
  asm("lop3.b32 %0, %1, %2, 0xFFFE0000, 0xE4;" : "=r"(r) : "r"(a), "r"(w)); return r;
}
DEVINL void load_kv(uint32_t sb, int h, int j, int s) {
  const uint32_t dst = sb + C_KV + (s & 1) * 12288, bar = sb + S_BAR + B_KV + (s & 1) * 8;
  const char* src = g_kv + (size_t)(s * 32 + h) * 16384;
  fence_proxy_async();
  mbar_arrive_tx(bar, 12288);
  bulk_g2s(dst, src + j * 4096, 4096, bar); bulk_g2s(dst + 4096, src + 8192 + j * 4096, 4096, bar); bulk_g2s(dst + 8192, src + 8192 + (j ^ 1) * 4096, 4096, bar);
}

template <int KH>
DEVINL void chain_mma(uint32_t sb, uint32_t px, int h, int j, const ArgsA& args) {
  const int lane = threadIdx.x & 31, mg = (threadIdx.x >> 5) & 3, mi = lane >> 3, r = lane & 7;
  const uint32_t aW = opaque(sb + (uint32_t)(((mi >> 1) * 8 + r) * 128 + (((2 * mg + (mi & 1)) ^ r) << 4)));
  const uint32_t aL = opaque(sb + lane * 16);
  const uint32_t aLm = opaque(sb + mg * 512 + lane * 16);
  constexpr int OV = C_WV + KH * 40960, OM = C_M + KH * 5120, NF = KH ? 16 : 24;
  auto owo = [](int f) { return C_WO + (KH ? 1 + 3 * (f >> 3) : (f < 8 ? 0 : 1 + (f >> 3))) * 16384 + (f & 7) * 2048; };
  auto held = [](int k) { return (HELD >> k) & 1; };
  auto rank = [](int k) { return __popc(HELD & ((1 << k) - 1)); };
  uint32_t wq[20][4], wk[20][4];
  mbar_wait(sb + S_BAR + B_W, 0);
#pragma unroll
  for (int k = 0; k < 20; k++) { ldsm4t(wq[k], aW + OV + k * 2048); ldsm4t(wk[k], aW + C_WO + KH * 40960 + k * 2048); }
  bar_sync(BAR_H, 384);
  mbar_wait(sb + S_BAR + B_W, 1);
#pragma unroll 1
  for (int s = 0;; s++) {
    uint32_t v[20][4];
    if (s == 0) {
#pragma unroll
      for (int k = 0; k < 20; k++) if (held(k)) ldsm4t(v[k], aW + OV + k * 2048);
    } else {
      const uint32_t o = launder(aLm) - sb;
      const char* p = args.comm + (g1page((h & 3) * 4) + G2_OFF + KH * 2048 + o);
      const uint32_t am = sb + OM + (o & 0x700) + ((o & 0xf0) >> 1), tm = 0u - ((s + args.layer) & 1);
#pragma unroll
      for (int k = 0; k < 20; k++) if (held(k) && rank(k) < VPRE) ldsm4t(v[k], aW + OV + k * 2048);
      spin_until(lds32(sb + C_R + 48) + args.tb[0]);
      uint4 a = ldg_rlx128(p);
#pragma unroll
      for (int k = 0; k < 20; k++) if (held(k) && rank(k) >= VPRE) ldsm4t(v[k], aW + OV + k * 2048);
      SCHED(am ^ tm, 29);
      sts64(am, a.x, a.z); sts64(am + 128, a.y, a.w);
      if (__any_sync(~0u, ((a.x ^ tm) | (a.z ^ tm)) & 0x10000u)) {
        int lim = 0;
        do { a = ldg_rlx128(p); ++lim; } while (__any_sync(~0u, (((a.x ^ tm) | (a.z ^ tm)) & 0x10000u) && lim < POLL_LIMIT));
        sts64(am, a.x, a.z); sts64(am + 128, a.y, a.w);
      }
    }
    bar_sync(BAR_W + KH, 128);
    float cq[4], ck[4], cv[4];
    uint32_t b[10][4];
    ldsm4t(b[0], aL + OM); ldsm4t(b[1], aL + OM + 512);
#pragma unroll
    for (int k = 0; k < 20; k++) {
      const int p = k >> 1;
      const uint32_t b0 = b[p][(k & 1) * 2], b1 = b[p][(k & 1) * 2 + 1];
      if (k == 0) { mma16816z(cv, v[0], b0, b1); mma16816z(cq, wq[k], b0, b1); mma16816z(ck, wk[k], b0, b1); }
      else { if (k < 20 - VP) mma16816(cv, v[k], b0, b1); mma16816(cq, wq[k], b0, b1); mma16816(ck, wk[k], b0, b1); }
      if (k == 5) bar_sync(BAR_M1, 320);
      if (k == 9) bar_sync(BAR_M2, 352);
      if ((k & 1) && p + 2 < 10) ldsm4t(b[p + 2], aL + OM + (p + 2) * 512);
      if (k + 3 < 20 - VP && !held(k + 3)) ldsm4t(v[k + 3], aW + OV + (k + 3) * 2048);
      if (k >= 20 - VP && k < 20 - VP + PRE && !held(k)) ldsm4t(v[k], aW + OV + k * 2048);
    }
    stsm4(aLm + C_QK + KH * 2048, pack_bf16(cq[0], cq[1]), pack_bf16(cq[2], cq[3]), pack_bf16(ck[0], ck[1]), pack_bf16(ck[2], ck[3]));
    const bool tsw = KH == 1 && launder(aLm) == aL + 512;
    if (tsw) bar_sync(BAR_QK, 384); else bar_arrive(BAR_QK, 384);
    SCHED(aL, 1);
    const uint32_t l8 = (launder(aL) - sb) >> 1;
    uint2 ts;
    if (tsw) ts = ldg_rlx64(args.comm + TS_OFF + l8);
#pragma unroll
    for (int k = 20 - VP + PRE; k < 20; k++) if (!held(k)) ldsm4t(v[k], aW + OV + k * 2048);
#pragma unroll
    for (int k = 20 - VP; k < 20; k++) {
      const int p = k >> 1, q = k - 20 + VP; const uint32_t b0 = b[p][(k & 1) * 2], b1 = b[p][(k & 1) * 2 + 1];
      if (q % 3 == 0) mma16816(cv, v[k], b0, b1); else if (q == 1) mma16816z(cq, v[k], b0, b1); else if (q == 2) mma16816z(ck, v[k], b0, b1);
      else if (q % 3 == 1) mma16816(cq, v[k], b0, b1); else mma16816(ck, v[k], b0, b1);
    }
    if (VP >= 3) {
#pragma unroll
      for (int i = 0; i < 4; i++) cv[i] += cq[i] + ck[i];
    }
    { const uint32_t vx = pack_bf16(cv[0], cv[1]), vy = pack_bf16(cv[2], cv[3]);
      const uint32_t av = aLm - l8 + C_VP + KH * 256;
      stasync64(av + 2048 + px, vx, vy, launder(sb) + S_BAR + B_V + px);
      sts64(av, vx, vy);
      __syncwarp();
      if (l8 == 0) mbar_arrive(sb + S_BAR + B_V); }
    auto do_export = [&]() {
      const uint32_t off = launder(aLm) - sb;
      char* dst = g_kvm + (launder(s * 32 + h) * 4096 + launder(j) * 1024);
      const uint32_t av = aLm - l8 + C_VP; const uint2 a = lds64(av), c = lds64(av + 256);
      char* q = dst + 2048 + ((off >> 9) << 8) + (l8 >> 1);
      *(uint32_t*)q = hadd2bf(a.x, c.x); *(uint32_t*)(q + 128) = hadd2bf(a.y, c.y);
      if (off < 1024) {
        uint32_t k0[4], k1[4]; const uint32_t ak = sb + C_QK + 256 + ((off >> 8) << 9) + (off & 255);
        ldsm4t(k0, ak); ldsm4t(k1, ak + 2048);
        *(uint4*)(dst + off) = make_uint4(hadd2bf(k0[0], k1[0]), hadd2bf(k0[1], k1[1]), hadd2bf(k0[2], k1[2]), hadd2bf(k0[3], k1[3]));
      }
    };
    if (KH == 1) bar_arrive(BAR_E, 256);
    if (s == 63) { if (KH == 0) { bar_sync(BAR_E, 256); do_export(); } bar_arrive(BAR_O, 384); break; }
    uint32_t w[NF][4];
    { uint32_t t = clk() + ((((launder(aLm) - aL) >> 8) + KH) * TRK >> 3);
#pragma unroll
      for (int f = 0; f < 8; f++) {
        spin_until(t); t += TRK; ldsm4t(w[f], aW + owo(f));
        if (f == 3) {
          if (KH == 0) { bar_sync(BAR_E, 256); do_export(); }
          if (tsw) {
            const uint4 cal = lds128(sb + C_R + 64);
            const uint32_t d0 = ts.x - cal.x, d1 = ts.y - cal.x;
            const int dt = (int)__reduce_max_sync(~0u, max(d0 < 32768u ? d0 : 0u, d1 < 32768u ? d1 : 0u));
            sts32(sb + C_R + 48, cal.y + (uint32_t)min(__float2int_rn((float)dt * __uint_as_float(cal.z)), 8192));
          }
          if (KH == 1 && launder(aLm) == sb + 1024 && s < 62) load_kv(sb, h, j, s + 1);
        }
      } }
    const uint32_t tg = ((s + args.layer + 1) & 1) << 16;
    const uint32_t ar = sb + C_R + (l8 & 24);
    const uint32_t o = launder(aLm) - sb;
    char* g1w = args.comm + (g1page(j * 16 + KH * 8 + (o >> 8)) + ((o & 128) << 4) + h * 64 + ((o & 112) >> 1));
    bar_sync(BAR_O, 384);
    uint32_t ob[16];
#pragma unroll
    for (int p = 0; p < 4; p++) ldsm4t(ob + 4 * p, aL + C_O + p * 512);
    const uint2 rr = lds64(ar);
    const float r0 = rcp(__uint_as_float(rr.x)), r1 = rcp(__uint_as_float(rr.y));
#pragma unroll
    for (int f = 0; f < NF; f++) {
      const int k = f & 7; const uint32_t* A = w[f];
      if (k == 0) mma16816z(cq, A, ob[0], ob[1]); else if (k == 1) mma16816z(ck, A, ob[2], ob[3]);
      else if (k & 1) mma16816(ck, A, ob[2 * k], ob[2 * k + 1]); else mma16816(cq, A, ob[2 * k], ob[2 * k + 1]);
      constexpr int RA = KH ? 0 : R0;
      if (k >= 2 && k < 2 + RA && (f & ~7) + 8 < NF) ldsm4t(w[f + 6], aW + owo(f + 6));
      if (k == 7) {
        stg_rlx64(g1w + (f < 8 ? 0 : (f < 16 && KH == 0) ? 0x30000 : 0x100000), pack_tag((cq[0] + ck[0]) * r0, (cq[1] + ck[1]) * r1, tg), pack_bf16((cq[2] + ck[2]) * r0, (cq[3] + ck[3]) * r1));
        if (KH == 1 && f == 7) spin_until(clk() + W1D); else SCHED(aL, 32 + f);
#pragma unroll
        for (int q = RA; q < 8; q++) if (f + 1 < NF) ldsm4t(w[f + 1 + q], aW + owo(f + 1 + q));
        if (KH == 1 && f == 7) SCHED(aL, 33);
      }
    }
  }
}

DEVINL void chain_helper(uint32_t sb, uint32_t px, int h, int j, const ArgsA& args, const CUtensorMap* tq, const CUtensorMap* tk, const CUtensorMap* tv, const CUtensorMap* to) {
  const int c = 2 * h + j;
  const uint32_t bW = sb + S_BAR + B_W, bS = sb + S_BAR + B_S, bV = sb + S_BAR + B_V, bKV = sb + S_BAR + B_KV;
  const uint32_t lane0 = opaque(threadIdx.x & 31);
  const uint32_t warp = __shfl_sync(~0u, (threadIdx.x >> 5) & 3, 0);
  uint32_t G0, C0;
  { const int tid = threadIdx.x - 256;
    if (tid == 0) { mbar_arrive_tx(bW, 163840);
#pragma unroll 1
      for (int i = 0; i < 10; i++) { tma_2d(sb + C_WV + i * 8192, tq, h * 128 + j * 64, i * 64, bW); tma_2d(sb + C_WO + i * 8192, tk, h * 128 + j * 64, i * 64, bW); } }
    gedge(G0, C0, lane0 >> 5);
#pragma unroll
    for (int i = 0; i < 5; i++) { const int q = tid + i * 128, n = q & 7, d0 = (q >> 3) * 8; const uint4 v = *(const uint4*)(args.mem0 + n * 640 + d0); const uint32_t w[4] = {v.x, v.y, v.z, v.w};
#pragma unroll
      for (int e = 0; e < 8; e++) asm volatile("st.shared.u16 [%0], %1;" ::"r"(sb + C_M + (d0 + e) * 16 + n * 2), "h"((unsigned short)(w[e >> 1] >> ((e & 1) * 16))) : "memory"); }
    bar_sync(BAR_H, 384);
    if (tid == 0) { mbar_arrive_tx(bW, 163840);
#pragma unroll 1
      for (int i = 0; i < 10; i++) { tma_2d(sb + C_WV + i * 8192, tv, h * 128 + j * 64, i * 64, bW); tma_2d(sb + C_WO + i * 8192, to, j * 320 + (i >> 1) * 64, h * 128 + ((i & 1) ^ j) * 64, bW); } }
    if (tid == 96) { flag_wait(args.flags + F_KV + h, 2); load_kv(sb, h, j, 0); }
    __syncwarp();
  }
  auto calib = [&]() { uint32_t G, C; gedge(G, C, lane0 >> 5);
    const float rt = (float)(C - C0) * rcp(16.f * (float)(G - G0));
    sts128(sb + C_R + 32, make_uint4(G, C, __float_as_uint(rt), __float_as_uint(rcp(rt)))); __syncwarp(); };
  if (warp == 3) calib();
  if (warp == 0 || warp == 3) bar_arrive(BAR_M1, 320); else bar_arrive(BAR_M2, 352);
#pragma unroll 1
  for (int s = 0;; s++) {
    const uint32_t ph = s & 1, kvb = sb + C_KV + ph * 12288;
    uint32_t lane = launder(lane0);
    if (warp == 3) {
      if (lane == 0) { mbar_arrive_tx(bV, 2048); if (s < 63) mbar_arrive_tx(bS, 1024); }
      const uint4 cal = lds128(sb + C_R + 32);
      bar_sync(BAR_M2, 352);
      sts32(sb + C_R + 52, 0);
      const uint32_t E = clk();
      if (lane == 0) { const uint32_t e16 = cal.x * 16 + (uint32_t)__float2int_rn((float)(int)(E - cal.y) * __uint_as_float(cal.w));
        stg_rlx32(args.comm + TS_OFF + c * 4, e16); sts128(sb + C_R + 64, make_uint4(e16, E, cal.z, 0)); }
      __syncwarp();
    }
    if (s == 63) { bar_sync(BAR_QK, 384); mbar_wait(bV, 1); bar_sync(BAR_O, 384); if (warp == 3 && lane == 0) flag_add(args.flags + F_KM + 63 * 32 + h); break; }
    mbar_wait(bKV + ph * 8, (s >> 1) & 1);
    const uint32_t mi = lane >> 3, r = lane & 7;
    {
      uint32_t qa[4][4], km[4]; uint2 kb[4]; float s0[4], s1[4], s2[4], s3[4];
      const uint32_t aK = kvb + warp * 1024 + lane * 16, aQ = sb + C_QK + (mi & 1) * 2048 + ((mi >> 1) * 8 + r) * 16;
#pragma unroll
      for (int i = 0; i < 4; i++) kb[i] = lds64(aK + ((warp ^ i) >> 1) * 512 + ((warp ^ i) & 1) * 8);
      const uint32_t aH = sb + C_S + warp * 256 + lane * 8, aR = aH + 1024 + px;
      SCHED(aQ ^ aR, 60);
      bar_sync(BAR_QK, 384);
      ldsm4t(qa[0], aQ + warp * 512); ldsm4t(qa[1], aQ + (warp ^ 1) * 512); ldsm4t(km, aQ + warp * 512 + 256); ldsm4t(qa[2], aQ + (warp ^ 2) * 512); ldsm4t(qa[3], aQ + (warp ^ 3) * 512);
      mma16816z(s0, qa[0], kb[0].x, kb[0].y); mma16816z(s1, qa[1], kb[1].x, kb[1].y);
      mma16816z(s2, qa[0], km[0], km[2]); mma16816z(s3, qa[0], km[1], km[3]);
      mma16816(s0, qa[2], kb[2].x, kb[2].y); mma16816(s1, qa[3], kb[3].x, kb[3].y);
      const uint32_t w0 = pack_bf16((s0[0] + s0[2]) + (s1[0] + s1[2]), (s0[1] + s0[3]) + (s1[1] + s1[3]));
      const uint32_t w1 = pack_bf16((s2[0] + s2[2]) + (s3[0] + s3[2]), (s2[1] + s2[3]) + (s3[1] + s3[3]));
      stasync64(aR, w0, w1, bS + px);
      sts64(aH, w0, w1);
    }
    {
      float sv[10]; uint32_t vx[4][4];
      const uint32_t aVx = kvb + 4096 + (warp >> 1) * 4096 + (warp & 1) * 1024 + lane * 16;
      const uint32_t a8 = sb + lane * 8, av = a8 + C_VP + (warp >> 1) * 2048 + (warp & 1) * 512;
      const uint32_t aO = sb + C_O + ((warp >> 1) * 64 + (warp & 1) * 16 + (mi & 1) * 32 + (mi >> 1) * 8 + r) * 16, aR = sb + C_R + (lane & 28);
#pragma unroll
      for (int i = 0; i < 4; i++) { const uint4 t = lds128(aVx + (i & 1) * 2048 + (i >> 1) * 512); vx[i][0] = t.x; vx[i][1] = t.z; vx[i][2] = t.y; vx[i][3] = t.w; }
      bar_sync(BAR_X, 128);
      { uint2 t[4];
#pragma unroll
        for (int u = 0; u < 4; u++) t[u] = lds64(a8 + C_S + u * 256);
#pragma unroll
        for (int u = 0; u < 4; u++) { sv[2 * u] = bf_lo(t[u].x); sv[2 * u + 1] = bf_hi(t[u].x); }
        sv[8] = (bf_lo(t[0].y) + bf_lo(t[1].y)) + (bf_lo(t[2].y) + bf_lo(t[3].y));
        sv[9] = (bf_hi(t[0].y) + bf_hi(t[1].y)) + (bf_hi(t[2].y) + bf_hi(t[3].y)); }
      mbar_wait(bS, ph);
      { uint2 t[4];
#pragma unroll
        for (int u = 0; u < 4; u++) t[u] = lds64(a8 + C_S + 1024 + u * 256);
#pragma unroll
        for (int u = 0; u < 4; u++) { sv[2 * u] += bf_lo(t[u].x); sv[2 * u + 1] += bf_hi(t[u].x); }
        sv[8] = (sv[8] + bf_lo(t[0].y) + bf_lo(t[1].y)) + (bf_lo(t[2].y) + bf_lo(t[3].y));
        sv[9] = (sv[9] + bf_hi(t[0].y) + bf_hi(t[1].y)) + (bf_hi(t[2].y) + bf_hi(t[3].y)); }
      float mx = fmaxf(fmaxf(fmaxf(sv[0], sv[1]), fmaxf(sv[2], sv[3])), fmaxf(fmaxf(sv[4], sv[5]), fmaxf(sv[6], sv[7])));
      mx = fmaxf(mx, fmaxf(sv[8], sv[9]));
      const float m1 = __shfl_xor_sync(~0u, mx, 1), m2 = __shfl_xor_sync(~0u, mx, 2), m3 = __shfl_xor_sync(~0u, mx, 3);
      mbar_wait(bV, ph);
      const uint2 n00 = lds64(av), n01 = lds64(av + 256), n10 = lds64(av + 1024), n11 = lds64(av + 1280);
      mx = fmaxf(fmaxf(mx, m1), fmaxf(m2, m3));
      const float mo = -mx * SM_SCALE;
      float o0[4], o1[4];
#pragma unroll
      for (int i = 0; i < 4; i++) sv[i] = ex2(fmaf(sv[i], SM_SCALE, mo));
      { const uint32_t p0 = pack_bf16(sv[0], sv[1]), p1 = pack_bf16(sv[2], sv[3]); mma16816z(o0, vx[0], p0, p1); mma16816z(o1, vx[2], p0, p1); }
#pragma unroll
      for (int i = 4; i < 10; i++) sv[i] = ex2(fmaf(sv[i], SM_SCALE, mo));
      { const uint32_t p0 = pack_bf16(sv[4], sv[5]), p1 = pack_bf16(sv[6], sv[7]); mma16816(o0, vx[1], p0, p1); mma16816(o1, vx[3], p0, p1); }
      { const uint32_t p = pack_bf16(sv[8], sv[9]); const uint32_t a0[4] = {n00.x, n10.x, n01.x, n11.x}, a1[4] = {n00.y, n10.y, n01.y, n11.y};
        mma16816(o0, a0, p, p); mma16816(o1, a1, p, p); }
      float su = ((sv[8] + sv[9]) + ((sv[0] + sv[1]) + (sv[2] + sv[3]))) + ((sv[4] + sv[5]) + (sv[6] + sv[7]));
      { const float a1 = __shfl_xor_sync(~0u, su, 1), a2 = __shfl_xor_sync(~0u, su, 2), a3 = __shfl_xor_sync(~0u, su, 3); su = (su + a1) + (a2 + a3); }
      sts32(aR, __float_as_uint(su));
      stsm4(aO, pack_bf16(o0[0], o0[1]), pack_bf16(o0[2], o0[3]), pack_bf16(o1[0], o1[1]), pack_bf16(o1[2], o1[3]));
      bar_sync(BAR_O, 384);
    }
    lane = launder(lane0);
    const uint32_t t0 = lds32(sb + C_R + 48), tag = (s + args.layer + 1) & 1, tm = 0u - tag;
    if (warp == 3) {
      if (lane == 0) { flag_add(args.flags + F_KM + s * 32 + h); if (!ph && s < 61) flag_wait(args.flags + F_KV + ((s + 2) >> 1) * 32 + h, 2); }
      __syncwarp();
      calib();
    } else if (warp != 1 || !(c & 16)) {
      const uint32_t g = lane >> 2, t = lane & 3;
      const char* p = args.comm + (g1page(c >> 1) + (c & 1) * 2048 + (warp == 0 ? 0 : warp == 1 ? 0x30000 : 0x100000) + ((g >> 2) * 4 + t) * 64 + (g & 3) * 16);
      char* g2w = args.comm + (g1page(((t >> 1) + (g >> 2) * 2) * 4 + warp) + G2_OFF + c * 64 + (g & 3) * 16 + (t & 1) * 8);
      const uint32_t one = (g & 1) ? 0x3F800000u : 0x00003F80u, s0 = (g & 2) ? 0u : one, s1 = (g & 2) ? one : 0u;
      int lim = 0; bool bad;
      spin_until(t0 + args.ta[warp]);
      do {
        uint4 a[4]; float z0[4], z1[4], y[4];
#pragma unroll
        for (int i = 0; i < 4; i++) a[i] = ldg_rlx128(p + i * 512);
        ++lim;
        { const uint32_t A[4] = {a[0].x, a[0].y, a[0].z, a[0].w}; mma16816z(z0, A, s0, s1); }
        { const uint32_t A[4] = {a[1].x, a[1].y, a[1].z, a[1].w}; mma16816z(z1, A, s0, s1); }
        { const uint32_t A[4] = {a[2].x, a[2].y, a[2].z, a[2].w}; mma16816(z0, A, s0, s1); }
        { const uint32_t A[4] = {a[3].x, a[3].y, a[3].z, a[3].w}; mma16816(z1, A, s0, s1); }
        const uint32_t m0 = launder((a[0].x ^ tm) | (a[0].z ^ tm)), m1 = launder((a[1].x ^ tm) | (a[1].z ^ tm)), m2 = launder((a[2].x ^ tm) | (a[2].z ^ tm)), m3 = launder((a[3].x ^ tm) | (a[3].z ^ tm));
        bad = __any_sync(~0u, ((launder(m0 | m1 | m2) | m3) & 0x10000u) && lim < POLL_LIMIT);
#pragma unroll
        for (int i = 0; i < 4; i++) { y[i] = z0[i] + z1[i]; y[i] += __shfl_xor_sync(~0u, y[i], 16); }
        const uint32_t w0 = pack_tag(y[0], y[1], tag << 16), w1 = pack_bf16(y[2], y[3]);
        if (!bad) stg_rlx64(g2w, w0, w1);
      } while (bad);
    }
    {
      const bool st2 = warp == 1 || warp == 2; const uint32_t hf = warp >> 1;
      const char* p = args.comm + (g1page((h & 3) * 4 + (st2 ? 2 : 1)) + G2_OFF + hf * 2048 + lane * 16);
      const uint32_t aMw = sb + C_M + (st2 ? 3072 : 2048) + hf * 5120 + (lane >> 4) * 256 + (lane & 15) * 8;
      int lim = 0; bool bad;
      spin_until(t0 + args.tb[st2 ? 2 : 1]);
      if (st2) {
        do { uint4 a[4]; uint32_t m = 0; ++lim;
#pragma unroll
          for (int i = 0; i < 4; i++) a[i] = ldg_rlx128(p + i * 512);
#pragma unroll
          for (int i = 0; i < 4; i++) { sts64(aMw + i * 512, a[i].x, a[i].z); sts64(aMw + i * 512 + 128, a[i].y, a[i].w); m |= (a[i].x ^ tm) | (a[i].z ^ tm); }
          bad = __any_sync(~0u, (m & 0x10000u) && lim < POLL_LIMIT);
        } while (bad);
        bar_arrive(BAR_M2, 352);
      } else {
        do { uint4 a[2]; uint32_t m = 0; ++lim;
#pragma unroll
          for (int i = 0; i < 2; i++) a[i] = ldg_rlx128(p + i * 512);
#pragma unroll
          for (int i = 0; i < 2; i++) { sts64(aMw + i * 512, a[i].x, a[i].z); sts64(aMw + i * 512 + 128, a[i].y, a[i].w); m |= (a[i].x ^ tm) | (a[i].z ^ tm); }
          bad = __any_sync(~0u, (m & 0x10000u) && lim < POLL_LIMIT);
        } while (bad);
        bar_arrive(BAR_M1, 320);
      }
    }
  }
}

constexpr int G_ST = 163840;
constexpr int B_FULL = 64, B_EMPTY = 96, B_WF = 128, B_WD = 136, B_ROLE = 144;
enum { BAR_T = 1  , BAR_G = 3   };
DEVINL uint64_t mkdesc(uint32_t a, uint32_t lbo, uint32_t sbo, uint32_t sw) { return (uint64_t)((a & 0x3FFFF) >> 4) | ((uint64_t)(lbo >> 4) << 16) | ((uint64_t)(sbo >> 4) << 32) | ((uint64_t)sw << 62); }
DEVINL void wgmma_n128(float* d, uint64_t a, uint64_t b, int acc) {
  asm volatile("{.reg .pred p; setp.ne.b32 p, %66, 0; wgmma.mma_async.sync.aligned.m64n128k16.f32.bf16.bf16 {%0,%1,%2,%3,%4,%5,%6,%7,%8,%9,%10,%11,%12,%13,%14,%15,%16,%17,%18,%19,%20,%21,%22,%23,%24,%25,%26,%27,%28,%29,%30,%31,%32,%33,%34,%35,%36,%37,%38,%39,%40,%41,%42,%43,%44,%45,%46,%47,%48,%49,%50,%51,%52,%53,%54,%55,%56,%57,%58,%59,%60,%61,%62,%63}, %64, %65, p, 1, 1, 0, 1;}"
               : "+f"(d[0]),"+f"(d[1]),"+f"(d[2]),"+f"(d[3]),"+f"(d[4]),"+f"(d[5]),"+f"(d[6]),"+f"(d[7]),"+f"(d[8]),"+f"(d[9]),"+f"(d[10]),"+f"(d[11]),"+f"(d[12]),"+f"(d[13]),"+f"(d[14]),"+f"(d[15]),"+f"(d[16]),"+f"(d[17]),"+f"(d[18]),"+f"(d[19]),"+f"(d[20]),"+f"(d[21]),"+f"(d[22]),"+f"(d[23]),"+f"(d[24]),"+f"(d[25]),"+f"(d[26]),"+f"(d[27]),"+f"(d[28]),"+f"(d[29]),"+f"(d[30]),"+f"(d[31]),"+f"(d[32]),"+f"(d[33]),"+f"(d[34]),"+f"(d[35]),"+f"(d[36]),"+f"(d[37]),"+f"(d[38]),"+f"(d[39]),"+f"(d[40]),"+f"(d[41]),"+f"(d[42]),"+f"(d[43]),"+f"(d[44]),"+f"(d[45]),"+f"(d[46]),"+f"(d[47]),"+f"(d[48]),"+f"(d[49]),"+f"(d[50]),"+f"(d[51]),"+f"(d[52]),"+f"(d[53]),"+f"(d[54]),"+f"(d[55]),"+f"(d[56]),"+f"(d[57]),"+f"(d[58]),"+f"(d[59]),"+f"(d[60]),"+f"(d[61]),"+f"(d[62]),"+f"(d[63]) : "l"(a), "l"(b), "r"(acc));
}
DEVINL void wgmma_n80(float* d, uint64_t a, uint64_t b, int acc) {
  asm volatile("{.reg .pred p; setp.ne.b32 p, %42, 0; wgmma.mma_async.sync.aligned.m64n80k16.f32.bf16.bf16 {%0,%1,%2,%3,%4,%5,%6,%7,%8,%9,%10,%11,%12,%13,%14,%15,%16,%17,%18,%19,%20,%21,%22,%23,%24,%25,%26,%27,%28,%29,%30,%31,%32,%33,%34,%35,%36,%37,%38,%39}, %40, %41, p, 1, 1, 0, 1;}"
               : "+f"(d[0]),"+f"(d[1]),"+f"(d[2]),"+f"(d[3]),"+f"(d[4]),"+f"(d[5]),"+f"(d[6]),"+f"(d[7]),"+f"(d[8]),"+f"(d[9]),"+f"(d[10]),"+f"(d[11]),"+f"(d[12]),"+f"(d[13]),"+f"(d[14]),"+f"(d[15]),"+f"(d[16]),"+f"(d[17]),"+f"(d[18]),"+f"(d[19]),"+f"(d[20]),"+f"(d[21]),"+f"(d[22]),"+f"(d[23]),"+f"(d[24]),"+f"(d[25]),"+f"(d[26]),"+f"(d[27]),"+f"(d[28]),"+f"(d[29]),"+f"(d[30]),"+f"(d[31]),"+f"(d[32]),"+f"(d[33]),"+f"(d[34]),"+f"(d[35]),"+f"(d[36]),"+f"(d[37]),"+f"(d[38]),"+f"(d[39]) : "l"(a), "l"(b), "r"(acc));
}

template <int N, int NST>
DEVINL void gemm_tile(float* acc, uint32_t sb, uint32_t px, int wg, uint32_t u0) {
  const uint64_t db = N == 128 ? mkdesc(sb, 81920, 1024, 1) : mkdesc(sb, 32768, 256, 3);
  const bool lead = (threadIdx.x & 127) == 0;
  bar_sync(BAR_T + wg, 256);
#pragma unroll 1
  for (int st = 0; st < NST; st++) {
    const uint32_t u = u0 + st, slot = u & 3;
    mbar_wait(sb + S_BAR + B_FULL + slot * 8, (u >> 2) & 1);
    const uint64_t da = mkdesc(sb + G_ST + slot * 16384, 16, 1024, 1);
    asm volatile("wgmma.fence.sync.aligned;" ::: "memory");
#pragma unroll
    for (int k = 0; k < 8; k++) {
      const uint64_t a = da + (k >> 2) * 512 + (k & 3) * 2;
      if (N == 128) wgmma_n128(acc, a, db + (uint32_t)(st * 8 + k) * 128, st | k); else wgmma_n80(acc, a, db + (uint32_t)(st * 8 + k) * 32, st | k);
    }
    asm volatile("wgmma.commit_group.sync.aligned;" ::: "memory");
    if (st == NST - 1) bar_arrive(BAR_T + (wg ^ 1), 256);
    if (st > 0) {
      asm volatile("wgmma.wait_group.sync.aligned 1;" ::: "memory");
      if (lead) { const uint32_t e = sb + S_BAR + B_EMPTY + ((u - 1) & 3) * 8; mbar_arrive(e); mbar_arrive_remote(e + px); }
    }
  }
  asm volatile("wgmma.wait_group.sync.aligned 0;" ::: "memory");
  if (lead) { const uint32_t e = sb + S_BAR + B_EMPTY + ((u0 + NST - 1) & 3) * 8; mbar_arrive(e); mbar_arrive_remote(e + px); }
}
DEVINL void wg_publish(int wg, uint32_t* flag) { bar_sync(BAR_G + wg, 128); if ((threadIdx.x & 127) == 0) flag_add(flag); }

template <int HF>
DEVINL void attend(const float* acc, const uint4 (*kf)[4], const char* kvp, const char* mp, bf16* orow, int lane) {
  constexpr int NT = HF ? 4 : 2;
  const int g = lane >> 2, t = lane & 3;
  uint4 kmf[4]; uint32_t vm[16];
#pragma unroll
  for (int G = 0; G < 4; G++) kmf[G] = ldg_cg128(mp + G * 512 + lane * 16);
  const int e0 = 8 * (g >> 1) + (g & 1);
#pragma unroll
  for (int i = 0; i < 16; i++) vm[i] = ldg_cg32(mp + 2048 + (e0 + (i >> 2) * 32 + (i & 3) * 2) * 16 + t * 4);
  uint32_t qa[8][4];
#pragma unroll
  for (int k = 0; k < 8; k++)
#pragma unroll
    for (int i = 0; i < 4; i++) qa[k][i] = pack_bf16(acc[8 * k + 2 * i], acc[8 * k + 2 * i + 1]);
  uint4 vf[2][8];
  const char* vp = kvp + 8192 + (g >> 1) * 512 + ((g & 1) * 4 + t) * 16;
#pragma unroll
  for (int i = 0; i < 8; i++) vf[0][i] = ldg_cg128(vp + (i >> 2) * 4096 + (i & 3) * 128);
  float sc[NT + 1][4];
#pragma unroll
  for (int G = 0; G < 4; G++)
#pragma unroll
    for (int kt = 0; kt < NT; kt++) {
      if (G == 0) mma16816z(sc[kt], qa[0], kf[kt][0].x, kf[kt][0].y); else mma16816(sc[kt], qa[2 * G], kf[kt][G].x, kf[kt][G].y);
      mma16816(sc[kt], qa[2 * G + 1], kf[kt][G].z, kf[kt][G].w);
    }
  if (HF) {
#pragma unroll
    for (int i = 0; i < 8; i++) vf[1][i] = ldg_cg128(vp + 2048 + (i >> 2) * 4096 + (i & 3) * 128);
  }
#pragma unroll
  for (int G = 0; G < 4; G++) {
    if (G == 0) mma16816z(sc[NT], qa[0], kmf[0].x, kmf[0].y); else mma16816(sc[NT], qa[2 * G], kmf[G].x, kmf[G].y);
    mma16816(sc[NT], qa[2 * G + 1], kmf[G].z, kmf[G].w);
  }
  const float NINF = __int_as_float(0xff800000);
  if (2 * t > g) { sc[NT - 2][0] = NINF; sc[NT - 1][2] = NINF; }
  if (2 * t + 1 > g) { sc[NT - 2][1] = NINF; sc[NT - 1][3] = NINF; }
  sc[NT - 1][0] = NINF; sc[NT - 1][1] = NINF;
  float m0 = fmaxf(sc[NT][0], sc[NT][1]), m1 = fmaxf(sc[NT][2], sc[NT][3]);
#pragma unroll
  for (int kt = 0; kt < NT; kt++) { m0 = fmaxf(m0, fmaxf(sc[kt][0], sc[kt][1])); m1 = fmaxf(m1, fmaxf(sc[kt][2], sc[kt][3])); }
  m0 = fmaxf(m0, __shfl_xor_sync(~0u, m0, 1)); m1 = fmaxf(m1, __shfl_xor_sync(~0u, m1, 1));
  m0 = fmaxf(m0, __shfl_xor_sync(~0u, m0, 2)); m1 = fmaxf(m1, __shfl_xor_sync(~0u, m1, 2));
  m0 *= -SM_SCALE; m1 *= -SM_SCALE;
  float s0 = 0.f, s1 = 0.f; uint32_t p[NT + 1][2];
#pragma unroll
  for (int kt = 0; kt <= NT; kt++) {
    const float a = ex2(fmaf(sc[kt][0], SM_SCALE, m0)), b = ex2(fmaf(sc[kt][1], SM_SCALE, m0)), c = ex2(fmaf(sc[kt][2], SM_SCALE, m1)), d = ex2(fmaf(sc[kt][3], SM_SCALE, m1));
    s0 += a + b; s1 += c + d; p[kt][0] = pack_bf16(a, b); p[kt][1] = pack_bf16(c, d);
  }
  s0 += __shfl_xor_sync(~0u, s0, 1); s1 += __shfl_xor_sync(~0u, s1, 1);
  s0 += __shfl_xor_sync(~0u, s0, 2); s1 += __shfl_xor_sync(~0u, s1, 2);
  s0 = 1.f / s0; s1 = 1.f / s1;
#pragma unroll
  for (int grp = 0; grp < 4; grp++) {
    float o[4][4];
#pragma unroll
    for (int L = 0; L < 4; L++) {
      mma1688z(o[L], p[NT][0], p[NT][1], vm[grp * 4 + L]);
#pragma unroll
      for (int kh = 0; kh <= HF; kh++) {
        const uint4 w = vf[kh][(grp >> 1) * 4 + L]; const uint32_t A[4] = {p[2 * kh][0], p[2 * kh][1], p[2 * kh + 1][0], p[2 * kh + 1][1]};
        if (grp & 1) mma16816(o[L], A, w.z, w.w); else mma16816(o[L], A, w.x, w.y);
      }
    }
    *(uint4*)(orow + grp * 32) = make_uint4(pack_bf16(o[0][0] * s0, o[0][1] * s0), pack_bf16(o[1][0] * s0, o[1][1] * s0), pack_bf16(o[2][0] * s0, o[2][1] * s0), pack_bf16(o[3][0] * s0, o[3][1] * s0));
    *(uint4*)(orow + 8 * 4096 + grp * 32) = make_uint4(pack_bf16(o[0][2] * s1, o[0][3] * s1), pack_bf16(o[1][2] * s1, o[1][3] * s1), pack_bf16(o[2][2] * s1, o[2][3] * s1), pack_bf16(o[3][2] * s1, o[3][3] * s1));
  }
}

DEVINL void gemm_consumer(uint32_t sb, uint32_t px, int wg, int pr, int rank, const ArgsA& args) {
  const int lane = threadIdx.x & 31, w = __shfl_sync(~0u, (threadIdx.x >> 5) & 3, 0);
  if (wg == 1) bar_arrive(BAR_T, 256);
  mbar_wait(sb + S_BAR + B_WF, 0);
#pragma unroll 1
  for (int tile = wg; tile < 32; tile += 2) {
    float acc[64];
    gemm_tile<128, 5>(acc, sb, px, wg, tile * 5);
    if (tile >= 30 && (threadIdx.x & 127) == 0) mbar_arrive(sb + S_BAR + B_WD);
    char* dst = g_kv + (size_t)((tile * 2 + (w >> 1)) * 32 + pr) * 16384 + (w & 1) * 2048 + lane * 16;
    if (rank == 0) {
#pragma unroll
      for (int G = 0; G < 4; G++)
#pragma unroll
        for (int hh = 0; hh < 2; hh++) {
          const float* a = acc + 16 * G + 2 * hh;
          *(uint4*)(dst + (G >> 1) * 4096 + hh * 1024 + (G & 1) * 512) = make_uint4(pack_bf16(a[0], a[1]), pack_bf16(a[4], a[5]), pack_bf16(a[8], a[9]), pack_bf16(a[12], a[13]));
        }
    } else {
#pragma unroll
      for (int i = 0; i < 8; i++) {
        const float* a = acc + (i >> 2) * 32 + (i & 3) * 4;
        *(uint4*)(dst + 8192 + (i >> 2) * 4096 + (i & 3) * 512) = make_uint4(movm(pack_bf16(a[0], a[1])), movm(pack_bf16(a[2], a[3])), movm(pack_bf16(a[16], a[17])), movm(pack_bf16(a[18], a[19])));
      }
    }
    wg_publish(wg, args.flags + F_KV + tile * 32 + pr);
  }
  mbar_wait(sb + S_BAR + B_WF, 1);
  if (pr < 16) {
    const int h = 2 * pr + rank;
#pragma unroll 1
    for (int tile = wg; tile < 32; tile += 2) {
      const int seg = tile * 2 + (w >> 1);
      const char* kvp = g_kv + (size_t)(seg * 32 + h) * 16384;
      if (lane == 0) flag_wait(args.flags + F_KV + tile * 32 + h, 2);
      __syncwarp();
      uint4 kf[4][4];
#pragma unroll
      for (int kt = 0; kt < 4; kt++)
#pragma unroll
        for (int G = 0; G < 4; G++) if (kt < 2 || (w & 1)) kf[kt][G] = ldg_cg128(kvp + (G >> 1) * 4096 + kt * 1024 + (G & 1) * 512 + lane * 16);
      asm volatile("prefetch.global.L2 [%0];" ::"l"(kvp + 8192 + (w & 1) * 4096 + lane * 128));
      float acc[64];
      gemm_tile<128, 5>(acc, sb, px, wg, 160 + tile * 5);
      if (lane == 0) flag_wait(args.flags + F_KM + seg * 32 + h, 2);
      __syncwarp();
      const char* mp = g_kvm + (size_t)(seg * 32 + h) * 4096;
      bf16* orow = g_o + (size_t)(tile * 64 + w * 16 + (lane >> 2)) * 4096 + h * 128 + (lane & 3) * 8;
      if (w & 1) attend<1>(acc, kf, kvp, mp, orow, lane); else attend<0>(acc, kf, kvp, mp, orow, lane);
      wg_publish(wg, args.flags + F_O + tile * 4 + (h >> 3));
    }
  } else {
    const int kq = (pr - 16) >> 2, cg = 2 * (pr & 3) + rank;
#pragma unroll 1
    for (int tile = wg; tile < 32; tile += 2) {
      float acc[40];
      gemm_tile<80, 8>(acc, sb, px, wg, 160 + tile * 8);
      const bool odd = lane & 1;
      bf16* dst = g_part + (size_t)(kq * 2048 + tile * 64 + w * 16 + (lane >> 2)) * 640 + cg * 80 + (lane & 1) * 8 + (lane & 2) * 2;
#pragma unroll
      for (int q = 0; q < 5; q++)
#pragma unroll
        for (int hh = 0; hh < 2; hh++) {
          const uint32_t A = pack_bf16(acc[8 * q + 2 * hh], acc[8 * q + 2 * hh + 1]), B = pack_bf16(acc[8 * q + 4 + 2 * hh], acc[8 * q + 5 + 2 * hh]);
          const uint32_t x = __shfl_xor_sync(~0u, odd ? A : B, 1);
          *(uint2*)(dst + hh * 8 * 640 + q * 16) = odd ? make_uint2(x, B) : make_uint2(A, x);
        }
    }
  }
  if (wg == 0) bar_sync(BAR_T, 256);
}

DEVINL void gemm_producer(uint32_t sb, int pr, int rank, const ArgsA& args, const CUtensorMap* tq, const CUtensorMap* tk, const CUtensorMap* tv,
                          const CUtensorMap* to32, const CUtensorMap* tx, const CUtensorMap* tao) {
  const uint32_t bWF = sb + S_BAR + B_WF;
  auto load_w = [&](const CUtensorMap* tm, int col) { mbar_arrive_tx(bWF, 163840);
#pragma unroll 1
    for (int i = 0; i < 20; i++) tma_2d(sb + (i & 1) * 81920 + (i >> 1) * 8192, tm, col + (i & 1) * 64, (i >> 1) * 64, bWF); };
  uint32_t u = 0;
  auto push = [&](const CUtensorMap* tm, int c0, int c1) {
    const uint32_t slot = u & 3, full = sb + S_BAR + B_FULL + slot * 8;
    mbar_wait(sb + S_BAR + B_EMPTY + slot * 8, ((u >> 2) & 1) ^ 1);
    mbar_arrive_tx(full, 16384);
    tma_2d_mc(sb + G_ST + slot * 16384 + rank * 8192, tm, c0 + rank * 64, c1, full);
    u++; };
  load_w(rank ? tv : tk, pr * 128);
#pragma unroll 1
  for (int tile = 0; tile < 32; tile++)
#pragma unroll 1
    for (int st = 0; st < 5; st++) push(tx, st * 128, tile * 64);
  mbar_wait(sb + S_BAR + B_WD, 0);
  if (pr < 16) {
    load_w(tq, (2 * pr + rank) * 128);
#pragma unroll 1
    for (int tile = 0; tile < 32; tile++)
#pragma unroll 1
      for (int st = 0; st < 5; st++) push(tx, st * 128, tile * 64);
  } else {
    const int kq = (pr - 16) >> 2, cg = 2 * (pr & 3) + rank;
    mbar_arrive_tx(bWF, 163840);
#pragma unroll 1
    for (int i = 0; i < 20; i++) tma_2d(sb + (i % 5) * 32768 + (i / 5) * 8192, to32, cg * 80 + (i % 5) * 16, kq * 1024 + (i / 5) * 256, bWF);
#pragma unroll 1
    for (int tile = 0; tile < 32; tile++) {
      flag_wait(args.flags + F_O + tile * 4 + kq, 8);
      fence_proxy_async();
#pragma unroll 1
      for (int st = 0; st < 8; st++) push(tao, kq * 1024 + st * 128, tile * 64);
    }
  }
#pragma unroll 1
  for (int i = 0; i < 4; i++, u++) mbar_wait(sb + S_BAR + B_EMPTY + (u & 3) * 8, ((u >> 2) & 1) ^ 1);
}

DEVINL void filter_prep(uint32_t* sm, int part, const ArgsA& args) {
  const int tid = threadIdx.x;
  const unsigned short* wr = (const unsigned short*)args.wr; const unsigned short* wi = (const unsigned short*)args.wi;
#pragma unroll 1
  for (int it = part; it < 32; it += 4) {
#pragma unroll 4
    for (int i = tid; i < 64 * 321; i += 256) {
      const int pl = i / 321, col = i - pl * 321, pos = it * 64 + pl;
      const int q = pos >> 9, th = (pos >> 2) & 127, v = q * 4 + (pos & 3);
      const int uu = (th >> 3) + 16 * ((th & 7) + (v & 8)) + 256 * (v & 7);
      sm[col * 65 + pl] = (uint32_t)wr[uu * 321 + col] | ((uint32_t)wi[uu * 321 + col] << 16);
    }
    bar_sync(1, 256);
#pragma unroll 4
    for (int i = tid; i < 64 * 321; i += 256) g_wt[(i >> 6) * 2048 + it * 64 + (i & 63)] = sm[(i >> 6) * 65 + (i & 63)];
    bar_sync(1, 256);
  }
}

__global__ void __cluster_dims__(2, 1, 1) __launch_bounds__(384, 1)
layer_a_kernel(const __grid_constant__ CUtensorMap tq, const __grid_constant__ CUtensorMap tk, const __grid_constant__ CUtensorMap tv,
               const __grid_constant__ CUtensorMap to, const __grid_constant__ CUtensorMap to32, const __grid_constant__ CUtensorMap tx,
               const __grid_constant__ CUtensorMap tao, const __grid_constant__ ArgsA args) {
  extern __shared__ __align__(1024) char smraw[];
  const uint32_t sb = (smem_u32(smraw) + 1023) & ~1023u;
  uint32_t rank; asm volatile("mov.u32 %0, %%cluster_ctarank;" : "=r"(rank));
  const uint32_t px = mapa(sb, rank ^ 1) - sb;
  pdl_wait();
  if (threadIdx.x == 0) {
    const uint32_t b = sb + S_BAR;
    mbar_init(b + B_W, 1); mbar_init(b + B_S, 1); mbar_init(b + B_V, 9); mbar_init(b + B_KV, 1); mbar_init(b + B_KV + 8, 1);
    for (int i = 0; i < 4; i++) { mbar_init(b + B_FULL + i * 8, 1); mbar_init(b + B_EMPTY + i * 8, 2); }
    mbar_init(b + B_WF, 1); mbar_init(b + B_WD, 2);
    asm volatile("fence.mbarrier_init.release.cluster;" ::: "memory");
    if (rank == 0) {
      uint32_t smid; asm volatile("mov.u32 %0, %%smid;" : "=r"(smid));
      uint32_t* cnt = args.flags + F_ROLE; uint32_t role;
      if (g_side[smid & 255] == 0) { role = atomicAdd(cnt, 1); if (role >= 32) role = 32 + atomicAdd(cnt + 32, 1); }
      else { role = 32 + atomicAdd(cnt + 32, 1); if (role >= 66) role = atomicAdd(cnt, 1); }
      sts32(b + B_ROLE, role);
    }
  }
  __syncthreads();
  cluster_sync();
  uint32_t role; asm volatile("ld.shared::cluster.u32 %0, [%1];" : "=r"(role) : "r"(sb + S_BAR + B_ROLE + (rank ? px : 0)) : "memory");
  role = __shfl_sync(~0u, role, 0);
  if (role >= 64) cluster_sync();
  const int wg = __shfl_sync(~0u, threadIdx.x >> 7, 0);
  if (wg == 2) {
    asm volatile("setmaxnreg.dec.sync.aligned.u32 56;");
    if (role < 32) chain_helper(sb, px, role, rank, args, &tq, &tk, &tv, &to);
    else if (role < 64) { if (threadIdx.x == 256) gemm_producer(sb, role - 32, rank, args, &tq, &tk, &tv, &to32, &tx, &tao); }
  } else {
    asm volatile("setmaxnreg.inc.sync.aligned.u32 224;");
    if (role < 32) { if (wg == 0) chain_mma<0>(sb, px, role, rank, args); else chain_mma<1>(sb, px, role, rank, args); }
    else if (role < 64) gemm_consumer(sb, px, wg, role - 32, rank, args);
    else if (args.layer == 0) filter_prep((uint32_t*)smraw, (role - 64) * 2 + rank, args);
  }
}

DEVINL float2 cadd(float2 a, float2 b) { return make_float2(a.x + b.x, a.y + b.y); }
DEVINL float2 csub(float2 a, float2 b) { return make_float2(a.x - b.x, a.y - b.y); }
DEVINL float2 cmul(float2 a, float2 b) { return make_float2(fmaf(a.x, b.x, -a.y * b.y), fmaf(a.x, b.y, a.y * b.x)); }
DEVINL float2 cmulc(float2 a, float2 b) { return make_float2(fmaf(a.x, b.x, a.y * b.y), fmaf(a.y, b.x, -a.x * b.y)); }
template <int INV> DEVINL float2 ctw(float2 a, float2 w) { return INV ? cmulc(a, w) : cmul(a, w); }
template <int INV> DEVINL float2 rot(float2 a) { return INV ? make_float2(-a.y, a.x) : make_float2(a.y, -a.x); }
template <int INV> DEVINL void fft4(float2& a, float2& b, float2& c, float2& d) {
  const float2 s0 = cadd(a, c), d0 = csub(a, c), s1 = cadd(b, d), d1 = rot<INV>(csub(b, d));
  a = cadd(s0, s1); b = cadd(d0, d1); c = csub(s0, s1); d = csub(d0, d1);
}
template <int INV> DEVINL float2 w8(float2 a) { const float h = 0.70710678118654752f; const float2 r = rot<INV>(a); return make_float2((a.x + r.x) * h, (a.y + r.y) * h); }
template <int INV> DEVINL void fft8(float2* x) {
  fft4<INV>(x[0], x[2], x[4], x[6]); fft4<INV>(x[1], x[3], x[5], x[7]);
  const float2 e0 = x[0], e1 = x[2], e2 = x[4], e3 = x[6], o0 = x[1], o1 = w8<INV>(x[3]), o2 = rot<INV>(x[5]), o3 = rot<INV>(w8<INV>(x[7]));
  x[0] = cadd(e0, o0); x[1] = cadd(e1, o1); x[2] = cadd(e2, o2); x[3] = cadd(e3, o3);
  x[4] = csub(e0, o0); x[5] = csub(e1, o1); x[6] = csub(e2, o2); x[7] = csub(e3, o3);
}
template <int INV> DEVINL void fft16(float2* x) {
  const float c = 0.92387953251128674f, s = 0.38268343236508977f;
  const float2 w1 = make_float2(c, -s), w3 = make_float2(s, -c);
#pragma unroll
  for (int i = 0; i < 4; i++) fft4<INV>(x[i], x[i + 4], x[i + 8], x[i + 12]);
  x[5] = ctw<INV>(x[5], w1); x[9] = w8<INV>(x[9]); x[13] = ctw<INV>(x[13], w3);
  x[6] = w8<INV>(x[6]); x[10] = rot<INV>(x[10]); x[14] = rot<INV>(w8<INV>(x[14]));
  x[7] = ctw<INV>(x[7], w3); x[11] = rot<INV>(w8<INV>(x[11])); x[15] = ctw<INV>(x[15], make_float2(-c, s));
#pragma unroll
  for (int k = 0; k < 4; k++) fft4<INV>(x[4 * k], x[4 * k + 1], x[4 * k + 2], x[4 * k + 3]);
#pragma unroll
  for (int k = 0; k < 4; k++)
#pragma unroll
    for (int m = k + 1; m < 4; m++) { const float2 t = x[4 * k + m]; x[4 * k + m] = x[4 * m + k]; x[4 * m + k] = t; }
}
template <int INV> DEVINL void fft5(float2& x0, float2& x1, float2& x2, float2& x3, float2& x4) {
  const float c1 = 0.30901699437494742f, c2 = -0.80901699437494742f, s1 = 0.95105651629515357f, s2 = 0.58778525229247313f;
  const float2 a1 = cadd(x1, x4), a2 = cadd(x2, x3), b1 = rot<INV>(csub(x1, x4)), b2 = rot<INV>(csub(x2, x3));
  const float2 p1 = make_float2(fmaf(c1, a1.x, fmaf(c2, a2.x, x0.x)), fmaf(c1, a1.y, fmaf(c2, a2.y, x0.y)));
  const float2 p2 = make_float2(fmaf(c2, a1.x, fmaf(c1, a2.x, x0.x)), fmaf(c2, a1.y, fmaf(c1, a2.y, x0.y)));
  const float2 q1 = make_float2(fmaf(s1, b1.x, s2 * b2.x), fmaf(s1, b1.y, s2 * b2.y));
  const float2 q2 = make_float2(fmaf(s2, b1.x, -s1 * b2.x), fmaf(s2, b1.y, -s1 * b2.y));
  x0 = cadd(x0, cadd(a1, a2)); x1 = cadd(p1, q1); x4 = csub(p1, q1); x2 = cadd(p2, q2); x3 = csub(p2, q2);
}
template <int INV> DEVINL void fft20(const float2* in, float2* out) {
  float2 t[4][5];
#pragma unroll
  for (int a = 0; a < 4; a++) {
#pragma unroll
    for (int b = 0; b < 5; b++) t[a][b] = in[(5 * a + 4 * b) % 20];
    fft5<INV>(t[a][0], t[a][1], t[a][2], t[a][3], t[a][4]);
  }
#pragma unroll
  for (int d = 0; d < 5; d++) {
    fft4<INV>(t[0][d], t[1][d], t[2][d], t[3][d]);
#pragma unroll
    for (int c = 0; c < 4; c++) out[(5 * c + 16 * d) % 20] = t[c][d];
  }
}
DEVINL void unpack8(uint4 v, float* f) { f[0] = bf_lo(v.x); f[1] = bf_hi(v.x); f[2] = bf_lo(v.y); f[3] = bf_hi(v.y); f[4] = bf_lo(v.z); f[5] = bf_hi(v.z); f[6] = bf_lo(v.w); f[7] = bf_hi(v.w); }
DEVINL uint4 pack8(const float* f) { return make_uint4(pack_bf16(f[0], f[1]), pack_bf16(f[2], f[3]), pack_bf16(f[4], f[5]), pack_bf16(f[6], f[7])); }
DEVINL void ln_row(float* f) {
  float s = 0.f;
#pragma unroll
  for (int i = 0; i < 40; i++) s += f[i];
#pragma unroll
  for (int o = 1; o < 16; o <<= 1) s += __shfl_xor_sync(~0u, s, o);
  const float mean = s * (1.f / 640.f); float q = 0.f;
#pragma unroll
  for (int i = 0; i < 40; i++) { f[i] -= mean; q = fmaf(f[i], f[i], q); }
#pragma unroll
  for (int o = 1; o < 16; o <<= 1) q += __shfl_xor_sync(~0u, q, o);
  const float rs = rsqrtf(q * (1.f / 640.f) + 1e-5f);
#pragma unroll
  for (int i = 0; i < 40; i++) f[i] *= rs;
}
constexpr int ZP = 336;
struct RowSmem { float2 T[320 * 17]; uint32_t Z[16 * ZP]; float2 tw[320]; float2 tp[160]; };
DEVINL void row_tables(RowSmem& sm) {
  const int t = threadIdx.x; float s, c;
  sincospif(-(float)((t >> 4) * (t & 15)) * (1.f / 160.f), &s, &c); sm.tw[t] = make_float2(c, s);
  if (t < 160) { sincospif(-(float)t * (1.f / 320.f), &s, &c); sm.tp[t] = make_float2(c, s); }
}

__global__ void __launch_bounds__(320) rows_fwd_kernel(const bf16* __restrict__ xin) {
  extern __shared__ __align__(1024) char smraw[]; RowSmem& sm = *(RowSmem*)smraw;
  const int tid = threadIdx.x, s0 = blockIdx.x * 16;
  row_tables(sm);
  pdl_wait();
  pdl_launch();
  if (tid < 256) {
    const int row = tid >> 4, j = tid & 15; const size_t off = (size_t)(s0 + row) * 640 + j * 8;
    float f[40];
#pragma unroll
    for (int i = 0; i < 5; i++) {
      float a[8], b[8], c[8], d[8], x[8];
      unpack8(ldg_cg128(g_part + off + i * 128), a); unpack8(ldg_cg128(g_part + 2048 * 640 + off + i * 128), b);
      unpack8(ldg_cg128(g_part + 2 * 2048 * 640 + off + i * 128), c); unpack8(ldg_cg128(g_part + 3 * 2048 * 640 + off + i * 128), d);
      unpack8(ldg_cg128(xin + off + i * 128), x);
#pragma unroll
      for (int e = 0; e < 8; e++) a[e] = (a[e] + b[e]) + (c[e] + d[e]);
      unpack8(pack8(a), a);
#pragma unroll
      for (int e = 0; e < 8; e++) a[e] += x[e];
      const uint4 r = pack8(a); *(uint4*)(g_x + off + i * 128) = r; unpack8(r, f + 8 * i);
    }
    ln_row(f);
#pragma unroll
    for (int i = 0; i < 5; i++) *(uint4*)(sm.Z + row * ZP + i * 64 + j * 4) = pack8(f + 8 * i);
  }
  __syncthreads();
  if (tid < 256) {
    const int row = tid >> 4, n2 = tid & 15;
    float2 z[20], y[20];
#pragma unroll
    for (int n1 = 0; n1 < 20; n1++) { const uint32_t w = sm.Z[row * ZP + n1 * 16 + n2]; z[n1] = make_float2(bf_lo(w), bf_hi(w)); }
    fft20<0>(z, y);
#pragma unroll
    for (int k1 = 0; k1 < 20; k1++) sm.T[(k1 * 16 + n2) * 17 + row] = k1 ? cmul(y[k1], sm.tw[k1 * 16 + n2]) : y[0];
  }
  __syncthreads();
  const int wp = tid >> 5, up = (tid >> 4) & 1, row = tid & 15, k1 = wp ? (up ? 20 - wp : wp) : up * 10;
  float2 x[16];
#pragma unroll
  for (int n2 = 0; n2 < 16; n2++) x[n2] = sm.T[(k1 * 16 + n2) * 17 + row];
  fft16<0>(x);
  uint32_t* y = g_y + s0 + row;
#pragma unroll
  for (int k2 = 0; k2 < 8; k2++) {
    float2 b;
    if (wp) { b.x = __shfl_xor_sync(~0u, x[15 - k2].x, 16); b.y = __shfl_xor_sync(~0u, x[15 - k2].y, 16); }
    else b = up ? x[15 - k2] : x[(16 - k2) & 15];
    const int k = k1 + 20 * k2; const float2 a = x[k2];
    const float2 E = make_float2(a.x + b.x, a.y - b.y), O = cmul(make_float2(a.y + b.y, b.x - a.x), sm.tp[k]);
    if (k2 == 0 && k1 == 0) { y[0] = pack_f16(E.x + O.x, E.x - O.x); y[160 * 2048] = pack_f16(2.f * x[8].x, -2.f * x[8].y); }
    else { y[k * 2048] = pack_f16(E.x + O.x, E.y + O.y); y[(320 - k) * 2048] = pack_f16(E.x - O.x, O.y - E.y); }
  }
}

__global__ void __launch_bounds__(128) cols_kernel() {
  __shared__ float2 sm[16 * 152];
  const int tid = threadIdx.x, col = blockIdx.x, k1 = tid >> 3, j0 = tid & 7;
  pdl_wait();
  pdl_launch();
  uint32_t* y = g_y + (col == 320 ? 0 : col) * 2048 + tid;
  float2 x[16];
  if (col == 0 || col == 320) {
#pragma unroll
    for (int i = 0; i < 16; i++) x[i] = make_float2(__half2float(((const __half*)(y + i * 128))[col ? 1 : 0]), 0.f);
  } else {
#pragma unroll
    for (int i = 0; i < 16; i++) { const uint32_t w = ldg_cg32(y + i * 128); x[i] = __half22float2(*(const __half2*)&w); }
  }
  uint4 wf[4];
#pragma unroll
  for (int q = 0; q < 4; q++) wf[q] = ldg_cg128(g_wt + col * 2048 + q * 512 + tid * 4);
  fft16<0>(x);
#pragma unroll
  for (int k = 0; k < 16; k++) sm[k * 152 + tid] = k ? cmul(x[k], g_tw[(k - 1) * 128 + tid]) : x[0];
  __syncthreads();
  float2* reg = sm + k1 * 152;
#pragma unroll
  for (int i = 0; i < 16; i++) x[i] = reg[j0 + 8 * i];
  fft16<0>(x);
  __syncwarp();
#pragma unroll
  for (int k = 0; k < 16; k++) reg[k * 9 + j0] = k ? cmul(x[k], g_tw[1920 + (k - 1) * 8 + j0]) : x[0];
  __syncwarp();
#pragma unroll
  for (int i = 0; i < 16; i++) x[i] = reg[(j0 + (i & 8)) * 9 + (i & 7)];
  fft8<0>(x); fft8<0>(x + 8);
#pragma unroll
  for (int q = 0; q < 4; q++) {
    const uint32_t w[4] = {wf[q].x, wf[q].y, wf[q].z, wf[q].w};
#pragma unroll
    for (int r = 0; r < 4; r++) x[4 * q + r] = cmul(x[4 * q + r], make_float2(bf_lo(w[r]), bf_hi(w[r])));
  }
  fft8<1>(x); fft8<1>(x + 8);
#pragma unroll
  for (int i = 0; i < 16; i++) reg[(j0 + (i & 8)) * 9 + (i & 7)] = x[i];
  __syncwarp();
#pragma unroll
  for (int k = 0; k < 16; k++) x[k] = k ? cmulc(reg[k * 9 + j0], g_tw[1920 + (k - 1) * 8 + j0]) : reg[j0];
  fft16<1>(x);
  __syncwarp();
#pragma unroll
  for (int i = 0; i < 16; i++) reg[j0 + 8 * i] = x[i];
  __syncthreads();
#pragma unroll
  for (int k = 0; k < 16; k++) x[k] = k ? cmulc(sm[k * 152 + tid], g_tw[(k - 1) * 128 + tid]) : sm[tid];
  fft16<1>(x);
  const float sc = 1.f / 4096.f;
  if (col == 0 || col == 320) {
#pragma unroll
    for (int i = 0; i < 16; i++) ((bf16*)(y + i * 128))[col ? 1 : 0] = __float2bfloat16(x[i].x * sc);
  } else {
#pragma unroll
    for (int i = 0; i < 16; i++) y[i * 128] = pack_bf16(x[i].x * sc, x[i].y * sc);
  }
}

__global__ void __launch_bounds__(320) rows_inv_kernel(bf16* __restrict__ xout, int do_ln) {
  extern __shared__ __align__(1024) char smraw[]; RowSmem& sm = *(RowSmem*)smraw;
  const int tid = threadIdx.x, s0 = blockIdx.x * 16;
  row_tables(sm);
  __syncthreads();
  pdl_wait();
  pdl_launch();
  const size_t off = (size_t)(s0 + ((tid >> 4) & 15)) * 640 + (tid & 15) * 8;
  uint4 xr[5];
  {
    const int wp = tid >> 5, up = (tid >> 4) & 1, row = tid & 15, k1 = wp ? (up ? 20 - wp : wp) : up * 10;
    const uint32_t* y = g_y + s0 + row;
    uint32_t wa[8], wb[8];
#pragma unroll
    for (int k2 = 0; k2 < 8; k2++) { const int k = k1 + 20 * k2; wa[k2] = ldg_cg32(y + k * 2048); wb[k2] = ldg_cg32(y + (k ? 320 - k : 160) * 2048); }
    if (tid < 256) {
#pragma unroll
      for (int i = 0; i < 5; i++) xr[i] = ldg_cg128(g_x + off + i * 128);
    }
    float2 x[16], r[8];
#pragma unroll
    for (int k2 = 0; k2 < 8; k2++) {
      const float2 a = make_float2(bf_lo(wa[k2]), bf_hi(wa[k2])), b = make_float2(bf_lo(wb[k2]), bf_hi(wb[k2]));
      const float2 E = make_float2(a.x + b.x, a.y - b.y), O = cmulc(make_float2(a.x - b.x, a.y + b.y), sm.tp[k1 + 20 * k2]);
      x[k2] = make_float2(E.x - O.y, E.y + O.x); r[k2] = make_float2(E.x + O.y, O.x - E.y);
      if (k2 == 0 && k1 == 0) { x[0] = make_float2(a.x + a.y, a.x - a.y); r[0] = make_float2(2.f * b.x, -2.f * b.y); }
    }
#pragma unroll
    for (int i = 8; i < 16; i++) {
      if (wp) { x[i].x = __shfl_xor_sync(~0u, r[15 - i].x, 16); x[i].y = __shfl_xor_sync(~0u, r[15 - i].y, 16); }
      else x[i] = up ? r[15 - i] : r[(16 - i) & 7];
    }
    fft16<1>(x);
#pragma unroll
    for (int n2 = 0; n2 < 16; n2++) sm.T[(k1 * 16 + n2) * 17 + row] = x[n2];
  }
  __syncthreads();
  if (tid >= 256) return;
  const int row = tid >> 4, n2 = tid & 15;
  {
    float2 z[20], y[20];
#pragma unroll
    for (int k1 = 0; k1 < 20; k1++) { const float2 t = sm.T[(k1 * 16 + n2) * 17 + row]; z[k1] = k1 ? cmulc(t, sm.tw[k1 * 16 + n2]) : t; }
    fft20<1>(z, y);
    const float sc = 1.f / 640.f;
#pragma unroll
    for (int n1 = 0; n1 < 20; n1++) sm.Z[row * ZP + n1 * 16 + n2] = pack_bf16(y[n1].x * sc, y[n1].y * sc);
  }
  __syncwarp();
  float f[40];
#pragma unroll
  for (int i = 0; i < 5; i++) {
    float a[8], x[8]; unpack8(*(const uint4*)(sm.Z + row * ZP + i * 64 + n2 * 4), a); unpack8(xr[i], x);
#pragma unroll
    for (int e = 0; e < 8; e++) a[e] += x[e];
    const uint4 r = pack8(a); *(uint4*)(xout + off + i * 128) = r; unpack8(r, f + 8 * i);
  }
  if (do_ln) {
    ln_row(f);
#pragma unroll
    for (int i = 0; i < 5; i++) *(uint4*)(g_xn + off + i * 128) = pack8(f + 8 * i);
  }
}

__global__ void __launch_bounds__(320) prep_kernel(const bf16* __restrict__ x, char* comm, const char* wq, const char* wk, const char* wv, const char* wo) {
  extern __shared__ __align__(1024) char smraw[];
  const int tid = threadIdx.x, b = blockIdx.x;
  pdl_launch();
  if (tid >= 256) {
    uint32_t smid; asm volatile("mov.u32 %0, %%smid;" : "=r"(smid));
    volatile uint32_t* res = (volatile uint32_t*)smraw;
    if ((tid & 31) == 0) {
      uint32_t* p = (uint32_t*)(comm + 0x20000 + ((smid & 128) << 7) + (tid == 256 ? 0x1000 : 0) + (smid & 127) * 32);
      uint32_t v, best = ~0u;
      asm volatile("atom.relaxed.gpu.global.exch.b32 %0, [%1], 0;" : "=r"(v) : "l"(p) : "memory"); res[2] = v;
#pragma unroll 1
      for (int i = 0; i < 4; i++) { const uint32_t t0 = clk(); asm volatile("atom.relaxed.gpu.global.add.u32 %0, [%1], 1;" : "=r"(v) : "l"(p) : "memory"); res[2] = v; best = min(best, clk() - t0); }
      res[(tid >> 5) & 1] = best;
    }
    bar_sync(1, 64);
    if (tid == 256) g_side[smid & 255] = res[0] > res[1];
    return;
  }
  if (b < 128) {
    if (tid < 40) { const char* w = (tid < 10 ? wk : tid < 20 ? wq : tid < 30 ? wv : wo) + (size_t)b * 40960 + (tid % 10) * 4096;
      asm volatile("cp.async.bulk.prefetch.L2.global [%0], 4096;" ::"l"(w) : "memory"); }
    const size_t off = (size_t)(b * 16 + (tid >> 4)) * 640 + (tid & 15) * 8;
    float f[40];
#pragma unroll
    for (int i = 0; i < 5; i++) unpack8(*(const uint4*)(x + off + i * 128), f + 8 * i);
    *(uint4*)(comm + g1page(b & 31) + (b < 32 ? 0 : b < 64 ? 0x30000 : b < 96 ? 0x100000 : G2_OFF) + tid * 16) = make_uint4(0, 0, 0, 0);
    ln_row(f);
#pragma unroll
    for (int i = 0; i < 5; i++) *(uint4*)(g_xn + off + i * 128) = pack8(f + 8 * i);
  } else {
    for (int i = (b - 128) * 256 + tid; i < 2 * F_LAYER; i += 1024) g_flags[i] = 0;
    for (int i = (b - 128) * 256 + tid; i < 2040; i += 1024) {
      float s, c;
      if (i < 1920) sincospif(-(float)((i / 128 + 1) * (i & 127)) * (1.f / 1024.f), &s, &c);
      else sincospif(-(float)(((i - 1920) / 8 + 1) * (i & 7)) * (1.f / 64.f), &s, &c);
      g_tw[i] = make_float2(c, s);
    }
    if (b == 128 && tid < 64) *(uint32_t*)(comm + TS_OFF + tid * 4) = 0;
  }
}

typedef CUresult (*EncFn)(CUtensorMap*, CUtensorMapDataType, cuuint32_t, void*, const cuuint64_t*, const cuuint64_t*, const cuuint32_t*, const cuuint32_t*,
                          CUtensorMapInterleave, CUtensorMapSwizzle, CUtensorMapL2promotion, CUtensorMapFloatOOBfill);
static void make_map(EncFn fn, CUtensorMap* m, const void* p, uint64_t cols, uint64_t rows, uint32_t bc, uint32_t br, CUtensorMapSwizzle sw) {
  cuuint64_t gd[2] = {cols, rows}, gs[1] = {cols * 2}; cuuint32_t bd[2] = {bc, br}, es[2] = {1, 1};
  fn(m, CU_TENSOR_MAP_DATA_TYPE_BFLOAT16, 2, (void*)p, gd, gs, bd, es, CU_TENSOR_MAP_INTERLEAVE_NONE, sw, CU_TENSOR_MAP_L2_PROMOTION_L2_128B, CU_TENSOR_MAP_FLOAT_OOB_FILL_NONE);
}
template <class... P, class... A>
static void launch(void (*k)(P...), int grid, int block, int smem, bool pdl, A... a) {
  cudaLaunchConfig_t cfg = {}; cfg.gridDim = dim3(grid); cfg.blockDim = dim3(block); cfg.dynamicSmemBytes = smem; cfg.stream = cudaStreamPerThread;
  cudaLaunchAttribute at[1]; at[0].id = cudaLaunchAttributeProgrammaticStreamSerialization; at[0].val.programmaticStreamSerializationAllowed = 1;
  cfg.attrs = at; cfg.numAttrs = pdl ? 1 : 0;
  cudaLaunchKernelEx(&cfg, k, a...);
}
static const int tune_t[6] = {1800, 2050, 2350, 2550, 2800, 3000}; constexpr int dev_stop = 100, dev_pdl = 1;

extern "C" void kernel_launch(void* const* d_in, const int* in_sizes, int n_in, void* d_out, int out_size) {
  const bf16 *x = (const bf16*)d_in[0], *mem0 = (const bf16*)d_in[1], *Wq = (const bf16*)d_in[2], *Wk = (const bf16*)d_in[3], *Wv = (const bf16*)d_in[4], *Wo = (const bf16*)d_in[5];
  const bf16 *wr = (const bf16*)d_in[8], *wi = (const bf16*)d_in[9];
  constexpr int SM_A = S_END + 1024, SM_R = sizeof(RowSmem), SM_P = 120 * 1024;
  void *p_xn, *p_o, *p_x, *p_comm, *p_flags, *fn; cudaDriverEntryPointQueryResult qr;
  cudaGetSymbolAddress(&p_xn, g_xn); cudaGetSymbolAddress(&p_o, g_o); cudaGetSymbolAddress(&p_x, g_x); cudaGetSymbolAddress(&p_comm, g_comm); cudaGetSymbolAddress(&p_flags, g_flags);
  cudaGetDriverEntryPoint("cuTensorMapEncodeTiled", &fn, cudaEnableDefault, &qr);
  cudaFuncSetAttribute(layer_a_kernel, cudaFuncAttributeMaxDynamicSharedMemorySize, SM_A);
  cudaFuncSetAttribute(rows_fwd_kernel, cudaFuncAttributeMaxDynamicSharedMemorySize, SM_R);
  cudaFuncSetAttribute(rows_inv_kernel, cudaFuncAttributeMaxDynamicSharedMemorySize, SM_R);
  cudaFuncSetAttribute(prep_kernel, cudaFuncAttributeMaxDynamicSharedMemorySize, SM_P);
  CUtensorMap tq, tk, tv, to, to32, tx, tao; EncFn enc = (EncFn)fn;
  make_map(enc, &tq, Wq, 4096, 640, 64, 64, CU_TENSOR_MAP_SWIZZLE_128B); make_map(enc, &tk, Wk, 4096, 640, 64, 64, CU_TENSOR_MAP_SWIZZLE_128B);
  make_map(enc, &tv, Wv, 4096, 640, 64, 64, CU_TENSOR_MAP_SWIZZLE_128B); make_map(enc, &to, Wo, 640, 4096, 64, 64, CU_TENSOR_MAP_SWIZZLE_128B);
  make_map(enc, &to32, Wo, 640, 4096, 16, 256, CU_TENSOR_MAP_SWIZZLE_32B);
  make_map(enc, &tx, p_xn, 640, 2048, 64, 64, CU_TENSOR_MAP_SWIZZLE_128B); make_map(enc, &tao, p_o, 4096, 2048, 64, 64, CU_TENSOR_MAP_SWIZZLE_128B);
  char* comm = (char*)(((uintptr_t)p_comm + (2 << 20) - 1) & ~(uintptr_t)((2 << 20) - 1));
  const bool pdl = dev_pdl;
  launch(prep_kernel, 132, 320, SM_P, false, x, comm, (const char*)Wq, (const char*)Wk, (const char*)Wv, (const char*)Wo);
  for (int l = 0; l < 2; l++) {
    ArgsA a{mem0, comm, (uint32_t*)p_flags + l * F_LAYER, wr, wi, l, {tune_t[0], tune_t[1], tune_t[2]}, {tune_t[3], tune_t[4], tune_t[5]}};
    if (dev_stop > 4 * l + 0) launch(layer_a_kernel, 132, 384, SM_A, pdl, tq, tk, tv, to, to32, tx, tao, a);
    if (dev_stop > 4 * l + 1) launch(rows_fwd_kernel, 128, 320, SM_R, pdl, l ? (const bf16*)p_x : x);
    if (dev_stop > 4 * l + 2) launch(cols_kernel, 321, 128, 0, pdl);
    if (dev_stop > 4 * l + 3) launch(rows_inv_kernel, 128, 320, SM_R, pdl, l ? (bf16*)d_out : (bf16*)p_x, l == 0);
  }
}
```

```cpp
#include <cuda_runtime.h>
#include <cuda_bf16.h>
#include <cuda_fp16.h>
#include <cuda.h>
#include <stdint.h>

typedef __nv_bfloat16 bf16;
#define DEVINL __device__ __forceinline__

__device__ __align__(1024) bf16 g_xn[2048 * 640];
__device__ __align__(1024) bf16 g_x[2048 * 640];
__device__ __align__(1024) char g_kv[64 * 32 * 16384];
__device__ __align__(1024) char g_kvm[64 * 32 * 4096];
__device__ __align__(1024) bf16 g_o[2048 * 4096];
__device__ __align__(1024) bf16 g_part[4 * 2048 * 640];
__device__ __align__(1024) uint32_t g_y[320 * 2048];
__device__ __align__(1024) uint32_t g_wt[321 * 2048];
__device__ __align__(1024) float2 g_tw[15 * 128 + 15 * 8];
__device__ __align__(4096) char g_comm[4 << 20];
constexpr int F_KV = 0, F_KM = 1024, F_O = F_KM + 1024, F_ROLE = F_O + 128, F_LAYER = F_ROLE + 64;
__device__ __align__(1024) uint32_t g_flags[2 * F_LAYER];
__device__ int g_side[256];

#define POLL_LIMIT (1 << 17)
DEVINL uint32_t smem_u32(const void* p) { return (uint32_t)__cvta_generic_to_shared(p); }
DEVINL uint32_t mapa(uint32_t a, uint32_t r) { uint32_t o; asm volatile("mapa.shared::cluster.u32 %0, %1, %2;" : "=r"(o) : "r"(a), "r"(r)); return o; }
DEVINL uint32_t clk() { uint32_t v; asm volatile("{.reg .b64 w; mov.u64 w, %%clock64; cvt.u32.u64 %0, w;}" : "=r"(v)::"memory"); return v; }
DEVINL void mbar_init(uint32_t bar, uint32_t cnt) { asm volatile("mbarrier.init.shared::cta.b64 [%0], %1;" ::"r"(bar), "r"(cnt) : "memory"); }
DEVINL void mbar_arrive(uint32_t bar) { asm volatile("mbarrier.arrive.shared::cta.b64 _, [%0];" ::"r"(bar) : "memory"); }
DEVINL void mbar_arrive_remote(uint32_t bar) { asm volatile("mbarrier.arrive.shared::cluster.b64 _, [%0];" ::"r"(bar) : "memory"); }
DEVINL void mbar_arrive_tx(uint32_t bar, uint32_t tx) { asm volatile("mbarrier.arrive.expect_tx.shared::cta.b64 _, [%0], %1;" ::"r"(bar), "r"(tx) : "memory"); }
DEVINL void mbar_wait(uint32_t bar, uint32_t ph) {
  asm volatile("{.reg .pred p,q; .reg .b32 c; mov.b32 c, 0;\n"
               "W0: add.u32 c,c,1; setp.lt.u32 q,c,0x100000; mbarrier.try_wait.parity.shared::cta.b64 p, [%0], %1; not.pred p,p; and.pred p,p,q; @p bra W0;}" ::"r"(bar), "r"(ph) : "memory");
}
DEVINL void bar_sync(int id, int n) { asm volatile("bar.sync %0, %1;" ::"r"(id), "r"(n) : "memory"); }
DEVINL void bar_arrive(int id, int n) { asm volatile("bar.arrive %0, %1;" ::"r"(id), "r"(n) : "memory"); }
DEVINL void cluster_sync() { asm volatile("barrier.cluster.arrive.release.aligned; barrier.cluster.wait.acquire.aligned;" ::: "memory"); }
DEVINL void tma_2d(uint32_t dst, const CUtensorMap* tm, int c0, int c1, uint32_t bar) {
  asm volatile("cp.async.bulk.tensor.2d.shared::cluster.global.mbarrier::complete_tx::bytes [%0], [%1, {%2, %3}], [%4];" ::"r"(dst), "l"(tm), "r"(c0), "r"(c1), "r"(bar) : "memory");
}
DEVINL void tma_2d_mc(uint32_t dst, const CUtensorMap* tm, int c0, int c1, uint32_t bar) {
  asm volatile("cp.async.bulk.tensor.2d.shared::cluster.global.mbarrier::complete_tx::bytes.multicast::cluster [%0], [%1, {%2, %3}], [%4], %5;" ::"r"(dst), "l"(tm), "r"(c0), "r"(c1), "r"(bar), "h"((uint16_t)3) : "memory");
}
DEVINL void bulk_g2s(uint32_t dst, const void* src, uint32_t bytes, uint32_t bar) {
  asm volatile("cp.async.bulk.shared::cluster.global.mbarrier::complete_tx::bytes [%0], [%1], %2, [%3];" ::"r"(dst), "l"(src), "r"(bytes), "r"(bar) : "memory");
}
DEVINL void l2_prefetch(const void* p, uint32_t bytes) { asm volatile("cp.async.bulk.prefetch.L2.global [%0], %1;" ::"l"(p), "r"(bytes) : "memory"); }
DEVINL void fence_proxy_async() { asm volatile("fence.proxy.async;" ::: "memory"); }
DEVINL void ldsm4t(uint32_t* r, uint32_t a) { asm volatile("ldmatrix.sync.aligned.m8n8.x4.trans.shared.b16 {%0,%1,%2,%3}, [%4];" : "=r"(r[0]), "=r"(r[1]), "=r"(r[2]), "=r"(r[3]) : "r"(a) : "memory"); }
DEVINL void stsm4(uint32_t a, uint32_t r0, uint32_t r1, uint32_t r2, uint32_t r3) { asm volatile("stmatrix.sync.aligned.m8n8.x4.shared.b16 [%0], {%1,%2,%3,%4};" ::"r"(a), "r"(r0), "r"(r1), "r"(r2), "r"(r3) : "memory"); }
DEVINL void mma16816(float* d, const uint32_t* a, uint32_t b0, uint32_t b1) {
  asm volatile("mma.sync.aligned.m16n8k16.row.col.f32.bf16.bf16.f32 {%0,%1,%2,%3}, {%4,%5,%6,%7}, {%8,%9}, {%0,%1,%2,%3};"
               : "+f"(d[0]), "+f"(d[1]), "+f"(d[2]), "+f"(d[3]) : "r"(a[0]), "r"(a[1]), "r"(a[2]), "r"(a[3]), "r"(b0), "r"(b1));
}
DEVINL void mma16816z(float* d, const uint32_t* a, uint32_t b0, uint32_t b1) {
  asm volatile("mma.sync.aligned.m16n8k16.row.col.f32.bf16.bf16.f32 {%0,%1,%2,%3}, {%4,%5,%6,%7}, {%8,%9}, {%10,%10,%10,%10};"
               : "=f"(d[0]), "=f"(d[1]), "=f"(d[2]), "=f"(d[3]) : "r"(a[0]), "r"(a[1]), "r"(a[2]), "r"(a[3]), "r"(b0), "r"(b1), "f"(0.f));
}
DEVINL void mma1688z(float* d, uint32_t a0, uint32_t a1, uint32_t b0) {
  asm volatile("mma.sync.aligned.m16n8k8.row.col.f32.bf16.bf16.f32 {%0,%1,%2,%3}, {%4,%5}, {%6}, {%7,%7,%7,%7};"
               : "=f"(d[0]), "=f"(d[1]), "=f"(d[2]), "=f"(d[3]) : "r"(a0), "r"(a1), "r"(b0), "f"(0.f));
}
DEVINL uint32_t movm(uint32_t a) { uint32_t r; asm volatile("movmatrix.sync.aligned.m8n8.trans.b16 %0, %1;" : "=r"(r) : "r"(a)); return r; }
DEVINL uint32_t pack_bf16(float lo, float hi) { uint32_t r; asm("cvt.rn.bf16x2.f32 %0, %1, %2;" : "=r"(r) : "f"(hi), "f"(lo)); return r; }
DEVINL uint32_t pack_f16(float lo, float hi) { uint32_t r; asm("cvt.rn.f16x2.f32 %0, %1, %2;" : "=r"(r) : "f"(hi), "f"(lo)); return r; }
DEVINL float bf_lo(uint32_t w) { return __uint_as_float(w << 16); }
DEVINL float bf_hi(uint32_t w) { return __uint_as_float(w & 0xffff0000u); }
DEVINL uint32_t hadd2bf(uint32_t a, uint32_t b) { uint32_t r; asm("add.rn.bf16x2 %0, %1, %2;" : "=r"(r) : "r"(a), "r"(b)); return r; }
DEVINL uint32_t hmax2bf(uint32_t a, uint32_t b) { uint32_t r; asm("max.bf16x2 %0, %1, %2;" : "=r"(r) : "r"(a), "r"(b)); return r; }
DEVINL uint32_t lds32(uint32_t a) { uint32_t v; asm volatile("ld.shared.u32 %0, [%1];" : "=r"(v) : "r"(a) : "memory"); return v; }
DEVINL uint2 lds64(uint32_t a) { uint2 v; asm volatile("ld.shared.v2.u32 {%0,%1}, [%2];" : "=r"(v.x), "=r"(v.y) : "r"(a) : "memory"); return v; }
DEVINL uint4 lds128(uint32_t a) { uint4 v; asm volatile("ld.shared.v4.u32 {%0,%1,%2,%3}, [%4];" : "=r"(v.x), "=r"(v.y), "=r"(v.z), "=r"(v.w) : "r"(a) : "memory"); return v; }
DEVINL void sts32(uint32_t a, uint32_t v) { asm volatile("st.shared.u32 [%0], %1;" ::"r"(a), "r"(v) : "memory"); }
DEVINL void sts64(uint32_t a, uint32_t x, uint32_t y) { asm volatile("st.shared.v2.u32 [%0], {%1,%2};" ::"r"(a), "r"(x), "r"(y) : "memory"); }
DEVINL void sts128(uint32_t a, uint4 v) { asm volatile("st.shared.v4.u32 [%0], {%1,%2,%3,%4};" ::"r"(a), "r"(v.x), "r"(v.y), "r"(v.z), "r"(v.w) : "memory"); }
DEVINL void stasync64(uint32_t a, uint32_t x, uint32_t y, uint32_t bar) { asm volatile("st.async.weak.shared::cluster.mbarrier::complete_tx::bytes.v2.b32 [%0], {%1,%2}, [%3];" ::"r"(a), "r"(x), "r"(y), "r"(bar) : "memory"); }
DEVINL uint4 ldg_rlx128(const void* p) { uint4 v; asm volatile("{.reg .b64 a,b; ld.relaxed.gpu.global.v2.b64 {a,b}, [%4]; mov.b64 {%0,%1}, a; mov.b64 {%2,%3}, b;}" : "=r"(v.x), "=r"(v.y), "=r"(v.z), "=r"(v.w) : "l"(p) : "memory"); return v; }
DEVINL uint2 ldg_rlx64(const void* p) { uint2 v; asm volatile("ld.relaxed.gpu.global.v2.u32 {%0,%1}, [%2];" : "=r"(v.x), "=r"(v.y) : "l"(p) : "memory"); return v; }
DEVINL void stg_rlx64(void* p, uint32_t x, uint32_t y) { asm volatile("{.reg .b64 a; mov.b64 a, {%1,%2}; st.relaxed.gpu.global.b64 [%0], a;}" ::"l"(p), "r"(x), "r"(y) : "memory"); }
DEVINL void stg_rlx32(void* p, uint32_t x) { asm volatile("st.relaxed.gpu.global.u32 [%0], %1;" ::"l"(p), "r"(x) : "memory"); }
DEVINL uint4 ldg_cg128(const void* p) { uint4 v; asm volatile("ld.global.cg.v4.u32 {%0,%1,%2,%3}, [%4];" : "=r"(v.x), "=r"(v.y), "=r"(v.z), "=r"(v.w) : "l"(p) : "memory"); return v; }
DEVINL uint32_t ldg_cg32(const void* p) { uint32_t v; asm volatile("ld.global.cg.u32 %0, [%1];" : "=r"(v) : "l"(p) : "memory"); return v; }
DEVINL uint4 ldg_ca128(const void* p) { uint4 v; asm volatile("ld.global.ca.v4.u32 {%0,%1,%2,%3}, [%4];" : "=r"(v.x), "=r"(v.y), "=r"(v.z), "=r"(v.w) : "l"(p) : "memory"); return v; }
DEVINL uint32_t ldg_ca32(const void* p) { uint32_t v; asm volatile("ld.global.ca.u32 %0, [%1];" : "=r"(v) : "l"(p) : "memory"); return v; }
DEVINL void flag_wait(const uint32_t* p, uint32_t want) {
  uint32_t v; int n = 0;
  do { asm volatile("ld.acquire.gpu.global.u32 %0, [%1];" : "=r"(v) : "l"(p) : "memory"); if (v >= want) break; __nanosleep(40); } while (++n < POLL_LIMIT);
}
DEVINL void flag_wait_warp(const uint32_t* p, uint32_t want) {
  uint32_t v; int n = 0;
  do { asm volatile("ld.acquire.gpu.global.u32 %0, [%1];" : "=r"(v) : "l"(p) : "memory"); } while (__any_sync(~0u, v < want && ++n < POLL_LIMIT));
}
DEVINL void flag_add(uint32_t* p) { asm volatile("fence.acq_rel.gpu; red.relaxed.gpu.global.add.u32 [%0], 1;" ::"l"(p) : "memory"); }
DEVINL void flag_set(uint32_t* p, uint32_t v) { asm volatile("fence.acq_rel.gpu; st.relaxed.gpu.global.u32 [%0], %1;" ::"l"(p), "r"(v) : "memory"); }
DEVINL uint32_t ldg_rlx32(const void* p) { uint32_t v; asm volatile("ld.relaxed.gpu.global.u32 %0, [%1];" : "=r"(v) : "l"(p) : "memory"); return v; }
DEVINL float ex2(float x) { float y; asm("ex2.approx.ftz.f32 %0, %1;" : "=f"(y) : "f"(x)); return y; }
DEVINL float rcp(float x) { float y; asm("rcp.approx.ftz.f32 %0, %1;" : "=f"(y) : "f"(x)); return y; }
DEVINL uint32_t opaque(uint32_t x) { return __shfl_sync(~0u, x, threadIdx.x & 31); }
DEVINL uint32_t launder(uint32_t x) { asm volatile("" : "+r"(x)); return x; }
DEVINL void pdl_wait() { asm volatile("griddepcontrol.wait;" ::: "memory"); }
DEVINL void pdl_launch() { asm volatile("griddepcontrol.launch_dependents;" ::: "memory"); }
#define LOGS(cta, i)
#define LOG(cta, i)
#define LOGV(cta, i, v)
constexpr float SM_SCALE = 0.08838834764831845f * 1.4426950408889634f;

struct ArgsA {
  const bf16* mem0; char* comm; uint32_t* flags; const bf16* wr; const bf16* wi;
  int layer; int ta[3], tb[3];
};

#define VP 4
#define HELD 0x2557
#define PRE 4
#define VPRE 4
#define R0 5
#define TRK 30
#define TEXP 0
#define TRD 0
#define TKV 300
#define W1D 120
constexpr int C_WV = 0;
constexpr int C_WO = 81920;
constexpr int C_KV = 163840;
constexpr int C_M  = C_KV + 24576;
constexpr int C_QK = C_M + 10240;
constexpr int C_VP = C_QK + 4096;
constexpr int C_S  = C_VP + 4096;
constexpr int C_O  = C_S + 2048;
constexpr int C_R  = C_O + 2048;
constexpr int S_BAR = 229376;
constexpr int S_END = S_BAR + 256;
enum { BAR_M1 = 1, BAR_QK = 2, BAR_O = 3, BAR_H = 4, BAR_X = 5, BAR_M2 = 6, BAR_W = 7  , BAR_E = 9 };
constexpr int B_W = 0, B_S = 8, B_KV = 24;
constexpr int G2_OFF = 0x130000, TS_OFF = 0x11000;

#define SCHED(x, c) asm volatile("{.reg .pred p; setp.eq.u32 p, %0, %1; @p exit;}" ::"r"(x), "r"(0x7fff0001u + 2 * (c)) : "memory")
DEVINL uint32_t g1page(uint32_t L) { L = ((L & 7) | ((L & 24) << 2)) << 1; return (L | (__popc(L & 0xb2) & 1)) << 12; }
DEVINL void spin_until(uint32_t t) {
  asm volatile("{.reg .pred p; .reg .b32 c; .reg .b64 w;\nS0: mov.u64 w, %%clock64; cvt.u32.u64 c, w; sub.u32 c, %0, c; setp.lt.u32 p, c, 16384; @p bra S0;}" ::"r"(t) : "memory");
}
DEVINL uint32_t wait_until(uint32_t t, uint32_t z) { uint32_t r;
  asm volatile("{.reg .pred p; .reg .b32 c,x; .reg .b64 w;\nT0: .branchtargets L0, L1, L2, L3, L4, L5, L6, L7, L8, L9, L10;\n"
               "S0: mov.u64 w, %%clock64; cvt.u32.u64 c, w; sub.u32 c, %1, c; sub.u32 x, c, 72; setp.lt.u32 p, x, 16384; @p bra S0;\n"
               "max.s32 c, c, 0; min.s32 c, c, 71; mul.lo.u32 c, c, 37; shr.u32 c, c, 8; mov.u32 x, %2;\nbrx.idx.uni c, T0;\n"
               "L10: mul.lo.u32 x, x, x; L9: mul.lo.u32 x, x, x; L8: mul.lo.u32 x, x, x; L7: mul.lo.u32 x, x, x; L6: mul.lo.u32 x, x, x; L5: mul.lo.u32 x, x, x; L4: mul.lo.u32 x, x, x; L3: mul.lo.u32 x, x, x; L2: mul.lo.u32 x, x, x; L1: mul.lo.u32 x, x, x; L0: mov.u32 %0, x;}" : "=r"(r) : "r"(t), "r"(z) : "memory"); return r;
}
DEVINL void gtime(uint32_t& G16, uint32_t& C) {
  asm volatile("{.reg .b64 w; .reg .b32 g,g0,a;\n mov.u64 w, %%clock64; cvt.u32.u64 %1, w; mov.u64 w, %%globaltimer; cvt.u32.u64 g0, w; mul.lo.u32 a, g0, -8;\n"
               "mov.u64 w, %%globaltimer; cvt.u32.u64 g, w; add.u32 a, a, g; mov.u64 w, %%globaltimer; cvt.u32.u64 g, w; add.u32 a, a, g; mov.u64 w, %%globaltimer; cvt.u32.u64 g, w; add.u32 a, a, g; mov.u64 w, %%globaltimer; cvt.u32.u64 g, w; add.u32 a, a, g; mov.u64 w, %%globaltimer; cvt.u32.u64 g, w; add.u32 a, a, g; mov.u64 w, %%globaltimer; cvt.u32.u64 g, w; add.u32 a, a, g; mov.u64 w, %%globaltimer; cvt.u32.u64 g, w; add.u32 a, a, g; mov.u64 w, %%globaltimer; cvt.u32.u64 g, w; add.u32 a, a, g; \n mul.lo.u32 a, a, 455; shr.u32 a, a, 8; mad.lo.u32 %0, g0, 16, a;}" : "=r"(G16), "=r"(C)::"memory");
}
DEVINL uint32_t pack_tag(float lo, float hi, uint32_t tg) {
  const uint32_t w = pack_bf16(lo, __uint_as_float(tg | 0x3F800000u)), a = __float_as_uint(hi) + (tg ^ 0x10000u); uint32_t r;
  asm("lop3.b32 %0, %1, %2, 0xFFFE0000, 0xE4;" : "=r"(r) : "r"(a), "r"(w)); return r;
}
DEVINL void load_kv(uint32_t sb, int h, int j, int s) {
  asm volatile("{.reg .pred p; elect.sync _|p, 0xffffffff;\n @p mbarrier.arrive.expect_tx.shared::cta.b64 _, [%2], 12288;\n"
               " @p cp.async.bulk.shared::cluster.global.mbarrier::complete_tx::bytes [%0], [%1], 12288, [%2];}"
               ::"r"(sb + C_KV + (s & 1) * 12288), "l"(g_kv + (size_t)(s * 32 + h) * 16384 + j * 4096), "r"(sb + S_BAR + B_KV + (s & 1) * 8) : "memory");
}

template <int KH>
DEVINL void chain_mma(uint32_t sb0, const ArgsA& args) {
  const int lane = threadIdx.x & 31, mg = (threadIdx.x >> 5) & 3, mi = lane >> 3, r = lane & 7;
  const uint32_t aW = opaque(sb0 + (uint32_t)(((mi >> 1) * 8 + r) * 128 + (((mg + 4 * (mi & 1)) ^ r) << 4)));
  const uint32_t aL = opaque(sb0 + lane * 16);
  const uint32_t aLm = opaque(sb0 + mg * 512 + lane * 16);
#define sb (launder(aL) & ~511u)
  constexpr int OV = C_WV + KH * 40960, OM = C_M + KH * 5120, NF = KH ? 16 : 24;
  auto owo = [](int f) { return C_WO + (KH ? 1 + 3 * (f >> 3) : (f < 8 ? 0 : 1 + (f >> 3))) * 16384 + (f & 7) * 2048; };
  auto held = [](int k) { return (HELD >> k) & 1; };
  auto rank = [](int k) { return __popc(HELD & ((1 << k) - 1)); };
  uint32_t wq[20][4], wk[20][4];
  mbar_wait(sb + S_BAR + B_W, 0);
#pragma unroll
  for (int k = 0; k < 20; k++) { ldsm4t(wq[k], aW + OV + k * 2048); ldsm4t(wk[k], aW + C_WO + KH * 40960 + k * 2048); }
  bar_sync(BAR_H, 384);
  mbar_wait(sb + S_BAR + B_W, 1);
#pragma unroll 1
  for (int s = 0;; s++) {
    uint32_t v[20][4], b[10][4];
    if (s == 0) {
#pragma unroll
      for (int k = 0; k < 20; k++) if (held(k)) ldsm4t(v[k], aW + OV + k * 2048);
      ldsm4t(b[0], aL + OM); ldsm4t(b[1], aL + OM + 512);
    } else {
      const uint32_t o = launder(aLm) - sb;
      const char* p = args.comm + (lds32(sb + C_R + 84) + KH * 2048 + o);
      const uint32_t am = sb + OM + (o & 0x400) + ((o & 0x3f0) >> 1), tm = 0u - ((s + args.layer) & 1);
#pragma unroll
      for (int k = 0; k < 20; k++) if (held(k) && rank(k) < VPRE) ldsm4t(v[k], aW + OV + k * 2048);
      p += wait_until(lds32(sb + C_R + 48) + args.tb[0], am & 1);
      uint4 a = ldg_rlx128(p);
#pragma unroll
      for (int k = 0; k < 20; k++) if (held(k) && rank(k) >= VPRE) ldsm4t(v[k], aW + OV + k * 2048);
      SCHED(am ^ tm, 29);
      int lim = 0;
      while (true) {
        sts64(am, a.x, a.z); sts64(am + 512, a.y, a.w);
        uint32_t bad;
        asm volatile("{.reg .pred p,q; setp.ne.u32 q, %1, 0; bar.red.or.pred p, %2, 128, q; selp.u32 %0, 1, 0, p;}" : "=r"(bad) : "r"(((a.x ^ tm) | (a.z ^ tm)) & 0x10000u), "n"(BAR_W + KH) : "memory");
        ldsm4t(b[0], aL + OM); ldsm4t(b[1], aL + OM + 512);
        if (!bad || ++lim >= POLL_LIMIT) break;
        a = ldg_rlx128(p);
      }
    }
    float cq[4], ck[4], cv[4];
#pragma unroll
    for (int k = 0; k < 20; k++) {
      const int p = k >> 1;
      const uint32_t b0 = b[p][(k & 1) * 2], b1 = b[p][(k & 1) * 2 + 1];
      if (k == 0) { mma16816z(cv, v[0], b0, b1); mma16816z(cq, wq[k], b0, b1); mma16816z(ck, wk[k], b0, b1); }
      else { if (k < 20 - VP) mma16816(cv, v[k], b0, b1); mma16816(cq, wq[k], b0, b1); mma16816(ck, wk[k], b0, b1); }
      if (k == 5) bar_sync(BAR_M1, 288);
      if (k == 9) bar_sync(BAR_M2, 384);
      if ((k & 1) && p + 2 < 10) ldsm4t(b[p + 2], aL + OM + (p + 2) * 512);
      if (k + 3 < 20 - VP && !held(k + 3)) ldsm4t(v[k + 3], aW + OV + (k + 3) * 2048);
      if (k >= 20 - VP && k < 20 - VP + PRE && !held(k)) ldsm4t(v[k], aW + OV + k * 2048);
    }
    stsm4(aLm + C_QK + KH * 2048, pack_bf16(cq[0], cq[1]), pack_bf16(cq[2], cq[3]), pack_bf16(ck[0], ck[1]), pack_bf16(ck[2], ck[3]));
    bar_arrive(BAR_QK, 384);
    SCHED(aL, 1);
    const uint32_t l8 = (launder(aL) & 511) >> 1, px = lds32(sb + C_R + 80);
#pragma unroll
    for (int k = 20 - VP + PRE; k < 20; k++) if (!held(k)) ldsm4t(v[k], aW + OV + k * 2048);
#pragma unroll
    for (int k = 20 - VP; k < 20; k++) {
      const int p = k >> 1, q = k - 20 + VP; const uint32_t b0 = b[p][(k & 1) * 2], b1 = b[p][(k & 1) * 2 + 1];
      if (q % 3 == 0) mma16816(cv, v[k], b0, b1); else if (q == 1) mma16816z(cq, v[k], b0, b1); else if (q == 2) mma16816z(ck, v[k], b0, b1);
      else if (q % 3 == 1) mma16816(cq, v[k], b0, b1); else mma16816(ck, v[k], b0, b1);
    }
    if (VP >= 3) {
#pragma unroll
      for (int i = 0; i < 4; i++) cv[i] += cq[i] + ck[i];
    }
    { const uint32_t vx = pack_bf16(cv[0], cv[1]), vy = pack_bf16(cv[2], cv[3]);
      const uint32_t av = aLm - l8 + C_VP + KH * 256;
      stasync64(av + 2048 + px, vx, vy, sb + S_BAR + B_S + px);
      sts64(av, vx, vy);
      __syncwarp();
      if (l8 == 0) mbar_arrive(sb + S_BAR + B_S); }
    if (s == 63) break;
    uint32_t w[NF][4];
    {
      const uint32_t zero = px & 1; uint32_t a = aW;
      if (TRK) spin_until(clk() + TRK);
#pragma unroll
      for (int f = 0; f < 8; f++) { ldsm4t(w[f], a + owo(f)); uint32_t d = w[f][0] & zero;
#pragma unroll
        for (int q = 0; q < TRD; q++) d = __popc(d);
        a = aW + d; }
    }
    const uint32_t tg = ((s + args.layer + 1) & 1) << 16;
    const uint32_t ar = sb + C_R + 128 + (l8 & 120);
    const uint32_t o = launder(aLm) - sb;
    const uint2 jh = lds64(sb + C_R + 88);
    char* g1w = args.comm + (g1page(jh.x + KH * 8 + (o >> 8)) + ((o & 128) << 4) + jh.y + ((o & 112) >> 1));
    bar_sync(BAR_O, 384);
    uint32_t ob[16];
#pragma unroll
    for (int p = 0; p < 4; p++) ldsm4t(ob + 4 * p, aL + C_O + p * 512);
    const uint2 rr = lds64(ar);
    float r0 = __uint_as_float(rr.x), r1 = __uint_as_float(rr.y);
    r0 += __shfl_xor_sync(~0u, r0, 4); r1 += __shfl_xor_sync(~0u, r1, 4); r0 += __shfl_xor_sync(~0u, r0, 8); r1 += __shfl_xor_sync(~0u, r1, 8);
    r0 = rcp(r0); r1 = rcp(r1);
#pragma unroll
    for (int f = 0; f < NF; f++) {
      const int k = f & 7; const uint32_t* A = w[f];
      if (k == 0) mma16816z(cq, A, ob[0], ob[1]); else if (k == 1) mma16816z(ck, A, ob[2], ob[3]);
      else if (k & 1) mma16816(ck, A, ob[2 * k], ob[2 * k + 1]); else mma16816(cq, A, ob[2 * k], ob[2 * k + 1]);
      constexpr int RA = KH ? 0 : R0;
      if (k >= 2 && k < 2 + RA && (f & ~7) + 8 < NF) ldsm4t(w[f + 6], aW + owo(f + 6));
      if (k == 7) {
        stg_rlx64(g1w + (f < 8 ? 0 : (f < 16 && KH == 0) ? 0x30000 : 0x100000), pack_tag((cq[0] + ck[0]) * r0, (cq[1] + ck[1]) * r1, tg), pack_bf16((cq[2] + ck[2]) * r0, (cq[3] + ck[3]) * r1));
        if (KH == 1 && f == 7) spin_until(clk() + W1D); else SCHED(aL, 32 + f);
#pragma unroll
        for (int q = RA; q < 8; q++) if (f + 1 < NF) ldsm4t(w[f + 1 + q], aW + owo(f + 1 + q));
        if (KH == 1 && f == 7) SCHED(aL, 33);
      }
    }
  }
}

#undef sb
DEVINL void chain_helper(uint32_t sb, uint32_t px, int h, int j, const ArgsA& args, const CUtensorMap* tq, const CUtensorMap* tk, const CUtensorMap* tv, const CUtensorMap* to) {
  const int c = 2 * h + j;
  const uint32_t bW = sb + S_BAR + B_W, bS = sb + S_BAR + B_S, bKV = sb + S_BAR + B_KV;
  const uint32_t lane0 = opaque(threadIdx.x & 31);
  const uint32_t warp = __reduce_max_sync(~0u, (threadIdx.x >> 5) & 3);
  uint32_t G0, C0;
  { const int tid = threadIdx.x - 256;
    if (tid == 0) { mbar_arrive_tx(bW, 163840);
#pragma unroll 1
      for (int i = 0; i < 10; i++) { tma_2d(sb + C_WV + i * 8192, tq, h * 128 + j * 64, i * 64, bW); tma_2d(sb + C_WO + i * 8192, tk, h * 128 + j * 64, i * 64, bW); } }
    gtime(G0, C0);
    sts128(sb + C_R + 80, make_uint4(px, g1page((h & 3) * 4) + G2_OFF, j * 16, h * 64));
#pragma unroll
    for (int i = 0; i < 5; i++) { const int q = tid + i * 128, n = q & 7, d0 = (q >> 3) * 8; const uint4 v = *(const uint4*)(args.mem0 + n * 640 + d0); const uint32_t w[4] = {v.x, v.y, v.z, v.w};
#pragma unroll
      for (int e = 0; e < 8; e++) asm volatile("st.shared.u16 [%0], %1;" ::"r"(sb + C_M + (d0 + e) * 16 + n * 2), "h"((unsigned short)(w[e >> 1] >> ((e & 1) * 16))) : "memory"); }
    bar_sync(BAR_H, 384);
    if (tid == 0) { mbar_arrive_tx(bW, 163840);
#pragma unroll 1
      for (int i = 0; i < 10; i++) { tma_2d(sb + C_WV + i * 8192, tv, h * 128 + j * 64, i * 64, bW); tma_2d(sb + C_WO + i * 8192, to, j * 320 + (i >> 1) * 64, h * 128 + ((i & 1) ^ j) * 64, bW); } }
    if (warp == 3) {
      if (tid == 96) LOG(c, 250);
      flag_wait_warp(args.flags + F_KV + h, 2);
      load_kv(sb, h, j, 0); load_kv(sb, h, j, 1); if (tid == 96) LOG(c, 251);
    }
  }
  auto calib = [&]() { uint32_t G, C; gtime(G, C);
    const float rt = (float)(C - C0) * rcp((float)(G - G0));
    sts128(sb + C_R + 32, make_uint4(G, C, __float_as_uint(rt), __float_as_uint(rcp(rt)))); __syncwarp(); };
  auto do_export = [&](int s, uint32_t lane, bool arrive) {
    uint32_t k0[2][4], k1[2][4]; uint2 a[4], b[4];
    const uint32_t ak = sb + C_QK + 256 + (lane >> 4) * 512 + (lane & 15) * 16, av = sb + C_VP + lane * 8;
#pragma unroll
    for (int i = 0; i < 2; i++) { ldsm4t(k0[i], ak + i * 1024); ldsm4t(k1[i], ak + i * 1024 + 2048); }
#pragma unroll
    for (int i = 0; i < 4; i++) { a[i] = lds64(av + i * 512); b[i] = lds64(av + i * 512 + 256); }
    char* dst = g_kvm + ((s * 32 + h) * 4096 + j * 1024);
#pragma unroll
    for (int i = 0; i < 2; i++) *(uint4*)(dst + i * 512 + lane * 16) = make_uint4(hadd2bf(k0[i][0], k1[i][0]), hadd2bf(k0[i][1], k1[i][1]), hadd2bf(k0[i][2], k1[i][2]), hadd2bf(k0[i][3], k1[i][3]));
#pragma unroll
    for (int i = 0; i < 4; i++) { uint32_t* q = (uint32_t*)(dst + 2048 + i * 128) + lane; q[0] = hadd2bf(a[i].x, b[i].x); q[128] = hadd2bf(a[i].y, b[i].y); }
    if (arrive) bar_arrive(BAR_M2, 384);
    __syncwarp();
  };
  if (warp == 0) { calib(); bar_arrive(BAR_M1, 288); } else bar_arrive(BAR_M2, 384);
#pragma unroll 1
  for (int s = 0;; s++) {
    const uint32_t ph = s & 1, kvb = sb + C_KV + ph * 12288;
    uint32_t lane = __shfl_sync(~0u, lane0, lane0);
    if (warp == 0) {
      if (lane == 0) mbar_arrive_tx(bS, s < 63 ? 3072 : 2048);
      const uint4 cal = lds128(sb + C_R + 32);
      bar_sync(BAR_M2, 384);
      sts32(sb + C_R + 52, 0);
      const uint32_t E = clk();
      if (lane == 0) { const uint32_t e16 = cal.x + (uint32_t)__float2int_rn((float)(int)(E - cal.y) * __uint_as_float(cal.w));
        stg_rlx32(args.comm + TS_OFF + c * 4, e16); sts128(sb + C_R + 64, make_uint4(e16, E, cal.z, 0)); }
      __syncwarp();
    }
    if (s == 63) { bar_sync(BAR_QK, 384); mbar_wait(bS, 1); if (warp == 3) { do_export(63, lane, false); flag_set(args.flags + F_KM + h * 32 + j, 64); } break; }
    mbar_wait(bKV + ph * 8, (s >> 1) & 1);
    const uint32_t mi = lane >> 3, r = lane & 7, zero = lane >> 5;
    {
      uint32_t qa[4][4], km[4]; uint2 kb[4]; float s0[4], s1[4], s2[4];
      const uint32_t aK = kvb + j * 8192 + warp * 1024 + lane * 16, aQ = sb + C_QK + (mi & 1) * 2048 + ((mi >> 1) * 8 + r) * 16;
      const uint32_t aKm = sb + C_QK + 256 + warp * 512 + (lane >> 4) * 2048 + (lane & 15) * 16;
#pragma unroll
      for (int i = 0; i < 4; i++) kb[i] = lds64(aK + ((warp ^ i) >> 1) * 512 + ((warp ^ i) & 1) * 8);
      const uint32_t aH = sb + C_S + warp * 256 + lane * 8, aR = aH + 1024 + px;
      SCHED(aQ ^ aR ^ aKm ^ ((kb[0].x ^ kb[1].x ^ kb[2].x ^ kb[3].x) & zero), 60);
      bar_sync(BAR_QK, 384);
      ldsm4t(qa[0], aQ + warp * 512); ldsm4t(km, aKm); ldsm4t(qa[1], aQ + (warp ^ 1) * 512); ldsm4t(qa[2], aQ + (warp ^ 2) * 512); ldsm4t(qa[3], aQ + (warp ^ 3) * 512);
      mma16816z(s0, qa[0], kb[0].x, kb[0].y); mma16816z(s2, qa[0], km[0], km[1]); mma16816z(s1, qa[1], kb[1].x, kb[1].y);
      mma16816(s2, qa[0], km[2], km[3]); mma16816(s0, qa[2], kb[2].x, kb[2].y); mma16816(s1, qa[3], kb[3].x, kb[3].y);
      const uint32_t w0 = pack_bf16((s0[0] + s0[2]) + (s1[0] + s1[2]), (s0[1] + s0[3]) + (s1[1] + s1[3]));
      const uint32_t w1 = pack_bf16(s2[0] + s2[2], s2[1] + s2[3]);
      stasync64(aR, w0, w1, bS + px);
      sts64(aH, w0, w1);
    }
    uint2 ts;
    {
      uint32_t vx[4][4], sl[5];
      const uint32_t aVx = kvb + 4096 + (warp >> 1) * (j ? -4096 : 4096) + (warp & 1) * 1024 + lane * 16;
      const uint32_t a8 = sb + lane * 8, av = a8 + C_VP + warp * 1024;
      const uint32_t aO = sb + C_O + ((warp >> 1) * 64 + (warp & 1) * 16 + (mi & 1) * 32 + (mi >> 1) * 8 + r) * 16, aR = sb + C_R + (lane & 28);
      bar_sync(BAR_X, 128);
      { uint2 t[4];
#pragma unroll
        for (int u = 0; u < 4; u++) t[u] = lds64(a8 + C_S + u * 256);
#pragma unroll
        for (int i = 0; i < 4; i++) { const uint4 q = lds128(aVx + (i & 1) * 2048 + (i >> 1) * 512); vx[i][0] = q.x; vx[i][1] = q.z ^ zero; vx[i][2] = q.y ^ zero; vx[i][3] = q.w; }
#pragma unroll
        for (int u = 0; u < 4; u++) sl[u] = t[u].x;
        sl[4] = pack_bf16((bf_lo(t[0].y) + bf_lo(t[1].y)) + (bf_lo(t[2].y) + bf_lo(t[3].y)), (bf_hi(t[0].y) + bf_hi(t[1].y)) + (bf_hi(t[2].y) + bf_hi(t[3].y))); }
      mbar_wait(bS, ph);
      uint32_t vm[2][4];
      { uint2 t[4];
#pragma unroll
        for (int u = 0; u < 4; u++) t[u] = lds64(a8 + C_S + 1024 + u * 256);
#pragma unroll
        for (int u = 0; u < 4; u++) sl[u] = hadd2bf(sl[u], t[u].x);
        sl[4] = hadd2bf(hadd2bf(hadd2bf(sl[4], t[0].y), t[1].y), hadd2bf(t[2].y, t[3].y)); }
      uint32_t m2 = hmax2bf(hmax2bf(hmax2bf(sl[0], sl[1]), hmax2bf(sl[2], sl[3])), sl[4]);
      const uint32_t x1 = __shfl_xor_sync(~0u, m2, 1), x2 = __shfl_xor_sync(~0u, m2, 2), x3 = __shfl_xor_sync(~0u, m2, 3);
#pragma unroll
      for (int i = 0; i < 4; i++) { const uint2 q = lds64(av + i * 256); vm[i >> 1][(i & 1) * 2] = q.x; vm[i >> 1][(i & 1) * 2 + 1] = q.y; }
      ts = ldg_rlx64(args.comm + TS_OFF + lane * 8);
      float sv[10];
#pragma unroll
      for (int u = 0; u < 5; u++) { sv[2 * u] = bf_lo(sl[u]) * SM_SCALE; sv[2 * u + 1] = bf_hi(sl[u]) * SM_SCALE; }
      m2 = hmax2bf(hmax2bf(m2, x1), hmax2bf(x2, x3));
      const float mx = fmaxf(bf_lo(m2), bf_hi(m2));
      float o0[4], o1[4];
      sv[8] = ex2(fmaf(mx, -SM_SCALE, sv[8])); sv[9] = ex2(fmaf(mx, -SM_SCALE, sv[9]));
      { const uint32_t p = pack_bf16(sv[8], sv[9]); mma16816z(o0, vm[0], p, p); mma16816z(o1, vm[1], p, p); }
#pragma unroll
      for (int i = 0; i < 4; i++) sv[i] = ex2(fmaf(mx, -SM_SCALE, sv[i]));
      { const uint32_t p0 = pack_bf16(sv[0], sv[1]), p1 = pack_bf16(sv[2], sv[3]); mma16816(o0, vx[0], p0, p1); mma16816(o1, vx[2], p0, p1); }
#pragma unroll
      for (int i = 4; i < 8; i++) sv[i] = ex2(fmaf(mx, -SM_SCALE, sv[i]));
      { const uint32_t p0 = pack_bf16(sv[4], sv[5]), p1 = pack_bf16(sv[6], sv[7]); mma16816(o0, vx[1], p0, p1); mma16816(o1, vx[3], p0, p1); }
      sts32(aR + (lane & 3) * 32 + 128, __float_as_uint((((sv[8] + sv[9]) + ((sv[0] + sv[1]) + (sv[2] + sv[3]))) + (sv[4] + sv[5])) + (sv[6] + sv[7])));
      stsm4(aO, pack_bf16(o0[0], o0[1]), pack_bf16(o0[2], o0[3]), pack_bf16(o1[0], o1[1]), pack_bf16(o1[2], o1[3]));
      if (warp == 3) bar_sync(BAR_O, 384); else bar_arrive(BAR_O, 384);
    }
    lane = __shfl_sync(~0u, lane0, lane0);
    uint32_t t0;
    {
      const uint4 cal = lds128(sb + C_R + 64);
      const uint32_t d0 = ts.x - cal.x, d1 = ts.y - cal.x;
      const int dt = (int)__reduce_max_sync(~0u, max(d0 < 32768u ? d0 : 0u, d1 < 32768u ? d1 : 0u));
      t0 = cal.y + (uint32_t)min(__float2int_rn((float)dt * __uint_as_float(cal.z)), 8192);
      if (warp == 1) sts32(sb + C_R + 48, t0);
    }
    const uint32_t tag = (s + args.layer + 1) & 1, tm = 0u - tag;
    if (warp == 3) {
      if (lane == 0) { LOGS(c, s); LOGV(c, 192 + (s >> 1), clk()); }
      const uint32_t* f = args.flags + F_KV + min((s + 2) >> 1, 31) * 32 + h;
      const uint32_t rdy = ldg_rlx32(f);
      flag_set(args.flags + F_KM + h * 32 + j, s);
      spin_until(t0 + args.ta[2] - TEXP);
      do_export(s, lane, true);
      if (__any_sync(~0u, rdy < 2)) flag_wait_warp(f, 2);
      spin_until(t0 + args.tb[2] + TKV);
      if (s < 61) load_kv(sb, h, j, s + 2);
      if (lane == 0) LOG(c, 64 + s);
    }
    if (warp == 2) calib();
    if (warp == 0 || warp == 2 || (warp == 1 && !(c & 16))) {
      const uint32_t g = lane >> 2, t = lane & 3;
      const char* p = args.comm + (g1page(c >> 1) + (c & 1) * 2048 + (warp == 0 ? 0 : warp == 1 ? 0x30000 : 0x100000) + ((g >> 2) * 4 + t) * 64 + (g & 3) * 16);
      char* g2w = args.comm + (g1page(((t >> 1) + (g >> 2) * 2) * 4 + warp) + G2_OFF + c * 64 + (g & 3) * 16 + (t & 1) * 8);
      const uint32_t one = (g & 1) ? 0x3F800000u : 0x00003F80u, s0 = (g & 2) ? 0u : one, s1 = (g & 2) ? one : 0u;
      int lim = 0; bool bad;
      p += wait_until(t0 + args.ta[warp], lane >> 5);
      do {
        uint4 a[4]; float z0[4], z1[4], y[4];
#pragma unroll
        for (int i = 0; i < 4; i++) a[i] = ldg_rlx128(p + i * 512);
        ++lim;
        { const uint32_t A[4] = {a[0].x, a[0].y, a[0].z, a[0].w}; mma16816z(z0, A, s0, s1); }
        { const uint32_t A[4] = {a[1].x, a[1].y, a[1].z, a[1].w}; mma16816z(z1, A, s0, s1); }
        { const uint32_t A[4] = {a[2].x, a[2].y, a[2].z, a[2].w}; mma16816(z0, A, s0, s1); }
        { const uint32_t A[4] = {a[3].x, a[3].y, a[3].z, a[3].w}; mma16816(z1, A, s0, s1); }
        const uint32_t m0 = launder((a[0].x ^ tm) | (a[0].z ^ tm)), m1 = launder((a[1].x ^ tm) | (a[1].z ^ tm)), m2 = launder((a[2].x ^ tm) | (a[2].z ^ tm)), m3 = launder((a[3].x ^ tm) | (a[3].z ^ tm));
        bad = __any_sync(~0u, ((launder(m0 | m1 | m2) | m3) & 0x10000u) && lim < POLL_LIMIT);
#pragma unroll
        for (int i = 0; i < 4; i++) { y[i] = z0[i] + z1[i]; y[i] += __shfl_xor_sync(~0u, y[i], 16); }
        const uint32_t w0 = pack_tag(y[0], y[1], tag << 16), w1 = pack_bf16(y[2], y[3]);
        if (!bad) stg_rlx64(g2w, w0, w1);
      } while (bad);
      if (lane == 0 && warp == 0) LOGV(c, 128 + s, lim);
    }
    if (warp < 3) {
      const uint32_t hf = warp >> 1, hg = warp ? 1024 : 2048, hs = warp ? 1024 : 5120;
      const char* p = args.comm + (g1page((h & 3) * 4 + (warp ? 2 : 1)) + G2_OFF + hf * 2048 + lane * 16);
      const uint32_t aMw = sb + C_M + (warp ? 3072 : 2048) + hf * 5120 + lane * 8;
      int lim = 0; bool bad;
      p += wait_until(t0 + args.tb[warp ? 2 : 1], lane >> 5);
      do { uint4 a[4]; uint32_t m = 0; ++lim;
#pragma unroll
        for (int i = 0; i < 4; i++) a[i] = ldg_rlx128(p + (i & 1) * 512 + (i >> 1) * hg);
#pragma unroll
        for (int i = 0; i < 4; i++) { const uint32_t q = aMw + (i & 1) * 256 + (i >> 1) * hs; sts64(q, a[i].x, a[i].z); sts64(q + 512, a[i].y, a[i].w); m |= (a[i].x ^ tm) | (a[i].z ^ tm); }
        bad = __any_sync(~0u, (m & 0x10000u) && lim < POLL_LIMIT);
      } while (bad);
      if (warp) bar_arrive(BAR_M2, 384); else bar_arrive(BAR_M1, 288);
    }
  }
}

constexpr int G_ST = 163840;
constexpr int B_FULL = 64, B_EMPTY = 96, B_WF = 128, B_WD = 136, B_ROLE = 144, B_PROG = 148;
enum { BAR_T = 1  , BAR_G = 3  , BAR_V = 5   };
DEVINL uint64_t mkdesc(uint32_t a, uint32_t lbo, uint32_t sbo, uint32_t sw) { return (uint64_t)((a & 0x3FFFF) >> 4) | ((uint64_t)(lbo >> 4) << 16) | ((uint64_t)(sbo >> 4) << 32) | ((uint64_t)sw << 62); }
DEVINL void wgmma_n128(float* d, uint64_t a, uint64_t b, int acc) {
  asm volatile("{.reg .pred p; setp.ne.b32 p, %66, 0; wgmma.mma_async.sync.aligned.m64n128k16.f32.bf16.bf16 {%0,%1,%2,%3,%4,%5,%6,%7,%8,%9,%10,%11,%12,%13,%14,%15,%16,%17,%18,%19,%20,%21,%22,%23,%24,%25,%26,%27,%28,%29,%30,%31,%32,%33,%34,%35,%36,%37,%38,%39,%40,%41,%42,%43,%44,%45,%46,%47,%48,%49,%50,%51,%52,%53,%54,%55,%56,%57,%58,%59,%60,%61,%62,%63}, %64, %65, p, 1, 1, 0, 1;}"
               : "+f"(d[0]),"+f"(d[1]),"+f"(d[2]),"+f"(d[3]),"+f"(d[4]),"+f"(d[5]),"+f"(d[6]),"+f"(d[7]),"+f"(d[8]),"+f"(d[9]),"+f"(d[10]),"+f"(d[11]),"+f"(d[12]),"+f"(d[13]),"+f"(d[14]),"+f"(d[15]),"+f"(d[16]),"+f"(d[17]),"+f"(d[18]),"+f"(d[19]),"+f"(d[20]),"+f"(d[21]),"+f"(d[22]),"+f"(d[23]),"+f"(d[24]),"+f"(d[25]),"+f"(d[26]),"+f"(d[27]),"+f"(d[28]),"+f"(d[29]),"+f"(d[30]),"+f"(d[31]),"+f"(d[32]),"+f"(d[33]),"+f"(d[34]),"+f"(d[35]),"+f"(d[36]),"+f"(d[37]),"+f"(d[38]),"+f"(d[39]),"+f"(d[40]),"+f"(d[41]),"+f"(d[42]),"+f"(d[43]),"+f"(d[44]),"+f"(d[45]),"+f"(d[46]),"+f"(d[47]),"+f"(d[48]),"+f"(d[49]),"+f"(d[50]),"+f"(d[51]),"+f"(d[52]),"+f"(d[53]),"+f"(d[54]),"+f"(d[55]),"+f"(d[56]),"+f"(d[57]),"+f"(d[58]),"+f"(d[59]),"+f"(d[60]),"+f"(d[61]),"+f"(d[62]),"+f"(d[63]) : "l"(a), "l"(b), "r"(acc));
}
DEVINL void wgmma_n80(float* d, uint64_t a, uint64_t b, int acc) {
  asm volatile("{.reg .pred p; setp.ne.b32 p, %42, 0; wgmma.mma_async.sync.aligned.m64n80k16.f32.bf16.bf16 {%0,%1,%2,%3,%4,%5,%6,%7,%8,%9,%10,%11,%12,%13,%14,%15,%16,%17,%18,%19,%20,%21,%22,%23,%24,%25,%26,%27,%28,%29,%30,%31,%32,%33,%34,%35,%36,%37,%38,%39}, %40, %41, p, 1, 1, 0, 1;}"
               : "+f"(d[0]),"+f"(d[1]),"+f"(d[2]),"+f"(d[3]),"+f"(d[4]),"+f"(d[5]),"+f"(d[6]),"+f"(d[7]),"+f"(d[8]),"+f"(d[9]),"+f"(d[10]),"+f"(d[11]),"+f"(d[12]),"+f"(d[13]),"+f"(d[14]),"+f"(d[15]),"+f"(d[16]),"+f"(d[17]),"+f"(d[18]),"+f"(d[19]),"+f"(d[20]),"+f"(d[21]),"+f"(d[22]),"+f"(d[23]),"+f"(d[24]),"+f"(d[25]),"+f"(d[26]),"+f"(d[27]),"+f"(d[28]),"+f"(d[29]),"+f"(d[30]),"+f"(d[31]),"+f"(d[32]),"+f"(d[33]),"+f"(d[34]),"+f"(d[35]),"+f"(d[36]),"+f"(d[37]),"+f"(d[38]),"+f"(d[39]) : "l"(a), "l"(b), "r"(acc));
}

template <int N, int NST, bool HAND>
DEVINL void gemm_tile(float* acc, uint32_t sb, uint32_t px, int wg, uint32_t u0, int rot, bool lead) {
  const uint64_t db = N == 128 ? mkdesc(sb, 81920, 1024, 1) : mkdesc(sb, 32768, 256, 3);
#pragma unroll
  for (int i = 0; i < N / 2; i++) acc[i] = 0.f;
  bar_sync(BAR_T + wg, 256);
#pragma unroll 1
  for (int st = 0; st < NST; st++) {
    const uint32_t u = u0 + st, slot = u & 3, ks = (st + rot >= NST ? st + rot - NST : st + rot) * 8;
    mbar_wait(sb + S_BAR + B_FULL + slot * 8, (u >> 2) & 1);
    const uint64_t da = mkdesc(sb + G_ST + slot * 16384, 16, 1024, 1);
    asm volatile("wgmma.fence.sync.aligned;" ::: "memory");
#pragma unroll
    for (int k = 0; k < 8; k++) {
      const uint64_t a = da + (k >> 2) * 512 + (k & 3) * 2;
      if (N == 128) wgmma_n128(acc, a, db + (ks + k) * 128, 1); else wgmma_n80(acc, a, db + (ks + k) * 32, 1);
    }
    asm volatile("wgmma.commit_group.sync.aligned;" ::: "memory");
    if (HAND && st == NST - 1) bar_arrive(BAR_T + (wg ^ 1), 256);
    if (st > 0) {
      asm volatile("wgmma.wait_group.sync.aligned 1;" ::: "memory");
      if (lead) { const uint32_t e = sb + S_BAR + B_EMPTY + ((u - 1) & 3) * 8; mbar_arrive(e); mbar_arrive_remote(e + px); }
    }
  }
  asm volatile("wgmma.wait_group.sync.aligned 0;" ::: "memory");
  if (lead) { const uint32_t e = sb + S_BAR + B_EMPTY + ((u0 + NST - 1) & 3) * 8; mbar_arrive(e); mbar_arrive_remote(e + px); }
}
DEVINL void wg_publish(int wg) { bar_sync(BAR_G + wg, 160); }
DEVINL uint32_t km_known(uint32_t sb) { uint32_t v; asm volatile("ld.acquire.cta.shared.u32 %0, [%1];" : "=r"(v) : "r"(sb + S_BAR + B_PROG) : "memory"); return __reduce_min_sync(~0u, v); }
DEVINL void km_watcher(uint32_t sb, const uint32_t* p) {
  uint32_t v = 0;
#pragma unroll 1
  for (int n = 0; n < 16 * POLL_LIMIT && v < 64; n++) {
    const uint2 q = ldg_rlx64(p);
    if (min(q.x, q.y) != v) { v = min(q.x, q.y); asm volatile("fence.acquire.gpu; st.release.cta.shared.u32 [%0], %1;" ::"r"(sb + S_BAR + B_PROG), "r"(v) : "memory"); }
    __nanosleep(v < 61 ? 300 : 20);
  }
}

template <int HF>
DEVINL void attend(const float* acc, uint4 (*kf)[4], uint4* kmf, uint4* op, const char* kvp, const char* mp, bf16* orow, int lane, int wg, uint32_t sb, int tile, bool& pend) {
  constexpr int NT = HF ? 4 : 2;
  const int g = lane >> 2, t = lane & 3;
  float sc[NT + 1][4];
#pragma unroll
  for (int k = 0; k < 8; k++) {
    uint32_t qa[4];
#pragma unroll
    for (int i = 0; i < 4; i++) { const float* a = acc + 32 * (k >> 2) + 4 * (k & 3) + 16 * (i >> 1) + 2 * (i & 1); qa[i] = pack_bf16(a[0], a[1]); }
#pragma unroll
    for (int kt = 0; kt <= NT; kt++) {
      const uint4 b = kt < NT ? kf[kt][k >> 1] : kmf[k >> 1];
      if (k == 0) mma16816z(sc[kt], qa, b.x, b.y); else if (k & 1) mma16816(sc[kt], qa, b.z, b.w); else mma16816(sc[kt], qa, b.x, b.y);
    }
  }
  SCHED(lane, 70);
  bar_arrive(BAR_T + (wg ^ 1), 256);
  if (pend) {
#pragma unroll
    for (int q = 0; q < 4; q++) { *(uint4*)(orow - 128 * 4096 + q * 32) = op[2 * q]; *(uint4*)(orow - 120 * 4096 + q * 32) = op[2 * q + 1]; }
    wg_publish(wg);
  }
  {
    uint32_t go; asm volatile("{.reg .pred p,q; setp.ne.u32 q, %1, 0; bar.red.and.pred p, %2, 128, q; selp.u32 %0, 1, 0, p;}" : "=r"(go) : "r"((uint32_t)(tile < 30 && km_known(sb) > tile * 2 + 5)), "r"(BAR_V + wg) : "memory");
    pend = __reduce_max_sync(~0u, go); }
  uint4 vf[HF + 1][8]; uint32_t vm[16];
  const char* vp = kvp + 4096 + (g >> 1) * 512 + ((g & 1) * 4 + t) * 16;
  const char* vmp = mp + 2048 + ((8 * (g >> 1) + (g & 1)) * 16 + t * 4);
#pragma unroll
  for (int i = 0; i < 16; i++) vm[i] = ldg_ca32(vmp + (i >> 2) * 512 + (i & 3) * 32);
#pragma unroll
  for (int i = 0; i < 8; i++) vf[0][i] = ldg_ca128(vp + (i >> 2) * 4096 + (i & 3) * 128);
  if (tile < 30) {
#pragma unroll
    for (int i = 0; i < 8; i++) kf[i >> 2][i & 3] = ldg_ca128(kvp + 4 * 32 * 16384 + ((i >> 1) & 1) * 12288 + (i >> 2) * 1024 + (i & 1) * 512 + lane * 16);
  }
  if (pend) {
#pragma unroll
    for (int G = 0; G < 4; G++) kmf[G] = ldg_ca128(mp + 4 * 32 * 4096 + G * 512 + lane * 16);
  }
  if (HF) {
#pragma unroll
    for (int i = 0; i < 8; i++) vf[HF][i] = ldg_cg128(vp + 2048 + (i >> 2) * 4096 + (i & 3) * 128);
    if (tile < 30) {
#pragma unroll
      for (int i = 8; i < 16; i++) kf[i >> 2][i & 3] = ldg_cg128(kvp + 4 * 32 * 16384 + ((i >> 1) & 1) * 12288 + (i >> 2) * 1024 + (i & 1) * 512 + lane * 16);
    }
  }
  const float NINF = __int_as_float(0xff800000);
  if (2 * t > g) { sc[NT - 2][0] = NINF; sc[NT - 1][2] = NINF; }
  if (2 * t + 1 > g) { sc[NT - 2][1] = NINF; sc[NT - 1][3] = NINF; }
  sc[NT - 1][0] = NINF; sc[NT - 1][1] = NINF;
  float m0 = fmaxf(sc[NT][0], sc[NT][1]), m1 = fmaxf(sc[NT][2], sc[NT][3]);
#pragma unroll
  for (int kt = 0; kt < NT; kt++) { m0 = fmaxf(m0, fmaxf(sc[kt][0], sc[kt][1])); m1 = fmaxf(m1, fmaxf(sc[kt][2], sc[kt][3])); }
  m0 = fmaxf(fmaxf(m0, __shfl_xor_sync(~0u, m0, 1)), fmaxf(__shfl_xor_sync(~0u, m0, 2), __shfl_xor_sync(~0u, m0, 3)));
  m1 = fmaxf(fmaxf(m1, __shfl_xor_sync(~0u, m1, 1)), fmaxf(__shfl_xor_sync(~0u, m1, 2), __shfl_xor_sync(~0u, m1, 3)));
  m0 *= -SM_SCALE; m1 *= -SM_SCALE;
  float s0 = 0.f, s1 = 0.f; uint32_t p[NT + 1][2];
#pragma unroll
  for (int kt = 0; kt <= NT; kt++) {
    const float a = ex2(fmaf(sc[kt][0], SM_SCALE, m0)), b = ex2(fmaf(sc[kt][1], SM_SCALE, m0)), c = ex2(fmaf(sc[kt][2], SM_SCALE, m1)), d = ex2(fmaf(sc[kt][3], SM_SCALE, m1));
    s0 += a + b; s1 += c + d; p[kt][0] = pack_bf16(a, b); p[kt][1] = pack_bf16(c, d);
  }
  s0 = (s0 + __shfl_xor_sync(~0u, s0, 1)) + (__shfl_xor_sync(~0u, s0, 2) + __shfl_xor_sync(~0u, s0, 3));
  s1 = (s1 + __shfl_xor_sync(~0u, s1, 1)) + (__shfl_xor_sync(~0u, s1, 2) + __shfl_xor_sync(~0u, s1, 3));
  s0 = rcp(s0); s1 = rcp(s1);
#pragma unroll
  for (int grp = 0; grp < 4; grp++) {
    float o[4][4];
#pragma unroll
    for (int L = 0; L < 4; L++) {
      mma1688z(o[L], p[NT][0], p[NT][1], vm[grp * 4 + L]);
#pragma unroll
      for (int kh = 0; kh <= HF; kh++) {
        const uint4 w = vf[kh][(grp >> 1) * 4 + L]; const uint32_t A[4] = {p[2 * kh][0], p[2 * kh][1], p[2 * kh + 1][0], p[2 * kh + 1][1]};
        if (grp & 1) mma16816(o[L], A, w.z, w.w); else mma16816(o[L], A, w.x, w.y);
      }
    }
    op[2 * grp] = make_uint4(pack_bf16(o[0][0] * s0, o[0][1] * s0), pack_bf16(o[1][0] * s0, o[1][1] * s0), pack_bf16(o[2][0] * s0, o[2][1] * s0), pack_bf16(o[3][0] * s0, o[3][1] * s0));
    op[2 * grp + 1] = make_uint4(pack_bf16(o[0][2] * s1, o[0][3] * s1), pack_bf16(o[1][2] * s1, o[1][3] * s1), pack_bf16(o[2][2] * s1, o[2][3] * s1), pack_bf16(o[3][2] * s1, o[3][3] * s1));
  }
}

DEVINL void gemm_consumer(uint32_t sb, uint32_t px, int wg, int pr, int rank, const ArgsA& args) {
  const int lane = opaque(threadIdx.x & 31), w = __reduce_max_sync(~0u, (threadIdx.x >> 5) & 3);
  const bool lead = lane == 0 && w == 0;
  const int rot5 = pr % 5;
  if (wg == 1) bar_arrive(BAR_T, 256);
  mbar_wait(sb + S_BAR + B_WF, 0);
  if (threadIdx.x == 0) LOG(64 + pr * 2 + rank, 250);
#pragma unroll 1
  for (int tile = wg; tile < 32; tile += 2) {
    float acc[64];
    gemm_tile<128, 5, true>(acc, sb, px, wg, tile * 5, rot5, lead);
    if (tile >= 30 && lead) mbar_arrive(sb + S_BAR + B_WD);
    char* dst = g_kv + (size_t)((tile * 2 + (w >> 1)) * 32 + pr) * 16384 + (w & 1) * 2048 + lane * 16;
    if (rank == 0) {
#pragma unroll
      for (int G = 0; G < 4; G++)
#pragma unroll
        for (int hh = 0; hh < 2; hh++) {
          const float* a = acc + 32 * (G >> 1) + 8 * (G & 1) + 2 * hh;
          *(uint4*)(dst + (G >> 1) * 12288 + hh * 1024 + (G & 1) * 512) = make_uint4(pack_bf16(a[0], a[1]), pack_bf16(a[16], a[17]), pack_bf16(a[4], a[5]), pack_bf16(a[20], a[21]));
        }
    } else {
#pragma unroll
      for (int i = 0; i < 8; i++) {
        const float* a = acc + (i >> 2) * 32 + (i & 3) * 4;
        *(uint4*)(dst + 4096 + (i >> 2) * 4096 + (i & 3) * 512) = make_uint4(movm(pack_bf16(a[0], a[1])), movm(pack_bf16(a[2], a[3])), movm(pack_bf16(a[16], a[17])), movm(pack_bf16(a[18], a[19])));
      }
    }
    wg_publish(wg);
    if ((threadIdx.x & 127) == 0) LOG(64 + pr * 2 + rank, tile);
  }
  mbar_wait(sb + S_BAR + B_WF, 1);
  if (threadIdx.x == 0) LOG(64 + pr * 2 + rank, 251);
  if (pr < 16) {
    const int h = 2 * pr + rank;
    flag_wait_warp(args.flags + F_KV + (30 + (lane & 1)) * 32 + h, 2);
    bool pend = false; uint4 op[8], kf[4][4], kmf[4];
#pragma unroll
    for (int i = 0; i < 16; i++) kf[i >> 2][i & 3] = ldg_cg128(g_kv + (size_t)((wg * 2 + (w >> 1)) * 32 + h) * 16384 + ((i >> 1) & 1) * 12288 + (i >> 2) * 1024 + (i & 1) * 512 + lane * 16);
#pragma unroll
    for (int i = 0; i < 8; i++) op[i] = kmf[i & 3] = make_uint4(0, 0, 0, 0);
#pragma unroll 1
    for (int tile = wg; tile < 32; tile += 2) {
      const uint32_t seg = tile * 2 + (w >> 1);
      const char* kvp = g_kv + (size_t)(seg * 32 + h) * 16384;
      const char* mp = g_kvm + (size_t)(seg * 32 + h) * 4096;
      bf16* orow = g_o + (size_t)(tile * 64 + w * 16 + (lane >> 2)) * 4096 + h * 128 + (lane & 3) * 8;
      float acc[64];
      gemm_tile<128, 5, false>(acc, sb, px, wg, 160 + tile * 5, rot5, lead);
      if ((threadIdx.x & 127) == 96) LOG(64 + pr * 2 + rank, 64 + tile);
      if (!pend) {
        int n = 0;
        while (km_known(sb) <= seg && ++n < 16 * POLL_LIMIT) {}
#pragma unroll
        for (int G = 0; G < 4; G++) kmf[G] = ldg_ca128(mp + G * 512 + lane * 16);
      }
      if ((threadIdx.x & 127) == 96) LOG(64 + pr * 2 + rank, 96 + tile);
      if (w & 1) attend<1>(acc, kf, kmf, op, kvp, mp, orow, lane, wg, sb, tile, pend); else attend<0>(acc, kf, kmf, op, kvp, mp, orow, lane, wg, sb, tile, pend);
      if (!pend) {
#pragma unroll
        for (int q = 0; q < 4; q++) { *(uint4*)(orow + q * 32) = op[2 * q]; *(uint4*)(orow + 8 * 4096 + q * 32) = op[2 * q + 1]; }
        wg_publish(wg);
      }
      if ((threadIdx.x & 127) == 0) LOG(64 + pr * 2 + rank, 32 + tile);
    }
  } else {
    const int kq = (pr - 16) >> 2, cg = 2 * (pr & 3) + rank;
#pragma unroll 1
    for (int tile = wg; tile < 32; tile += 2) {
      float acc[40];
      gemm_tile<80, 8, true>(acc, sb, px, wg, 160 + tile * 8, (pr & 3) * 2, lead);
      const bool odd = lane & 1;
      bf16* dst = g_part + (size_t)(kq * 2048 + tile * 64 + w * 16 + (lane >> 2)) * 640 + cg * 80 + (lane & 1) * 8 + (lane & 2) * 2;
#pragma unroll
      for (int q = 0; q < 5; q++)
#pragma unroll
        for (int hh = 0; hh < 2; hh++) {
          const uint32_t A = pack_bf16(acc[8 * q + 2 * hh], acc[8 * q + 2 * hh + 1]), B = pack_bf16(acc[8 * q + 4 + 2 * hh], acc[8 * q + 5 + 2 * hh]);
          const uint32_t x = __shfl_xor_sync(~0u, odd ? A : B, 1);
          *(uint2*)(dst + hh * 8 * 640 + q * 16) = odd ? make_uint2(x, B) : make_uint2(A, x);
        }
      if ((threadIdx.x & 127) == 0) LOG(64 + pr * 2 + rank, 32 + tile);
    }
  }
  if (wg == 0) bar_sync(BAR_T, 256);
}

DEVINL void gemm_producer(uint32_t sb, int pr, int rank, const ArgsA& args, const CUtensorMap* tq, const CUtensorMap* tk, const CUtensorMap* tv,
                          const CUtensorMap* to32, const CUtensorMap* tx, const CUtensorMap* tao) {
  const uint32_t bWF = sb + S_BAR + B_WF;
  auto load_w = [&](const CUtensorMap* tm, int col) { mbar_arrive_tx(bWF, 163840);
#pragma unroll 1
    for (int i = 0; i < 20; i++) tma_2d(sb + (i & 1) * 81920 + (i >> 1) * 8192, tm, col + (i & 1) * 64, (i >> 1) * 64, bWF); };
  uint32_t u = 0;
  auto push = [&](const CUtensorMap* tm, int c0, int c1) {
    const uint32_t slot = u & 3, full = sb + S_BAR + B_FULL + slot * 8;
    mbar_wait(sb + S_BAR + B_EMPTY + slot * 8, ((u >> 2) & 1) ^ 1);
    mbar_arrive_tx(full, 16384);
    tma_2d_mc(sb + G_ST + slot * 16384 + rank * 8192, tm, c0 + rank * 64, c1, full);
    u++; };
  load_w(rank ? tv : tk, pr * 128);
#pragma unroll 1
  for (int tile = 0; tile < 32; tile++) {
    l2_prefetch((const char*)g_xn + ((tile + 2) & 31) * 81920 + (pr * 2 + rank) * 1280, 1280);
#pragma unroll 1
    for (int st = 0; st < 5; st++) push(tx, ((st + pr) % 5) * 128, tile * 64);
  }
  mbar_wait(sb + S_BAR + B_WD, 0);
  if (pr < 16) {
    load_w(tq, (2 * pr + rank) * 128);
#pragma unroll 1
    for (int tile = 0; tile < 32; tile++) {
      if (tile < 30) {
        l2_prefetch((const char*)g_xn + (tile + 2) * 81920 + (pr * 2 + rank) * 2560, 2560);
        const int q = (tile * 2 + 4) * 32 + 2 * pr + rank;
        l2_prefetch(g_kv + (size_t)q * 16384, 16384); l2_prefetch(g_kv + (size_t)(q + 32) * 16384, 16384);
        if (lds32(sb + S_BAR + B_PROG) > tile * 2 + 5) { l2_prefetch(g_kvm + (size_t)q * 4096, 4096); l2_prefetch(g_kvm + (size_t)(q + 32) * 4096, 4096); }
      }
#pragma unroll 1
      for (int st = 0; st < 5; st++) push(tx, ((st + pr) % 5) * 128, tile * 64);
    }
  } else {
    const int kq = (pr - 16) >> 2, cg = 2 * (pr & 3) + rank;
    mbar_arrive_tx(bWF, 163840);
#pragma unroll 1
    for (int i = 0; i < 20; i++) tma_2d(sb + (i % 5) * 32768 + (i / 5) * 8192, to32, cg * 80 + (i % 5) * 16, kq * 1024 + (i / 5) * 256, bWF);
#pragma unroll 1
    for (int tile = 0; tile < 32; tile++) {
      flag_wait(args.flags + F_O + tile * 4 + kq, 8);
#pragma unroll 1
      for (int st = 0; st < 8; st++) push(tao, kq * 1024 + ((st + (pr & 3) * 2) & 7) * 128, tile * 64);
    }
  }
#pragma unroll 1
  for (int i = 0; i < 4; i++, u++) mbar_wait(sb + S_BAR + B_EMPTY + (u & 3) * 8, ((u >> 2) & 1) ^ 1);
}

DEVINL void gemm_publisher(int wg, int pr, int rank, const ArgsA& args) {
#pragma unroll 1
  for (int i = 0; i < (pr < 16 ? 32 : 16); i++) {
    const int tile = (i & 15) * 2 + wg;
    bar_sync(BAR_G + wg, 160);
    if ((threadIdx.x & 31) == 0) fence_proxy_async(), flag_add(args.flags + (i < 16 ? F_KV + tile * 32 + pr : F_O + tile * 4 + (pr >> 2)));
    __syncwarp();
  }
}

DEVINL void filter_prep(uint32_t* sm, int part, const ArgsA& args) {
  const int tid = threadIdx.x, lane = tid & 31, w = tid >> 5;
  const unsigned short* wr = (const unsigned short*)args.wr; const unsigned short* wi = (const unsigned short*)args.wi;
#pragma unroll 1
  for (int it = part; it < 32; it += 4) {
#pragma unroll
    for (int rr = 0; rr < 8; rr += 4) {
      uint32_t a[4][11], b[4][11];
#pragma unroll
      for (int r = 0; r < 4; r++) {
        const int pos = it * 64 + w * 8 + rr + r, th = (pos >> 2) & 127, v = (pos >> 9) * 4 + (pos & 3);
        const int o = ((th >> 3) + 16 * ((th & 7) + (v & 8)) + 256 * (v & 7)) * 321 + lane;
#pragma unroll
        for (int c = 0; c < 11; c++) if (c < 10 || lane == 0) { a[r][c] = wr[o + c * 32]; b[r][c] = wi[o + c * 32]; }
      }
#pragma unroll
      for (int r = 0; r < 4; r++)
#pragma unroll
        for (int c = 0; c < 11; c++) if (c < 10 || lane == 0) sm[(c * 32 + lane) * 65 + w * 8 + rr + r] = a[r][c] | (b[r][c] << 16);
    }
    bar_sync(1, 256);
#pragma unroll 8
    for (int i = tid; i < 64 * 321; i += 256) g_wt[(i >> 6) * 2048 + it * 64 + (i & 63)] = sm[(i >> 6) * 65 + (i & 63)];
    bar_sync(1, 256);
  }
}

__global__ void __cluster_dims__(2, 1, 1) __launch_bounds__(384, 1)
layer_a_kernel(const __grid_constant__ CUtensorMap tq, const __grid_constant__ CUtensorMap tk, const __grid_constant__ CUtensorMap tv,
               const __grid_constant__ CUtensorMap to, const __grid_constant__ CUtensorMap to32, const __grid_constant__ CUtensorMap tx,
               const __grid_constant__ CUtensorMap tao, const __grid_constant__ ArgsA args) {
  extern __shared__ __align__(1024) char smraw[];
  const uint32_t sb = (smem_u32(smraw) + 1023) & ~1023u;
  uint32_t rank; asm volatile("mov.u32 %0, %%cluster_ctarank;" : "=r"(rank));
  rank = __reduce_max_sync(~0u, rank);
  const uint32_t px = __reduce_max_sync(~0u, mapa(sb, rank ^ 1) - sb);
  pdl_wait();
  if (threadIdx.x == 0) {
    const uint32_t b = sb + S_BAR;
    mbar_init(b + B_W, 1); mbar_init(b + B_S, 9); mbar_init(b + B_KV, 1); mbar_init(b + B_KV + 8, 1);
    for (int i = 0; i < 4; i++) { mbar_init(b + B_FULL + i * 8, 1); mbar_init(b + B_EMPTY + i * 8, 2); }
    mbar_init(b + B_WF, 1); mbar_init(b + B_WD, 2); sts32(b + B_PROG, 0);
    asm volatile("fence.mbarrier_init.release.cluster;" ::: "memory");
    if (rank == 0) {
      uint32_t smid; asm volatile("mov.u32 %0, %%smid;" : "=r"(smid));
      uint32_t* cnt = args.flags + F_ROLE; uint32_t role;
      if (g_side[smid & 255] + g_side[(smid ^ 1) & 255] < 0) { role = atomicAdd(cnt, 1); if (role >= 32) role = 32 + atomicAdd(cnt + 32, 1); }
      else { role = 32 + atomicAdd(cnt + 32, 1); if (role >= 66) role = atomicAdd(cnt, 1); }
      sts32(b + B_ROLE, role);
    }
  }
  __syncthreads();
  cluster_sync();
  uint32_t role; asm volatile("ld.shared::cluster.u32 %0, [%1];" : "=r"(role) : "r"(sb + S_BAR + B_ROLE + (rank ? px : 0)) : "memory");
  role = __reduce_max_sync(~0u, role);
  if (role >= 64) cluster_sync();
  const int wg = __reduce_max_sync(~0u, threadIdx.x >> 7);
  auto U = [](uint32_t x) { return __reduce_max_sync(~0u, opaque(x)); };
  if (wg == 2) {
    asm volatile("setmaxnreg.dec.sync.aligned.u32 56;");
    if (role < 32) chain_helper(U(sb), U(px), U(role), U(rank), args, &tq, &tk, &tv, &to);
    else if (role < 64) {
      if (threadIdx.x == 256) gemm_producer(sb, role - 32, rank, args, &tq, &tk, &tv, &to32, &tx, &tao);
      else if (threadIdx.x >= 288 && threadIdx.x < 352) gemm_publisher((threadIdx.x >> 5) - 9, role - 32, rank, args);
      else if (threadIdx.x == 352 && role < 48) km_watcher(sb, args.flags + F_KM + (2 * (role - 32) + rank) * 32);
    }
  } else {
    asm volatile("setmaxnreg.inc.sync.aligned.u32 224;");
    if (role < 32) { if (wg == 0) chain_mma<0>(sb, args); else chain_mma<1>(sb, args); }
    else if (role < 64) gemm_consumer(U(sb), U(px), U(wg), U(role - 32), U(rank), args);
    else if (args.layer == 0) { filter_prep((uint32_t*)smraw, (role - 64) * 2 + rank, args); if (threadIdx.x == 0) LOG(role * 2 + rank, 0); }
  }
}

DEVINL float2 cadd(float2 a, float2 b) { return make_float2(a.x + b.x, a.y + b.y); }
DEVINL float2 csub(float2 a, float2 b) { return make_float2(a.x - b.x, a.y - b.y); }
DEVINL float2 cmul(float2 a, float2 b) { return make_float2(fmaf(a.x, b.x, -a.y * b.y), fmaf(a.x, b.y, a.y * b.x)); }
DEVINL float2 cmulc(float2 a, float2 b) { return make_float2(fmaf(a.x, b.x, a.y * b.y), fmaf(a.y, b.x, -a.x * b.y)); }
template <int INV> DEVINL float2 ctw(float2 a, float2 w) { return INV ? cmulc(a, w) : cmul(a, w); }
template <int INV> DEVINL float2 rot(float2 a) { return INV ? make_float2(-a.y, a.x) : make_float2(a.y, -a.x); }
template <int INV> DEVINL void fft4(float2& a, float2& b, float2& c, float2& d) {
  const float2 s0 = cadd(a, c), d0 = csub(a, c), s1 = cadd(b, d), d1 = rot<INV>(csub(b, d));
  a = cadd(s0, s1); b = cadd(d0, d1); c = csub(s0, s1); d = csub(d0, d1);
}
template <int INV> DEVINL float2 w8(float2 a) { const float h = 0.70710678118654752f; const float2 r = rot<INV>(a); return make_float2((a.x + r.x) * h, (a.y + r.y) * h); }
template <int INV> DEVINL void fft8(float2* x) {
  fft4<INV>(x[0], x[2], x[4], x[6]); fft4<INV>(x[1], x[3], x[5], x[7]);
  const float2 e0 = x[0], e1 = x[2], e2 = x[4], e3 = x[6], o0 = x[1], o1 = w8<INV>(x[3]), o2 = rot<INV>(x[5]), o3 = rot<INV>(w8<INV>(x[7]));
  x[0] = cadd(e0, o0); x[1] = cadd(e1, o1); x[2] = cadd(e2, o2); x[3] = cadd(e3, o3);
  x[4] = csub(e0, o0); x[5] = csub(e1, o1); x[6] = csub(e2, o2); x[7] = csub(e3, o3);
}
template <int INV> DEVINL void fft16(float2* x) {
  const float c = 0.92387953251128674f, s = 0.38268343236508977f;
  const float2 w1 = make_float2(c, -s), w3 = make_float2(s, -c);
#pragma unroll
  for (int i = 0; i < 4; i++) fft4<INV>(x[i], x[i + 4], x[i + 8], x[i + 12]);
  x[5] = ctw<INV>(x[5], w1); x[9] = w8<INV>(x[9]); x[13] = ctw<INV>(x[13], w3);
  x[6] = w8<INV>(x[6]); x[10] = rot<INV>(x[10]); x[14] = rot<INV>(w8<INV>(x[14]));
  x[7] = ctw<INV>(x[7], w3); x[11] = rot<INV>(w8<INV>(x[11])); x[15] = ctw<INV>(x[15], make_float2(-c, s));
#pragma unroll
  for (int k = 0; k < 4; k++) fft4<INV>(x[4 * k], x[4 * k + 1], x[4 * k + 2], x[4 * k + 3]);
#pragma unroll
  for (int k = 0; k < 4; k++)
#pragma unroll
    for (int m = k + 1; m < 4; m++) { const float2 t = x[4 * k + m]; x[4 * k + m] = x[4 * m + k]; x[4 * m + k] = t; }
}
template <int INV> DEVINL void fft5(float2& x0, float2& x1, float2& x2, float2& x3, float2& x4) {
  const float c1 = 0.30901699437494742f, c2 = -0.80901699437494742f, s1 = 0.95105651629515357f, s2 = 0.58778525229247313f;
  const float2 a1 = cadd(x1, x4), a2 = cadd(x2, x3), b1 = rot<INV>(csub(x1, x4)), b2 = rot<INV>(csub(x2, x3));
  const float2 p1 = make_float2(fmaf(c1, a1.x, fmaf(c2, a2.x, x0.x)), fmaf(c1, a1.y, fmaf(c2, a2.y, x0.y)));
  const float2 p2 = make_float2(fmaf(c2, a1.x, fmaf(c1, a2.x, x0.x)), fmaf(c2, a1.y, fmaf(c1, a2.y, x0.y)));
  const float2 q1 = make_float2(fmaf(s1, b1.x, s2 * b2.x), fmaf(s1, b1.y, s2 * b2.y));
  const float2 q2 = make_float2(fmaf(s2, b1.x, -s1 * b2.x), fmaf(s2, b1.y, -s1 * b2.y));
  x0 = cadd(x0, cadd(a1, a2)); x1 = cadd(p1, q1); x4 = csub(p1, q1); x2 = cadd(p2, q2); x3 = csub(p2, q2);
}
template <int INV> DEVINL void fft20(const float2* in, float2* out) {
  float2 t[4][5];
#pragma unroll
  for (int a = 0; a < 4; a++) {
#pragma unroll
    for (int b = 0; b < 5; b++) t[a][b] = in[(5 * a + 4 * b) % 20];
    fft5<INV>(t[a][0], t[a][1], t[a][2], t[a][3], t[a][4]);
  }
#pragma unroll
  for (int d = 0; d < 5; d++) {
    fft4<INV>(t[0][d], t[1][d], t[2][d], t[3][d]);
#pragma unroll
    for (int c = 0; c < 4; c++) out[(5 * c + 16 * d) % 20] = t[c][d];
  }
}
DEVINL void unpack8(uint4 v, float* f) { f[0] = bf_lo(v.x); f[1] = bf_hi(v.x); f[2] = bf_lo(v.y); f[3] = bf_hi(v.y); f[4] = bf_lo(v.z); f[5] = bf_hi(v.z); f[6] = bf_lo(v.w); f[7] = bf_hi(v.w); }
DEVINL uint4 pack8(const float* f) { return make_uint4(pack_bf16(f[0], f[1]), pack_bf16(f[2], f[3]), pack_bf16(f[4], f[5]), pack_bf16(f[6], f[7])); }
DEVINL void ln_row(float* f) {
  float s = 0.f;
#pragma unroll
  for (int i = 0; i < 40; i++) s += f[i];
#pragma unroll
  for (int o = 1; o < 16; o <<= 1) s += __shfl_xor_sync(~0u, s, o);
  const float mean = s * (1.f / 640.f); float q = 0.f;
#pragma unroll
  for (int i = 0; i < 40; i++) { f[i] -= mean; q = fmaf(f[i], f[i], q); }
#pragma unroll
  for (int o = 1; o < 16; o <<= 1) q += __shfl_xor_sync(~0u, q, o);
  const float rs = rsqrtf(q * (1.f / 640.f) + 1e-5f);
#pragma unroll
  for (int i = 0; i < 40; i++) f[i] *= rs;
}
constexpr int ZP = 336;
struct RowSmem { float2 T[320 * 17]; uint32_t Z[16 * ZP]; float2 tw[320]; float2 tp[160]; };
DEVINL void row_tables(RowSmem& sm) {
  const int t = threadIdx.x; float s, c;
  sincospif(-(float)((t >> 4) * (t & 15)) * (1.f / 160.f), &s, &c); sm.tw[t] = make_float2(c, s);
  if (t < 160) { sincospif(-(float)t * (1.f / 320.f), &s, &c); sm.tp[t] = make_float2(c, s); }
}

__global__ void __launch_bounds__(320) rows_fwd_kernel(const bf16* __restrict__ xin) {
  extern __shared__ __align__(1024) char smraw[]; RowSmem& sm = *(RowSmem*)smraw;
  const int tid = threadIdx.x, s0 = blockIdx.x * 16;
  row_tables(sm);
  pdl_wait();
  pdl_launch();
  if (tid < 256) {
    const int row = tid >> 4, j = tid & 15; const size_t off = (size_t)(s0 + row) * 640 + j * 8;
    float f[40];
#pragma unroll
    for (int i = 0; i < 5; i++) {
      float a[8], b[8], c[8], d[8], x[8];
      unpack8(ldg_cg128(g_part + off + i * 128), a); unpack8(ldg_cg128(g_part + 2048 * 640 + off + i * 128), b);
      unpack8(ldg_cg128(g_part + 2 * 2048 * 640 + off + i * 128), c); unpack8(ldg_cg128(g_part + 3 * 2048 * 640 + off + i * 128), d);
      unpack8(ldg_cg128(xin + off + i * 128), x);
#pragma unroll
      for (int e = 0; e < 8; e++) a[e] = (a[e] + b[e]) + (c[e] + d[e]);
      unpack8(pack8(a), a);
#pragma unroll
      for (int e = 0; e < 8; e++) a[e] += x[e];
      const uint4 r = pack8(a); *(uint4*)(g_x + off + i * 128) = r; unpack8(r, f + 8 * i);
    }
    ln_row(f);
#pragma unroll
    for (int i = 0; i < 5; i++) *(uint4*)(sm.Z + row * ZP + i * 64 + j * 4) = pack8(f + 8 * i);
  }
  __syncthreads();
  if (tid < 256) {
    const int row = tid >> 4, n2 = tid & 15;
    float2 z[20], y[20];
#pragma unroll
    for (int n1 = 0; n1 < 20; n1++) { const uint32_t w = sm.Z[row * ZP + n1 * 16 + n2]; z[n1] = make_float2(bf_lo(w), bf_hi(w)); }
    fft20<0>(z, y);
#pragma unroll
    for (int k1 = 0; k1 < 20; k1++) sm.T[(k1 * 16 + n2) * 17 + row] = k1 ? cmul(y[k1], sm.tw[k1 * 16 + n2]) : y[0];
  }
  __syncthreads();
  const int wp = tid >> 5, up = (tid >> 4) & 1, row = tid & 15, k1 = wp ? (up ? 20 - wp : wp) : up * 10;
  float2 x[16];
#pragma unroll
  for (int n2 = 0; n2 < 16; n2++) x[n2] = sm.T[(k1 * 16 + n2) * 17 + row];
  fft16<0>(x);
  uint32_t* y = g_y + s0 + row;
#pragma unroll
  for (int k2 = 0; k2 < 8; k2++) {
    float2 b;
    if (wp) { b.x = __shfl_xor_sync(~0u, x[15 - k2].x, 16); b.y = __shfl_xor_sync(~0u, x[15 - k2].y, 16); }
    else b = up ? x[15 - k2] : x[(16 - k2) & 15];
    const int k = k1 + 20 * k2; const float2 a = x[k2];
    const float2 E = make_float2(a.x + b.x, a.y - b.y), O = cmul(make_float2(a.y + b.y, b.x - a.x), sm.tp[k]);
    if (k2 == 0 && k1 == 0) { y[0] = pack_f16(E.x + O.x, E.x - O.x); y[160 * 2048] = pack_f16(2.f * x[8].x, -2.f * x[8].y); }
    else { y[k * 2048] = pack_f16(E.x + O.x, E.y + O.y); y[(320 - k) * 2048] = pack_f16(E.x - O.x, O.y - E.y); }
  }
}

__global__ void __launch_bounds__(128) cols_kernel() {
  __shared__ float2 sm[16 * 152];
  const int tid = threadIdx.x, col = blockIdx.x, k1 = tid >> 3, j0 = tid & 7;
  pdl_wait();
  pdl_launch();
  uint32_t* y = g_y + (col == 320 ? 0 : col) * 2048 + tid;
  float2 x[16];
  if (col == 0 || col == 320) {
#pragma unroll
    for (int i = 0; i < 16; i++) x[i] = make_float2(__half2float(((const __half*)(y + i * 128))[col ? 1 : 0]), 0.f);
  } else {
#pragma unroll
    for (int i = 0; i < 16; i++) { const uint32_t w = ldg_cg32(y + i * 128); x[i] = __half22float2(*(const __half2*)&w); }
  }
  uint4 wf[4];
#pragma unroll
  for (int q = 0; q < 4; q++) wf[q] = ldg_cg128(g_wt + col * 2048 + q * 512 + tid * 4);
  fft16<0>(x);
#pragma unroll
  for (int k = 0; k < 16; k++) sm[k * 152 + tid] = k ? cmul(x[k], g_tw[(k - 1) * 128 + tid]) : x[0];
  __syncthreads();
  float2* reg = sm + k1 * 152;
#pragma unroll
  for (int i = 0; i < 16; i++) x[i] = reg[j0 + 8 * i];
  fft16<0>(x);
  __syncwarp();
#pragma unroll
  for (int k = 0; k < 16; k++) reg[k * 9 + j0] = k ? cmul(x[k], g_tw[1920 + (k - 1) * 8 + j0]) : x[0];
  __syncwarp();
#pragma unroll
  for (int i = 0; i < 16; i++) x[i] = reg[(j0 + (i & 8)) * 9 + (i & 7)];
  fft8<0>(x); fft8<0>(x + 8);
#pragma unroll
  for (int q = 0; q < 4; q++) {
    const uint32_t w[4] = {wf[q].x, wf[q].y, wf[q].z, wf[q].w};
#pragma unroll
    for (int r = 0; r < 4; r++) x[4 * q + r] = cmul(x[4 * q + r], make_float2(bf_lo(w[r]), bf_hi(w[r])));
  }
  fft8<1>(x); fft8<1>(x + 8);
#pragma unroll
  for (int i = 0; i < 16; i++) reg[(j0 + (i & 8)) * 9 + (i & 7)] = x[i];
  __syncwarp();
#pragma unroll
  for (int k = 0; k < 16; k++) x[k] = k ? cmulc(reg[k * 9 + j0], g_tw[1920 + (k - 1) * 8 + j0]) : reg[j0];
  fft16<1>(x);
  __syncwarp();
#pragma unroll
  for (int i = 0; i < 16; i++) reg[j0 + 8 * i] = x[i];
  __syncthreads();
#pragma unroll
  for (int k = 0; k < 16; k++) x[k] = k ? cmulc(sm[k * 152 + tid], g_tw[(k - 1) * 128 + tid]) : sm[tid];
  fft16<1>(x);
  const float sc = 1.f / 4096.f;
  if (col == 0 || col == 320) {
#pragma unroll
    for (int i = 0; i < 16; i++) ((bf16*)(y + i * 128))[col ? 1 : 0] = __float2bfloat16(x[i].x * sc);
  } else {
#pragma unroll
    for (int i = 0; i < 16; i++) y[i * 128] = pack_bf16(x[i].x * sc, x[i].y * sc);
  }
}

__global__ void __launch_bounds__(320) rows_inv_kernel(bf16* __restrict__ xout, int do_ln) {
  extern __shared__ __align__(1024) char smraw[]; RowSmem& sm = *(RowSmem*)smraw;
  const int tid = threadIdx.x, s0 = blockIdx.x * 16;
  row_tables(sm);
  __syncthreads();
  pdl_wait();
  pdl_launch();
  const size_t off = (size_t)(s0 + ((tid >> 4) & 15)) * 640 + (tid & 15) * 8;
  uint4 xr[5];
  {
    const int wp = tid >> 5, up = (tid >> 4) & 1, row = tid & 15, k1 = wp ? (up ? 20 - wp : wp) : up * 10;
    const uint32_t* y = g_y + s0 + row;
    uint32_t wa[8], wb[8];
#pragma unroll
    for (int k2 = 0; k2 < 8; k2++) { const int k = k1 + 20 * k2; wa[k2] = ldg_cg32(y + k * 2048); wb[k2] = ldg_cg32(y + (k ? 320 - k : 160) * 2048); }
    if (tid < 256) {
#pragma unroll
      for (int i = 0; i < 5; i++) xr[i] = ldg_cg128(g_x + off + i * 128);
    }
    float2 x[16], r[8];
#pragma unroll
    for (int k2 = 0; k2 < 8; k2++) {
      const float2 a = make_float2(bf_lo(wa[k2]), bf_hi(wa[k2])), b = make_float2(bf_lo(wb[k2]), bf_hi(wb[k2]));
      const float2 E = make_float2(a.x + b.x, a.y - b.y), O = cmulc(make_float2(a.x - b.x, a.y + b.y), sm.tp[k1 + 20 * k2]);
      x[k2] = make_float2(E.x - O.y, E.y + O.x); r[k2] = make_float2(E.x + O.y, O.x - E.y);
      if (k2 == 0 && k1 == 0) { x[0] = make_float2(a.x + a.y, a.x - a.y); r[0] = make_float2(2.f * b.x, -2.f * b.y); }
    }
#pragma unroll
    for (int i = 8; i < 16; i++) {
      if (wp) { x[i].x = __shfl_xor_sync(~0u, r[15 - i].x, 16); x[i].y = __shfl_xor_sync(~0u, r[15 - i].y, 16); }
      else x[i] = up ? r[15 - i] : r[(16 - i) & 7];
    }
    fft16<1>(x);
#pragma unroll
    for (int n2 = 0; n2 < 16; n2++) sm.T[(k1 * 16 + n2) * 17 + row] = x[n2];
  }
  __syncthreads();
  if (tid >= 256) return;
  const int row = tid >> 4, n2 = tid & 15;
  {
    float2 z[20], y[20];
#pragma unroll
    for (int k1 = 0; k1 < 20; k1++) { const float2 t = sm.T[(k1 * 16 + n2) * 17 + row]; z[k1] = k1 ? cmulc(t, sm.tw[k1 * 16 + n2]) : t; }
    fft20<1>(z, y);
    const float sc = 1.f / 640.f;
#pragma unroll
    for (int n1 = 0; n1 < 20; n1++) sm.Z[row * ZP + n1 * 16 + n2] = pack_bf16(y[n1].x * sc, y[n1].y * sc);
  }
  __syncwarp();
  float f[40];
#pragma unroll
  for (int i = 0; i < 5; i++) {
    float a[8], x[8]; unpack8(*(const uint4*)(sm.Z + row * ZP + i * 64 + n2 * 4), a); unpack8(xr[i], x);
#pragma unroll
    for (int e = 0; e < 8; e++) a[e] += x[e];
    const uint4 r = pack8(a); *(uint4*)(xout + off + i * 128) = r; unpack8(r, f + 8 * i);
  }
  if (do_ln) {
    ln_row(f);
#pragma unroll
    for (int i = 0; i < 5; i++) *(uint4*)(g_xn + off + i * 128) = pack8(f + 8 * i);
  }
}

__global__ void __launch_bounds__(320) prep_kernel(const bf16* __restrict__ x, char* comm, const char* wq, const char* wk, const char* wv, const char* wo) {
  extern __shared__ __align__(1024) char smraw[];
  const int tid = threadIdx.x, b = blockIdx.x;
  pdl_launch();
  if (tid >= 256) {
    uint32_t smid; asm volatile("mov.u32 %0, %%smid;" : "=r"(smid));
    volatile uint32_t* res = (volatile uint32_t*)smraw;
    if ((tid & 31) == 0) {
      uint32_t* p = (uint32_t*)(comm + 0x20000 + ((smid & 128) << 7) + (tid == 256 ? 0x1000 : 0) + (smid & 127) * 32);
      uint32_t v, best = ~0u;
      asm volatile("atom.relaxed.gpu.global.exch.b32 %0, [%1], 0;" : "=r"(v) : "l"(p) : "memory"); res[2] = v;
#pragma unroll 1
      for (int i = 0; i < 4; i++) { const uint32_t t0 = clk(); asm volatile("atom.relaxed.gpu.global.add.u32 %0, [%1], 1;" : "=r"(v) : "l"(p) : "memory"); res[2] = v; best = min(best, clk() - t0); }
      res[(tid >> 5) & 1] = best;
    }
    bar_sync(1, 64);
    if (tid == 256) g_side[smid & 255] = max(-200, min(200, (int)(res[0] - res[1])));
    const int q = tid - 256;
    if (q < 40 && b < 128) { const char* w = (q < 10 ? wk : q < 20 ? wq : q < 30 ? wv : wo) + (size_t)b * 40960 + (q % 10) * 4096;
      asm volatile("cp.async.bulk.prefetch.L2.global [%0], 4096;" ::"l"(w) : "memory"); }
    return;
  }
  if (b < 128) {
    const size_t off = (size_t)(b * 16 + (tid >> 4)) * 640 + (tid & 15) * 8;
    float f[40];
#pragma unroll
    for (int i = 0; i < 5; i++) unpack8(*(const uint4*)(x + off + i * 128), f + 8 * i);
    *(uint4*)(comm + g1page(b & 31) + (b < 32 ? 0 : b < 64 ? 0x30000 : b < 96 ? 0x100000 : G2_OFF) + tid * 16) = make_uint4(0, 0, 0, 0);
    ln_row(f);
#pragma unroll
    for (int i = 0; i < 5; i++) *(uint4*)(g_xn + off + i * 128) = pack8(f + 8 * i);
  } else {
    for (int i = (b - 128) * 256 + tid; i < 2 * F_LAYER; i += 1024) g_flags[i] = 0;
    for (int i = (b - 128) * 256 + tid; i < 2040; i += 1024) {
      float s, c;
      if (i < 1920) sincospif(-(float)((i / 128 + 1) * (i & 127)) * (1.f / 1024.f), &s, &c);
      else sincospif(-(float)(((i - 1920) / 8 + 1) * (i & 7)) * (1.f / 64.f), &s, &c);
      g_tw[i] = make_float2(c, s);
    }
    if (b == 128 && tid < 64) *(uint32_t*)(comm + TS_OFF + tid * 4) = 0;
  }
}

typedef CUresult (*EncFn)(CUtensorMap*, CUtensorMapDataType, cuuint32_t, void*, const cuuint64_t*, const cuuint64_t*, const cuuint32_t*, const cuuint32_t*,
                          CUtensorMapInterleave, CUtensorMapSwizzle, CUtensorMapL2promotion, CUtensorMapFloatOOBfill);
static void make_map(EncFn fn, CUtensorMap* m, const void* p, uint64_t cols, uint64_t rows, uint32_t bc, uint32_t br, CUtensorMapSwizzle sw) {
  cuuint64_t gd[2] = {cols, rows}, gs[1] = {cols * 2}; cuuint32_t bd[2] = {bc, br}, es[2] = {1, 1};
  fn(m, CU_TENSOR_MAP_DATA_TYPE_BFLOAT16, 2, (void*)p, gd, gs, bd, es, CU_TENSOR_MAP_INTERLEAVE_NONE, sw, CU_TENSOR_MAP_L2_PROMOTION_L2_128B, CU_TENSOR_MAP_FLOAT_OOB_FILL_NONE);
}
template <class... P, class... A>
static void launch(void (*k)(P...), int grid, int block, int smem, bool pdl, A... a) {
  cudaLaunchConfig_t cfg = {}; cfg.gridDim = dim3(grid); cfg.blockDim = dim3(block); cfg.dynamicSmemBytes = smem; cfg.stream = cudaStreamPerThread;
  cudaLaunchAttribute at[1]; at[0].id = cudaLaunchAttributeProgrammaticStreamSerialization; at[0].val.programmaticStreamSerializationAllowed = 1;
  cfg.attrs = at; cfg.numAttrs = pdl ? 1 : 0;
  cudaLaunchKernelEx(&cfg, k, a...);
}
static const int tune_t[6] = {1740, 1980, 2160, 2490, 2850, 2860}; constexpr int dev_stop = 100, dev_pdl = 1;

extern "C" void kernel_launch(void* const* d_in, const int* in_sizes, int n_in, void* d_out, int out_size) {
  const bf16 *x = (const bf16*)d_in[0], *mem0 = (const bf16*)d_in[1], *Wq = (const bf16*)d_in[2], *Wk = (const bf16*)d_in[3], *Wv = (const bf16*)d_in[4], *Wo = (const bf16*)d_in[5];
  const bf16 *wr = (const bf16*)d_in[8], *wi = (const bf16*)d_in[9];
  constexpr int SM_A = S_END + 1024, SM_R = sizeof(RowSmem), SM_P = 120 * 1024;
  void *p_xn, *p_o, *p_x, *p_comm, *p_flags, *fn; cudaDriverEntryPointQueryResult qr;
  cudaGetSymbolAddress(&p_xn, g_xn); cudaGetSymbolAddress(&p_o, g_o); cudaGetSymbolAddress(&p_x, g_x); cudaGetSymbolAddress(&p_comm, g_comm); cudaGetSymbolAddress(&p_flags, g_flags);
  cudaGetDriverEntryPoint("cuTensorMapEncodeTiled", &fn, cudaEnableDefault, &qr);
  cudaFuncSetAttribute(layer_a_kernel, cudaFuncAttributeMaxDynamicSharedMemorySize, SM_A);
  cudaFuncSetAttribute(rows_fwd_kernel, cudaFuncAttributeMaxDynamicSharedMemorySize, SM_R);
  cudaFuncSetAttribute(rows_inv_kernel, cudaFuncAttributeMaxDynamicSharedMemorySize, SM_R);
  cudaFuncSetAttribute(prep_kernel, cudaFuncAttributeMaxDynamicSharedMemorySize, SM_P);
  CUtensorMap tq, tk, tv, to, to32, tx, tao; EncFn enc = (EncFn)fn;
  make_map(enc, &tq, Wq, 4096, 640, 64, 64, CU_TENSOR_MAP_SWIZZLE_128B); make_map(enc, &tk, Wk, 4096, 640, 64, 64, CU_TENSOR_MAP_SWIZZLE_128B);
  make_map(enc, &tv, Wv, 4096, 640, 64, 64, CU_TENSOR_MAP_SWIZZLE_128B); make_map(enc, &to, Wo, 640, 4096, 64, 64, CU_TENSOR_MAP_SWIZZLE_128B);
  make_map(enc, &to32, Wo, 640, 4096, 16, 256, CU_TENSOR_MAP_SWIZZLE_32B);
  make_map(enc, &tx, p_xn, 640, 2048, 64, 64, CU_TENSOR_MAP_SWIZZLE_128B); make_map(enc, &tao, p_o, 4096, 2048, 64, 64, CU_TENSOR_MAP_SWIZZLE_128B);
  char* comm = (char*)(((uintptr_t)p_comm + (2 << 20) - 1) & ~(uintptr_t)((2 << 20) - 1));
  const bool pdl = dev_pdl;
  launch(prep_kernel, 132, 320, SM_P, false, x, comm, (const char*)Wq, (const char*)Wk, (const char*)Wv, (const char*)Wo);
  for (int l = 0; l < 2; l++) {
    ArgsA a{mem0, comm, (uint32_t*)p_flags + l * F_LAYER, wr, wi, l, {tune_t[0], tune_t[1], tune_t[2]}, {tune_t[3], tune_t[4], tune_t[5]}};
    if (dev_stop > 4 * l + 0) launch(layer_a_kernel, 132, 384, SM_A, pdl, tq, tk, tv, to, to32, tx, tao, a);
    if (dev_stop > 4 * l + 1) launch(rows_fwd_kernel, 128, 320, SM_R, pdl, l ? (const bf16*)p_x : x);
    if (dev_stop > 4 * l + 2) launch(cols_kernel, 321, 128, 0, pdl);
    if (dev_stop > 4 * l + 3) launch(rows_inv_kernel, 128, 320, SM_R, pdl, l ? (bf16*)d_out : (bf16*)p_x, l == 0);
  }
}
```

```cpp
#include <cuda_runtime.h>
#include <cuda_bf16.h>
#include <cuda_fp16.h>
#include <cuda.h>
#include <stdint.h>

typedef __nv_bfloat16 bf16;
#define DEVINL __device__ __forceinline__

__device__ __align__(1024) bf16 g_xn[2048 * 640];
__device__ __align__(1024) bf16 g_x[2048 * 640];
__device__ __align__(1024) char g_kv[64 * 32 * 16384];
__device__ __align__(1024) char g_kvm[64 * 32 * 4096];
__device__ __align__(1024) bf16 g_o[2048 * 4096];
__device__ __align__(1024) bf16 g_part[4 * 2048 * 640];
__device__ __align__(1024) uint32_t g_y[321 * 2048];
__device__ __align__(1024) uint32_t g_wt[321 * 2048];
__device__ __align__(4096) char g_comm[4 << 20];
constexpr int F_KV = 0, F_KM = 1024, F_O = F_KM + 1024, F_P = F_O + 128, F_ROLE = F_P + 32 * 32, F_X = F_ROLE + 64, F_LAYER = F_X + 32;
__device__ __align__(1024) uint32_t g_flags[2 * F_LAYER];
__device__ int g_side[256];

#define POLL_LIMIT (1 << 17)
DEVINL uint32_t smem_u32(const void* p) { return (uint32_t)__cvta_generic_to_shared(p); }
DEVINL uint32_t mapa(uint32_t a, uint32_t r) { uint32_t o; asm volatile("mapa.shared::cluster.u32 %0, %1, %2;" : "=r"(o) : "r"(a), "r"(r)); return o; }
DEVINL uint32_t clk() { uint32_t v; asm volatile("{.reg .b64 w; mov.u64 w, %%clock64; cvt.u32.u64 %0, w;}" : "=r"(v)::"memory"); return v; }
DEVINL void mbar_init(uint32_t bar, uint32_t cnt) { asm volatile("mbarrier.init.shared::cta.b64 [%0], %1;" ::"r"(bar), "r"(cnt) : "memory"); }
DEVINL void mbar_arrive(uint32_t bar) { asm volatile("mbarrier.arrive.shared::cta.b64 _, [%0];" ::"r"(bar) : "memory"); }
DEVINL void mbar_arrive_remote(uint32_t bar) { asm volatile("mbarrier.arrive.shared::cluster.b64 _, [%0];" ::"r"(bar) : "memory"); }
DEVINL void mbar_arrive_tx(uint32_t bar, uint32_t tx) { asm volatile("mbarrier.arrive.expect_tx.shared::cta.b64 _, [%0], %1;" ::"r"(bar), "r"(tx) : "memory"); }
DEVINL void mbar_wait(uint32_t bar, uint32_t ph) {
  asm volatile("{.reg .pred p,q; .reg .b32 c; mov.b32 c, 0;\n"
               "W0: add.u32 c,c,1; setp.lt.u32 q,c,0x100000; mbarrier.try_wait.parity.shared::cta.b64 p, [%0], %1; not.pred p,p; and.pred p,p,q; @p bra W0;}" ::"r"(bar), "r"(ph) : "memory");
}
DEVINL void bar_sync(int id, int n) { asm volatile("bar.sync %0, %1;" ::"r"(id), "r"(n) : "memory"); }
DEVINL void bar_arrive(int id, int n) { asm volatile("bar.arrive %0, %1;" ::"r"(id), "r"(n) : "memory"); }
DEVINL void cluster_sync() { asm volatile("barrier.cluster.arrive.release.aligned; barrier.cluster.wait.acquire.aligned;" ::: "memory"); }
DEVINL void tma_2d(uint32_t dst, const CUtensorMap* tm, int c0, int c1, uint32_t bar) {
  asm volatile("cp.async.bulk.tensor.2d.shared::cluster.global.mbarrier::complete_tx::bytes [%0], [%1, {%2, %3}], [%4];" ::"r"(dst), "l"(tm), "r"(c0), "r"(c1), "r"(bar) : "memory");
}
DEVINL void tma_2d_mc(uint32_t dst, const CUtensorMap* tm, int c0, int c1, uint32_t bar) {
  asm volatile("cp.async.bulk.tensor.2d.shared::cluster.global.mbarrier::complete_tx::bytes.multicast::cluster [%0], [%1, {%2, %3}], [%4], %5;" ::"r"(dst), "l"(tm), "r"(c0), "r"(c1), "r"(bar), "h"((uint16_t)3) : "memory");
}
DEVINL void bulk_g2s(uint32_t dst, const void* src, uint32_t bytes, uint32_t bar) {
  asm volatile("cp.async.bulk.shared::cluster.global.mbarrier::complete_tx::bytes [%0], [%1], %2, [%3];" ::"r"(dst), "l"(src), "r"(bytes), "r"(bar) : "memory");
}
DEVINL void l2_prefetch(const void* p, uint32_t bytes) { asm volatile("cp.async.bulk.prefetch.L2.global [%0], %1;" ::"l"(p), "r"(bytes) : "memory"); }
DEVINL void fence_proxy_async() { asm volatile("fence.proxy.async.global;" ::: "memory"); }
DEVINL void ldsm4t(uint32_t* r, uint32_t a) { asm volatile("ldmatrix.sync.aligned.m8n8.x4.trans.shared.b16 {%0,%1,%2,%3}, [%4];" : "=r"(r[0]), "=r"(r[1]), "=r"(r[2]), "=r"(r[3]) : "r"(a) : "memory"); }
DEVINL void stsm4(uint32_t a, uint32_t r0, uint32_t r1, uint32_t r2, uint32_t r3) { asm volatile("stmatrix.sync.aligned.m8n8.x4.shared.b16 [%0], {%1,%2,%3,%4};" ::"r"(a), "r"(r0), "r"(r1), "r"(r2), "r"(r3) : "memory"); }
DEVINL void mma16816(float* d, const uint32_t* a, uint32_t b0, uint32_t b1) {
  asm volatile("mma.sync.aligned.m16n8k16.row.col.f32.bf16.bf16.f32 {%0,%1,%2,%3}, {%4,%5,%6,%7}, {%8,%9}, {%0,%1,%2,%3};"
               : "+f"(d[0]), "+f"(d[1]), "+f"(d[2]), "+f"(d[3]) : "r"(a[0]), "r"(a[1]), "r"(a[2]), "r"(a[3]), "r"(b0), "r"(b1));
}
DEVINL void mma16816z(float* d, const uint32_t* a, uint32_t b0, uint32_t b1) {
  asm volatile("mma.sync.aligned.m16n8k16.row.col.f32.bf16.bf16.f32 {%0,%1,%2,%3}, {%4,%5,%6,%7}, {%8,%9}, {%10,%10,%10,%10};"
               : "=f"(d[0]), "=f"(d[1]), "=f"(d[2]), "=f"(d[3]) : "r"(a[0]), "r"(a[1]), "r"(a[2]), "r"(a[3]), "r"(b0), "r"(b1), "f"(0.f));
}
DEVINL void mma1688z(float* d, uint32_t a0, uint32_t a1, uint32_t b0) {
  asm volatile("mma.sync.aligned.m16n8k8.row.col.f32.bf16.bf16.f32 {%0,%1,%2,%3}, {%4,%5}, {%6}, {%7,%7,%7,%7};"
               : "=f"(d[0]), "=f"(d[1]), "=f"(d[2]), "=f"(d[3]) : "r"(a0), "r"(a1), "r"(b0), "f"(0.f));
}
DEVINL uint32_t movm(uint32_t a) { uint32_t r; asm volatile("movmatrix.sync.aligned.m8n8.trans.b16 %0, %1;" : "=r"(r) : "r"(a)); return r; }
DEVINL uint32_t pack_bf16(float lo, float hi) { uint32_t r; asm("cvt.rn.bf16x2.f32 %0, %1, %2;" : "=r"(r) : "f"(hi), "f"(lo)); return r; }
DEVINL uint32_t pack_f16(float lo, float hi) { uint32_t r; asm("cvt.rn.f16x2.f32 %0, %1, %2;" : "=r"(r) : "f"(hi), "f"(lo)); return r; }
DEVINL float bf_lo(uint32_t w) { return __uint_as_float(w << 16); }
DEVINL float bf_hi(uint32_t w) { return __uint_as_float(w & 0xffff0000u); }
DEVINL uint32_t hadd2bf(uint32_t a, uint32_t b) { uint32_t r; asm("add.rn.bf16x2 %0, %1, %2;" : "=r"(r) : "r"(a), "r"(b)); return r; }
DEVINL uint32_t hmax2bf(uint32_t a, uint32_t b) { uint32_t r; asm("max.bf16x2 %0, %1, %2;" : "=r"(r) : "r"(a), "r"(b)); return r; }
DEVINL uint32_t lds32(uint32_t a) { uint32_t v; asm volatile("ld.shared.u32 %0, [%1];" : "=r"(v) : "r"(a) : "memory"); return v; }
DEVINL uint2 lds64(uint32_t a) { uint2 v; asm volatile("ld.shared.v2.u32 {%0,%1}, [%2];" : "=r"(v.x), "=r"(v.y) : "r"(a) : "memory"); return v; }
DEVINL uint4 lds128(uint32_t a) { uint4 v; asm volatile("ld.shared.v4.u32 {%0,%1,%2,%3}, [%4];" : "=r"(v.x), "=r"(v.y), "=r"(v.z), "=r"(v.w) : "r"(a) : "memory"); return v; }
DEVINL void sts32(uint32_t a, uint32_t v) { asm volatile("st.shared.u32 [%0], %1;" ::"r"(a), "r"(v) : "memory"); }
DEVINL void sts64(uint32_t a, uint32_t x, uint32_t y) { asm volatile("st.shared.v2.u32 [%0], {%1,%2};" ::"r"(a), "r"(x), "r"(y) : "memory"); }
DEVINL void sts128(uint32_t a, uint4 v) { asm volatile("st.shared.v4.u32 [%0], {%1,%2,%3,%4};" ::"r"(a), "r"(v.x), "r"(v.y), "r"(v.z), "r"(v.w) : "memory"); }
DEVINL void stasync64(uint32_t a, uint32_t x, uint32_t y, uint32_t bar) { asm volatile("st.async.weak.shared::cluster.mbarrier::complete_tx::bytes.v2.b32 [%0], {%1,%2}, [%3];" ::"r"(a), "r"(x), "r"(y), "r"(bar) : "memory"); }
DEVINL uint4 ldg_rlx128(const void* p) { uint4 v; asm volatile("{.reg .b64 a,b; ld.relaxed.gpu.global.v2.b64 {a,b}, [%4]; mov.b64 {%0,%1}, a; mov.b64 {%2,%3}, b;}" : "=r"(v.x), "=r"(v.y), "=r"(v.z), "=r"(v.w) : "l"(p) : "memory"); return v; }
DEVINL uint2 ldg_rlx64(const void* p) { uint2 v; asm volatile("ld.relaxed.gpu.global.v2.u32 {%0,%1}, [%2];" : "=r"(v.x), "=r"(v.y) : "l"(p) : "memory"); return v; }
DEVINL void stg_rlx64(void* p, uint32_t x, uint32_t y) { asm volatile("{.reg .b64 a; mov.b64 a, {%1,%2}; st.relaxed.gpu.global.b64 [%0], a;}" ::"l"(p), "r"(x), "r"(y) : "memory"); }
DEVINL void stg_rlx32(void* p, uint32_t x) { asm volatile("st.relaxed.gpu.global.u32 [%0], %1;" ::"l"(p), "r"(x) : "memory"); }
DEVINL uint4 ldg_cg128(const void* p) { uint4 v; asm volatile("ld.global.cg.v4.u32 {%0,%1,%2,%3}, [%4];" : "=r"(v.x), "=r"(v.y), "=r"(v.z), "=r"(v.w) : "l"(p) : "memory"); return v; }
DEVINL uint32_t ldg_cg32(const void* p) { uint32_t v; asm volatile("ld.global.cg.u32 %0, [%1];" : "=r"(v) : "l"(p) : "memory"); return v; }
DEVINL uint32_t ldg32_if(const void* p, int on) { uint32_t v; asm volatile("{.reg .pred q; setp.ne.s32 q, %2, 0; mov.u32 %0, 0; @q ld.global.cg.u32 %0, [%1];}" : "=r"(v) : "l"(p), "r"(on) : "memory"); return v; }
DEVINL uint4 ldg128_if(const void* p, int on) { uint4 v; asm volatile("{.reg .pred q; setp.ne.s32 q, %5, 0; mov.u32 %0, 0; mov.u32 %1, 0; mov.u32 %2, 0; mov.u32 %3, 0; @q ld.global.cg.v4.u32 {%0,%1,%2,%3}, [%4];}" : "=r"(v.x), "=r"(v.y), "=r"(v.z), "=r"(v.w) : "l"(p), "r"(on) : "memory"); return v; }
DEVINL void stg32_if(void* p, uint32_t v, int on) { asm volatile("{.reg .pred q; setp.ne.s32 q, %2, 0; @q st.global.u32 [%0], %1;}" ::"l"(p), "r"(v), "r"(on) : "memory"); }
DEVINL void stg128_if(void* p, uint4 v, int on) { asm volatile("{.reg .pred q; setp.ne.s32 q, %5, 0; @q st.global.v4.u32 [%0], {%1,%2,%3,%4};}" ::"l"(p), "r"(v.x), "r"(v.y), "r"(v.z), "r"(v.w), "r"(on) : "memory"); }
DEVINL uint4 ldg_ca128(const void* p) { uint4 v; asm volatile("ld.global.ca.v4.u32 {%0,%1,%2,%3}, [%4];" : "=r"(v.x), "=r"(v.y), "=r"(v.z), "=r"(v.w) : "l"(p) : "memory"); return v; }
DEVINL uint32_t ldg_ca32(const void* p) { uint32_t v; asm volatile("ld.global.ca.u32 %0, [%1];" : "=r"(v) : "l"(p) : "memory"); return v; }
DEVINL void flag_wait(const uint32_t* p, uint32_t want) {
  uint32_t v;
#pragma unroll 1
  for (int n = 0; n < POLL_LIMIT; n++) { asm volatile("ld.acquire.gpu.global.u32 %0, [%1];" : "=r"(v) : "l"(p) : "memory"); if (v >= want) break; __nanosleep(40); }
}
DEVINL void flag_wait_warp(const uint32_t* p, uint32_t want) {
  uint32_t v; int n = 0;
  do { asm volatile("ld.acquire.gpu.global.u32 %0, [%1];" : "=r"(v) : "l"(p) : "memory"); } while (__any_sync(~0u, v < want && ++n < POLL_LIMIT));
}
DEVINL void flag_add(uint32_t* p) { asm volatile("red.release.gpu.global.add.u32 [%0], 1;" ::"l"(p) : "memory"); }
DEVINL void flag_set(uint32_t* p, uint32_t v) { asm volatile("fence.acq_rel.gpu; st.relaxed.gpu.global.u32 [%0], %1;" ::"l"(p), "r"(v) : "memory"); }
DEVINL uint32_t ldg_rlx32(const void* p) { uint32_t v; asm volatile("ld.relaxed.gpu.global.u32 %0, [%1];" : "=r"(v) : "l"(p) : "memory"); return v; }
DEVINL float ex2(float x) { float y; asm("ex2.approx.ftz.f32 %0, %1;" : "=f"(y) : "f"(x)); return y; }
DEVINL float rcp(float x) { float y; asm("rcp.approx.ftz.f32 %0, %1;" : "=f"(y) : "f"(x)); return y; }
DEVINL uint32_t opaque(uint32_t x) { return __shfl_sync(~0u, x, threadIdx.x & 31); }
DEVINL uint32_t launder(uint32_t x) { asm volatile("" : "+r"(x)); return x; }
DEVINL void pdl_wait() { asm volatile("griddepcontrol.wait;" ::: "memory"); }
DEVINL void pdl_launch() { asm volatile("griddepcontrol.launch_dependents;" ::: "memory"); }
#define LOGS(cta, i)
#define LOGK(k, i)
#define LOG(cta, i)
#define LOGV(cta, i, v)
constexpr float SM_SCALE = 0.08838834764831845f * 1.4426950408889634f;

DEVINL void unpack8(uint4 v, float* f) { f[0] = bf_lo(v.x); f[1] = bf_hi(v.x); f[2] = bf_lo(v.y); f[3] = bf_hi(v.y); f[4] = bf_lo(v.z); f[5] = bf_hi(v.z); f[6] = bf_lo(v.w); f[7] = bf_hi(v.w); }
DEVINL uint4 pack8(const float* f) { return make_uint4(pack_bf16(f[0], f[1]), pack_bf16(f[2], f[3]), pack_bf16(f[4], f[5]), pack_bf16(f[6], f[7])); }
DEVINL void ln_row(float* f) {
  float s = 0.f;
#pragma unroll
  for (int i = 0; i < 40; i++) s += f[i];
#pragma unroll
  for (int o = 1; o < 16; o <<= 1) s += __shfl_xor_sync(~0u, s, o);
  const float mean = s * (1.f / 640.f); float q = 0.f;
#pragma unroll
  for (int i = 0; i < 40; i++) { f[i] -= mean; q = fmaf(f[i], f[i], q); }
#pragma unroll
  for (int o = 1; o < 16; o <<= 1) q += __shfl_xor_sync(~0u, q, o);
  const float rs = rsqrtf(q * (1.f / 640.f) + 1e-5f);
#pragma unroll
  for (int i = 0; i < 40; i++) f[i] *= rs;
}

struct ArgsA {
  const bf16* x; const bf16* mem0; char* comm; uint32_t* flags; const bf16* wr; const bf16* wi; const char* wq; const char* wo;
  int layer; int ta[3], tb[3];
};

#define VP 4
#define HELD 0x2557
#define PRE 4
#define VPRE 4
#define R0 5
#define TRK 30
#define TEXP 0
#define TRD 0
#define TKV 300
#define W1D 120
constexpr int C_WV = 0;
constexpr int C_WO = 81920;
constexpr int C_KV = 163840;
constexpr int C_M  = C_KV + 24576;
constexpr int C_QK = C_M + 10240;
constexpr int C_VP = C_QK + 4096;
constexpr int C_S  = C_VP + 4096;
constexpr int C_O  = C_S + 2048;
constexpr int C_R  = C_O + 2048;
constexpr int S_BAR = 229376;
constexpr int S_END = S_BAR + 256;
enum { BAR_M1 = 1, BAR_QK = 2, BAR_O = 3, BAR_H = 4, BAR_X = 5, BAR_M2 = 6, BAR_W = 7  , BAR_E = 9 };
constexpr int B_W = 0, B_S = 8, B_W2 = 16, B_KV = 24, B_WV = 40, B_WO = 48;
constexpr int G2_OFF = 0x130000, TS_OFF = 0x11000;

#define SCHED(x, c) asm volatile("{.reg .pred p; setp.eq.u32 p, %0, %1; @p exit;}" ::"r"(x), "r"(0x7fff0001u + 2 * (c)) : "memory")
DEVINL uint32_t g1page(uint32_t L) { L = ((L & 7) | ((L & 24) << 2)) << 1; return (L | (__popc(L & 0xb2) & 1)) << 12; }
DEVINL void spin_until(uint32_t t) {
  asm volatile("{.reg .pred p; .reg .b32 c; .reg .b64 w;\nS0: mov.u64 w, %%clock64; cvt.u32.u64 c, w; sub.u32 c, %0, c; setp.lt.u32 p, c, 16384; @p bra S0;}" ::"r"(t) : "memory");
}
DEVINL uint32_t wait_until(uint32_t t, uint32_t z) { uint32_t r;
  asm volatile("{.reg .pred p; .reg .b32 c,x; .reg .b64 w;\nT0: .branchtargets L0, L1, L2, L3, L4, L5, L6, L7, L8, L9, L10;\n"
               "S0: mov.u64 w, %%clock64; cvt.u32.u64 c, w; sub.u32 c, %1, c; sub.u32 x, c, 72; setp.lt.u32 p, x, 16384; @p bra S0;\n"
               "max.s32 c, c, 0; min.s32 c, c, 71; mul.lo.u32 c, c, 37; shr.u32 c, c, 8; mov.u32 x, %2;\nbrx.idx.uni c, T0;\n"
               "L10: mul.lo.u32 x, x, x; L9: mul.lo.u32 x, x, x; L8: mul.lo.u32 x, x, x; L7: mul.lo.u32 x, x, x; L6: mul.lo.u32 x, x, x; L5: mul.lo.u32 x, x, x; L4: mul.lo.u32 x, x, x; L3: mul.lo.u32 x, x, x; L2: mul.lo.u32 x, x, x; L1: mul.lo.u32 x, x, x; L0: mov.u32 %0, x;}" : "=r"(r) : "r"(t), "r"(z) : "memory"); return r;
}
DEVINL void gtime(uint32_t& G16, uint32_t& C) {
  asm volatile("{.reg .b64 w; .reg .b32 g,g0,a;\n mov.u64 w, %%clock64; cvt.u32.u64 %1, w; mov.u64 w, %%globaltimer; cvt.u32.u64 g0, w; mul.lo.u32 a, g0, -8;\n"
               "mov.u64 w, %%globaltimer; cvt.u32.u64 g, w; add.u32 a, a, g; mov.u64 w, %%globaltimer; cvt.u32.u64 g, w; add.u32 a, a, g; mov.u64 w, %%globaltimer; cvt.u32.u64 g, w; add.u32 a, a, g; mov.u64 w, %%globaltimer; cvt.u32.u64 g, w; add.u32 a, a, g; mov.u64 w, %%globaltimer; cvt.u32.u64 g, w; add.u32 a, a, g; mov.u64 w, %%globaltimer; cvt.u32.u64 g, w; add.u32 a, a, g; mov.u64 w, %%globaltimer; cvt.u32.u64 g, w; add.u32 a, a, g; mov.u64 w, %%globaltimer; cvt.u32.u64 g, w; add.u32 a, a, g; \n mul.lo.u32 a, a, 455; shr.u32 a, a, 8; mad.lo.u32 %0, g0, 16, a;}" : "=r"(G16), "=r"(C)::"memory");
}
DEVINL uint32_t pack_tag(float lo, float hi, uint32_t tg) {
  const uint32_t w = pack_bf16(lo, __uint_as_float(tg | 0x3F800000u)), a = __float_as_uint(hi) + (tg ^ 0x10000u); uint32_t r;
  asm("lop3.b32 %0, %1, %2, 0xFFFE0000, 0xE4;" : "=r"(r) : "r"(a), "r"(w)); return r;
}
DEVINL void load_kv(uint32_t sb, int h, int j, int s) {
  asm volatile("{.reg .pred p; elect.sync _|p, 0xffffffff;\n fence.proxy.async.global;\n @p mbarrier.arrive.expect_tx.shared::cta.b64 _, [%2], 12288;\n"
               " @p cp.async.bulk.shared::cluster.global.mbarrier::complete_tx::bytes [%0], [%1], 12288, [%2];}"
               ::"r"(sb + C_KV + (s & 1) * 12288), "l"(g_kv + (size_t)(s * 32 + h) * 16384 + j * 4096), "r"(sb + S_BAR + B_KV + (s & 1) * 8) : "memory");
}

template <int KH>
DEVINL void chain_mma(uint32_t sb0, const ArgsA& args) {
  const int lane = threadIdx.x & 31, mg = (threadIdx.x >> 5) & 3, mi = lane >> 3, r = lane & 7;
  const uint32_t aW = opaque(sb0 + (uint32_t)(((mi >> 1) * 8 + r) * 128 + (((mg + 4 * (mi & 1)) ^ r) << 4)));
  const uint32_t aL = opaque(sb0 + lane * 16);
  const uint32_t aLm = opaque(sb0 + mg * 512 + lane * 16);
#define sb (launder(aL) & ~511u)
  constexpr int OV = C_WV + KH * 40960, OM = C_M + KH * 5120, NF = KH ? 16 : 24;
  auto owo = [](int f) { return C_WO + (KH ? 1 + 3 * (f >> 3) : (f < 8 ? 0 : 1 + (f >> 3))) * 16384 + (f & 7) * 2048; };
  auto held = [](int k) { return (HELD >> k) & 1; };
  auto rank = [](int k) { return __popc(HELD & ((1 << k) - 1)); };
  uint32_t wq[20][4], wk[20][4];
  mbar_wait(sb + S_BAR + B_W, 0);
#pragma unroll
  for (int k = 0; k < 12; k++) { ldsm4t(wq[k], aW + OV + k * 2048); ldsm4t(wk[k], aW + C_WO + KH * 40960 + k * 2048); }
  bar_arrive(BAR_H, 288);
  mbar_wait(sb + S_BAR + B_W2, 0);
#pragma unroll
  for (int k = 12; k < 20; k++) { ldsm4t(wq[k], aW + OV + k * 2048); ldsm4t(wk[k], aW + C_WO + KH * 40960 + k * 2048); }
  bar_sync(BAR_E, 384);
  mbar_wait(sb + S_BAR + B_WV, 0);
#pragma unroll 1
  for (int s = 0;; s++) {
    uint32_t v[20][4], b[10][4];
    if (s == 0) {
#pragma unroll
      for (int k = 0; k < 20; k++) if (held(k)) ldsm4t(v[k], aW + OV + k * 2048);
      ldsm4t(b[0], aL + OM); ldsm4t(b[1], aL + OM + 512);
    } else {
      const uint32_t o = launder(aLm) - sb;
      const char* p = args.comm + (lds32(sb + C_R + 84) + KH * 2048 + o);
      const uint32_t am = sb + OM + (o & 0x400) + ((o & 0x3f0) >> 1), tm = 0u - ((s + args.layer) & 1);
#pragma unroll
      for (int k = 0; k < 20; k++) if (held(k) && rank(k) < VPRE) ldsm4t(v[k], aW + OV + k * 2048);
      p += wait_until(lds32(sb + C_R + 48) + args.tb[0], am & 1);
      uint4 a = ldg_rlx128(p);
#pragma unroll
      for (int k = 0; k < 20; k++) if (held(k) && rank(k) >= VPRE) ldsm4t(v[k], aW + OV + k * 2048);
      SCHED(am ^ tm, 29);
      int lim = 0;
      while (true) {
        sts64(am, a.x, a.z); sts64(am + 512, a.y, a.w);
        uint32_t bad;
        asm volatile("{.reg .pred p,q; setp.ne.u32 q, %1, 0; bar.red.or.pred p, %2, 128, q; selp.u32 %0, 1, 0, p;}" : "=r"(bad) : "r"(((a.x ^ tm) | (a.z ^ tm)) & 0x10000u), "n"(BAR_W + KH) : "memory");
        ldsm4t(b[0], aL + OM); ldsm4t(b[1], aL + OM + 512);
        if (!bad || ++lim >= POLL_LIMIT) break;
        a = ldg_rlx128(p);
      }
    }
    float cq[4], ck[4], cv[4];
#pragma unroll
    for (int k = 0; k < 20; k++) {
      const int p = k >> 1;
      const uint32_t b0 = b[p][(k & 1) * 2], b1 = b[p][(k & 1) * 2 + 1];
      if (k == 0) { mma16816z(cv, v[0], b0, b1); mma16816z(cq, wq[k], b0, b1); mma16816z(ck, wk[k], b0, b1); }
      else { if (k < 20 - VP) mma16816(cv, v[k], b0, b1); mma16816(cq, wq[k], b0, b1); mma16816(ck, wk[k], b0, b1); }
      if (k == 5) bar_sync(BAR_M1, 288);
      if (k == 9) bar_sync(BAR_M2, 384);
      if ((k & 1) && p + 2 < 10) ldsm4t(b[p + 2], aL + OM + (p + 2) * 512);
      if (k + 3 < 20 - VP && !held(k + 3)) ldsm4t(v[k + 3], aW + OV + (k + 3) * 2048);
      if (k >= 20 - VP && k < 20 - VP + PRE && !held(k)) ldsm4t(v[k], aW + OV + k * 2048);
    }
    stsm4(aLm + C_QK + KH * 2048, pack_bf16(cq[0], cq[1]), pack_bf16(cq[2], cq[3]), pack_bf16(ck[0], ck[1]), pack_bf16(ck[2], ck[3]));
    bar_arrive(BAR_QK, 384);
    SCHED(aL, 1);
    const uint32_t l8 = (launder(aL) & 511) >> 1, px = lds32(sb + C_R + 80);
#pragma unroll
    for (int k = 20 - VP + PRE; k < 20; k++) if (!held(k)) ldsm4t(v[k], aW + OV + k * 2048);
#pragma unroll
    for (int k = 20 - VP; k < 20; k++) {
      const int p = k >> 1, q = k - 20 + VP; const uint32_t b0 = b[p][(k & 1) * 2], b1 = b[p][(k & 1) * 2 + 1];
      if (q % 3 == 0) mma16816(cv, v[k], b0, b1); else if (q == 1) mma16816z(cq, v[k], b0, b1); else if (q == 2) mma16816z(ck, v[k], b0, b1);
      else if (q % 3 == 1) mma16816(cq, v[k], b0, b1); else mma16816(ck, v[k], b0, b1);
    }
    if (VP >= 3) {
#pragma unroll
      for (int i = 0; i < 4; i++) cv[i] += cq[i] + ck[i];
    }
    { const uint32_t vx = pack_bf16(cv[0], cv[1]), vy = pack_bf16(cv[2], cv[3]);
      const uint32_t av = aLm - l8 + C_VP + KH * 256;
      stasync64(av + 2048 + px, vx, vy, sb + S_BAR + B_S + px);
      sts64(av, vx, vy);
      __syncwarp();
      if (l8 == 0) mbar_arrive(sb + S_BAR + B_S); }
    if (s == 63) break;
    uint32_t w[NF][4];
    {
      const uint32_t zero = px & 1; uint32_t a = aW;
      if (s == 0) mbar_wait(sb + S_BAR + B_WO, 0);
      if (TRK) spin_until(clk() + TRK);
#pragma unroll
      for (int f = 0; f < 8; f++) { ldsm4t(w[f], a + owo(f)); uint32_t d = w[f][0] & zero;
#pragma unroll
        for (int q = 0; q < TRD; q++) d = __popc(d);
        a = aW + d; }
    }
    const uint32_t tg = ((s + args.layer + 1) & 1) << 16;
    const uint32_t ar = sb + C_R + 128 + (l8 & 120);
    const uint32_t o = launder(aLm) - sb;
    const uint2 jh = lds64(sb + C_R + 88);
    char* g1w = args.comm + (g1page(jh.x + KH * 8 + (o >> 8)) + ((o & 128) << 4) + jh.y + ((o & 112) >> 1));
    bar_sync(BAR_O, 384);
    uint32_t ob[16];
#pragma unroll
    for (int p = 0; p < 4; p++) ldsm4t(ob + 4 * p, aL + C_O + p * 512);
    const uint2 rr = lds64(ar);
    float r0 = __uint_as_float(rr.x), r1 = __uint_as_float(rr.y);
    r0 += __shfl_xor_sync(~0u, r0, 4); r1 += __shfl_xor_sync(~0u, r1, 4); r0 += __shfl_xor_sync(~0u, r0, 8); r1 += __shfl_xor_sync(~0u, r1, 8);
    r0 = rcp(r0); r1 = rcp(r1);
#pragma unroll
    for (int f = 0; f < NF; f++) {
      const int k = f & 7; const uint32_t* A = w[f];
      if (k == 0) mma16816z(cq, A, ob[0], ob[1]); else if (k == 1) mma16816z(ck, A, ob[2], ob[3]);
      else if (k & 1) mma16816(ck, A, ob[2 * k], ob[2 * k + 1]); else mma16816(cq, A, ob[2 * k], ob[2 * k + 1]);
      constexpr int RA = KH ? 0 : R0;
      if (k >= 2 && k < 2 + RA && (f & ~7) + 8 < NF) ldsm4t(w[f + 6], aW + owo(f + 6));
      if (k == 7) {
        stg_rlx64(g1w + (f < 8 ? 0 : (f < 16 && KH == 0) ? 0x30000 : 0x100000), pack_tag((cq[0] + ck[0]) * r0, (cq[1] + ck[1]) * r1, tg), pack_bf16((cq[2] + ck[2]) * r0, (cq[3] + ck[3]) * r1));
        if (KH == 1 && f == 7) spin_until(clk() + W1D); else SCHED(aL, 32 + f);
#pragma unroll
        for (int q = RA; q < 8; q++) if (f + 1 < NF) ldsm4t(w[f + 1 + q], aW + owo(f + 1 + q));
        if (KH == 1 && f == 7) SCHED(aL, 33);
      }
    }
  }
}

#undef sb
DEVINL void chain_helper(uint32_t sb, uint32_t px, int h, int j, const ArgsA& args, const CUtensorMap* tq, const CUtensorMap* tk, const CUtensorMap* tv, const CUtensorMap* to) {
  const int c = 2 * h + j;
  const uint32_t bW = sb + S_BAR + B_W, bS = sb + S_BAR + B_S, bKV = sb + S_BAR + B_KV;
  const uint32_t lane0 = opaque(threadIdx.x & 31);
  const uint32_t warp = __reduce_max_sync(~0u, (threadIdx.x >> 5) & 3);
  uint32_t G0, C0;
  { const int tid = threadIdx.x - 256;
    if (tid == 0) { mbar_arrive_tx(bW, 98304); mbar_arrive_tx(bW + B_W2, 65536); mbar_arrive_tx(bW + B_WV, 81920); mbar_arrive_tx(bW + B_WO, 81920);
#pragma unroll 1
      for (int q = 0; q < 10; q++) { const int i = (q & 1) * 5 + (q >> 1); const uint32_t bar = q < 6 ? bW : bW + B_W2;
        tma_2d(sb + C_WV + i * 8192, tq, h * 128 + j * 64, i * 64, bar); tma_2d(sb + C_WO + i * 8192, tk, h * 128 + j * 64, i * 64, bar); } }
    gtime(G0, C0);
    sts128(sb + C_R + 80, make_uint4(px, g1page((h & 3) * 4) + G2_OFF, j * 16, h * 64));
#pragma unroll
    for (int i = 0; i < 5; i++) { const int q = tid + i * 128, n = q & 7, d0 = (q >> 3) * 8; const uint4 v = *(const uint4*)(args.mem0 + n * 640 + d0); const uint32_t w[4] = {v.x, v.y, v.z, v.w};
#pragma unroll
      for (int e = 0; e < 8; e++) asm volatile("st.shared.u16 [%0], %1;" ::"r"(sb + C_M + (d0 + e) * 16 + n * 2), "h"((unsigned short)(w[e >> 1] >> ((e & 1) * 16))) : "memory"); }
    auto round2 = [&](int q0, int q1) {
#pragma unroll 1
      for (int q = q0; q < q1; q++) { const int i = (q & 1) * 5 + (q >> 1); tma_2d(sb + C_WV + i * 8192, tv, h * 128 + j * 64, i * 64, bW + B_WV); }
#pragma unroll 1
      for (int q = q0; q < q1; q++) { const int i = (q & 1) * 5 + (q >> 1); tma_2d(sb + C_WO + i * 8192, to, j * 320 + (i >> 1) * 64, h * 128 + ((i & 1) ^ j) * 64, bW + B_WO); } };
    if (warp == 0) { bar_sync(BAR_H, 288); if (tid == 0) round2(0, 6); __syncwarp(); }
    bar_sync(BAR_E, 384);
    if (tid == 0) round2(6, 10);
    if (warp == 3) {
      if (tid == 96) LOG(c, 250);
      flag_wait_warp(args.flags + F_KV + h, 2);
      load_kv(sb, h, j, 0); load_kv(sb, h, j, 1); if (tid == 96) LOG(c, 251);
    }
  }
  auto calib = [&]() { uint32_t G, C; gtime(G, C);
    const float rt = (float)(C - C0) * rcp((float)(G - G0));
    sts128(sb + C_R + 32, make_uint4(G, C, __float_as_uint(rt), __float_as_uint(rcp(rt)))); __syncwarp(); };
  auto do_export = [&](int s, uint32_t lane, bool arrive) {
    uint32_t k0[2][4], k1[2][4]; uint2 a[4], b[4];
    const uint32_t ak = sb + C_QK + 256 + (lane >> 4) * 512 + (lane & 15) * 16, av = sb + C_VP + lane * 8;
#pragma unroll
    for (int i = 0; i < 2; i++) { ldsm4t(k0[i], ak + i * 1024); ldsm4t(k1[i], ak + i * 1024 + 2048); }
#pragma unroll
    for (int i = 0; i < 4; i++) { a[i] = lds64(av + i * 512); b[i] = lds64(av + i * 512 + 256); }
    char* dst = g_kvm + ((s * 32 + h) * 4096 + j * 1024);
#pragma unroll
    for (int i = 0; i < 2; i++) *(uint4*)(dst + i * 512 + lane * 16) = make_uint4(hadd2bf(k0[i][0], k1[i][0]), hadd2bf(k0[i][1], k1[i][1]), hadd2bf(k0[i][2], k1[i][2]), hadd2bf(k0[i][3], k1[i][3]));
#pragma unroll
    for (int i = 0; i < 4; i++) { uint32_t* q = (uint32_t*)(dst + 2048 + i * 128) + lane; q[0] = hadd2bf(a[i].x, b[i].x); q[128] = hadd2bf(a[i].y, b[i].y); }
    if (arrive) bar_arrive(BAR_M2, 384);
    __syncwarp();
  };
  if (warp == 0) { calib(); bar_arrive(BAR_M1, 288); } else bar_arrive(BAR_M2, 384);
#pragma unroll 1
  for (int s = 0;; s++) {
    const uint32_t ph = s & 1, kvb = sb + C_KV + ph * 12288;
    uint32_t lane = __shfl_sync(~0u, lane0, lane0);
    if (warp == 0) {
      if (lane == 0) mbar_arrive_tx(bS, s < 63 ? 3072 : 2048);
      const uint4 cal = lds128(sb + C_R + 32);
      bar_sync(BAR_M2, 384);
      sts32(sb + C_R + 52, 0);
      const uint32_t E = clk();
      if (lane == 0) { const uint32_t e16 = cal.x + (uint32_t)__float2int_rn((float)(int)(E - cal.y) * __uint_as_float(cal.w));
        stg_rlx32(args.comm + TS_OFF + c * 4, e16); sts128(sb + C_R + 64, make_uint4(e16, E, cal.z, 0)); }
      __syncwarp();
    }
    if (s == 63) { bar_sync(BAR_QK, 384); mbar_wait(bS, 1); if (warp == 3) { do_export(63, lane, false); flag_set(args.flags + F_KM + h * 32 + j, 64); } break; }
    mbar_wait(bKV + ph * 8, (s >> 1) & 1);
    const uint32_t mi = lane >> 3, r = lane & 7, zero = lane >> 5;
    {
      uint32_t qa[4][4], km[4]; uint2 kb[4]; float s0[4], s1[4], s2[4];
      const uint32_t aK = kvb + j * 8192 + warp * 1024 + lane * 16, aQ = sb + C_QK + (mi & 1) * 2048 + ((mi >> 1) * 8 + r) * 16;
      const uint32_t aKm = sb + C_QK + 256 + warp * 512 + (lane >> 4) * 2048 + (lane & 15) * 16;
#pragma unroll
      for (int i = 0; i < 4; i++) kb[i] = lds64(aK + ((warp ^ i) >> 1) * 512 + ((warp ^ i) & 1) * 8);
      const uint32_t aH = sb + C_S + warp * 256 + lane * 8, aR = aH + 1024 + px;
      SCHED(aQ ^ aR ^ aKm ^ ((kb[0].x ^ kb[1].x ^ kb[2].x ^ kb[3].x) & zero), 60);
      bar_sync(BAR_QK, 384);
      ldsm4t(qa[0], aQ + warp * 512); ldsm4t(km, aKm); ldsm4t(qa[1], aQ + (warp ^ 1) * 512); ldsm4t(qa[2], aQ + (warp ^ 2) * 512); ldsm4t(qa[3], aQ + (warp ^ 3) * 512);
      mma16816z(s0, qa[0], kb[0].x, kb[0].y); mma16816z(s2, qa[0], km[0], km[1]); mma16816z(s1, qa[1], kb[1].x, kb[1].y);
      mma16816(s2, qa[0], km[2], km[3]); mma16816(s0, qa[2], kb[2].x, kb[2].y); mma16816(s1, qa[3], kb[3].x, kb[3].y);
      const uint32_t w0 = pack_bf16((s0[0] + s0[2]) + (s1[0] + s1[2]), (s0[1] + s0[3]) + (s1[1] + s1[3]));
      const uint32_t w1 = pack_bf16(s2[0] + s2[2], s2[1] + s2[3]);
      stasync64(aR, w0, w1, bS + px);
      sts64(aH, w0, w1);
    }
    uint2 ts;
    {
      uint32_t vx[4][4], sl[5];
      const uint32_t aVx = kvb + 4096 + (warp >> 1) * (j ? -4096 : 4096) + (warp & 1) * 1024 + lane * 16;
      const uint32_t a8 = sb + lane * 8, av = a8 + C_VP + warp * 1024;
      const uint32_t aO = sb + C_O + ((warp >> 1) * 64 + (warp & 1) * 16 + (mi & 1) * 32 + (mi >> 1) * 8 + r) * 16, aR = sb + C_R + (lane & 28);
      bar_sync(BAR_X, 128);
      { uint2 t[4];
#pragma unroll
        for (int u = 0; u < 4; u++) t[u] = lds64(a8 + C_S + u * 256);
#pragma unroll
        for (int i = 0; i < 4; i++) { const uint4 q = lds128(aVx + (i & 1) * 2048 + (i >> 1) * 512); vx[i][0] = q.x; vx[i][1] = q.z ^ zero; vx[i][2] = q.y ^ zero; vx[i][3] = q.w; }
#pragma unroll
        for (int u = 0; u < 4; u++) sl[u] = t[u].x;
        sl[4] = pack_bf16((bf_lo(t[0].y) + bf_lo(t[1].y)) + (bf_lo(t[2].y) + bf_lo(t[3].y)), (bf_hi(t[0].y) + bf_hi(t[1].y)) + (bf_hi(t[2].y) + bf_hi(t[3].y))); }
      mbar_wait(bS, ph);
      uint32_t vm[2][4];
      { uint2 t[4];
#pragma unroll
        for (int u = 0; u < 4; u++) t[u] = lds64(a8 + C_S + 1024 + u * 256);
#pragma unroll
        for (int u = 0; u < 4; u++) sl[u] = hadd2bf(sl[u], t[u].x);
        sl[4] = hadd2bf(hadd2bf(hadd2bf(sl[4], t[0].y), t[1].y), hadd2bf(t[2].y, t[3].y)); }
      uint32_t m2 = hmax2bf(hmax2bf(hmax2bf(sl[0], sl[1]), hmax2bf(sl[2], sl[3])), sl[4]);
      const uint32_t x1 = __shfl_xor_sync(~0u, m2, 1), x2 = __shfl_xor_sync(~0u, m2, 2), x3 = __shfl_xor_sync(~0u, m2, 3);
#pragma unroll
      for (int i = 0; i < 4; i++) { const uint2 q = lds64(av + i * 256); vm[i >> 1][(i & 1) * 2] = q.x; vm[i >> 1][(i & 1) * 2 + 1] = q.y; }
      ts = ldg_rlx64(args.comm + TS_OFF + lane * 8);
      float sv[10];
#pragma unroll
      for (int u = 0; u < 5; u++) { sv[2 * u] = bf_lo(sl[u]) * SM_SCALE; sv[2 * u + 1] = bf_hi(sl[u]) * SM_SCALE; }
      m2 = hmax2bf(hmax2bf(m2, x1), hmax2bf(x2, x3));
      const float mx = fmaxf(bf_lo(m2), bf_hi(m2));
      float o0[4], o1[4];
      sv[8] = ex2(fmaf(mx, -SM_SCALE, sv[8])); sv[9] = ex2(fmaf(mx, -SM_SCALE, sv[9]));
      { const uint32_t p = pack_bf16(sv[8], sv[9]); mma16816z(o0, vm[0], p, p); mma16816z(o1, vm[1], p, p); }
#pragma unroll
      for (int i = 0; i < 4; i++) sv[i] = ex2(fmaf(mx, -SM_SCALE, sv[i]));
      { const uint32_t p0 = pack_bf16(sv[0], sv[1]), p1 = pack_bf16(sv[2], sv[3]); mma16816(o0, vx[0], p0, p1); mma16816(o1, vx[2], p0, p1); }
#pragma unroll
      for (int i = 4; i < 8; i++) sv[i] = ex2(fmaf(mx, -SM_SCALE, sv[i]));
      { const uint32_t p0 = pack_bf16(sv[4], sv[5]), p1 = pack_bf16(sv[6], sv[7]); mma16816(o0, vx[1], p0, p1); mma16816(o1, vx[3], p0, p1); }
      sts32(aR + (lane & 3) * 32 + 128, __float_as_uint((((sv[8] + sv[9]) + ((sv[0] + sv[1]) + (sv[2] + sv[3]))) + (sv[4] + sv[5])) + (sv[6] + sv[7])));
      stsm4(aO, pack_bf16(o0[0], o0[1]), pack_bf16(o0[2], o0[3]), pack_bf16(o1[0], o1[1]), pack_bf16(o1[2], o1[3]));
      if (warp == 3) bar_sync(BAR_O, 384); else bar_arrive(BAR_O, 384);
    }
    lane = __shfl_sync(~0u, lane0, lane0);
    uint32_t t0;
    {
      const uint4 cal = lds128(sb + C_R + 64);
      const uint32_t d0 = ts.x - cal.x, d1 = ts.y - cal.x;
      const int dt = (int)__reduce_max_sync(~0u, max(d0 < 32768u ? d0 : 0u, d1 < 32768u ? d1 : 0u));
      t0 = cal.y + (uint32_t)min(__float2int_rn((float)dt * __uint_as_float(cal.z)), 8192);
      if (warp == 1) sts32(sb + C_R + 48, t0);
    }
    const uint32_t tag = (s + args.layer + 1) & 1, tm = 0u - tag;
    if (warp == 3) {
      if (lane == 0) { LOGS(c, s); LOGV(c, 192 + (s >> 1), clk()); }
      const uint32_t* f = args.flags + F_KV + min((s + 2) >> 1, 31) * 32 + h;
      const uint32_t rdy = ldg_rlx32(f);
      flag_set(args.flags + F_KM + h * 32 + j, s);
      spin_until(t0 + args.ta[2] - TEXP);
      do_export(s, lane, true);
      if (__any_sync(~0u, rdy < 2)) flag_wait_warp(f, 2);
      spin_until(t0 + args.tb[2] + TKV);
      if (s < 61) load_kv(sb, h, j, s + 2);
      if (lane == 0) LOG(c, 64 + s);
    }
    if (warp == 2) calib();
    if (warp == 0 || warp == 2 || (warp == 1 && !(c & 16))) {
      const uint32_t g = lane >> 2, t = lane & 3;
      const char* p = args.comm + (g1page(c >> 1) + (c & 1) * 2048 + (warp == 0 ? 0 : warp == 1 ? 0x30000 : 0x100000) + ((g >> 2) * 4 + t) * 64 + (g & 3) * 16);
      char* g2w = args.comm + (g1page(((t >> 1) + (g >> 2) * 2) * 4 + warp) + G2_OFF + c * 64 + (g & 3) * 16 + (t & 1) * 8);
      const uint32_t one = (g & 1) ? 0x3F800000u : 0x00003F80u, s0 = (g & 2) ? 0u : one, s1 = (g & 2) ? one : 0u;
      int lim = 0; bool bad;
      p += wait_until(t0 + args.ta[warp], lane >> 5);
      do {
        uint4 a[4]; float z0[4], z1[4], y[4];
#pragma unroll
        for (int i = 0; i < 4; i++) a[i] = ldg_rlx128(p + i * 512);
        ++lim;
        { const uint32_t A[4] = {a[0].x, a[0].y, a[0].z, a[0].w}; mma16816z(z0, A, s0, s1); }
        { const uint32_t A[4] = {a[1].x, a[1].y, a[1].z, a[1].w}; mma16816z(z1, A, s0, s1); }
        { const uint32_t A[4] = {a[2].x, a[2].y, a[2].z, a[2].w}; mma16816(z0, A, s0, s1); }
        { const uint32_t A[4] = {a[3].x, a[3].y, a[3].z, a[3].w}; mma16816(z1, A, s0, s1); }
        const uint32_t m0 = launder((a[0].x ^ tm) | (a[0].z ^ tm)), m1 = launder((a[1].x ^ tm) | (a[1].z ^ tm)), m2 = launder((a[2].x ^ tm) | (a[2].z ^ tm)), m3 = launder((a[3].x ^ tm) | (a[3].z ^ tm));
        bad = __any_sync(~0u, ((launder(m0 | m1 | m2) | m3) & 0x10000u) && lim < POLL_LIMIT);
#pragma unroll
        for (int i = 0; i < 4; i++) { y[i] = z0[i] + z1[i]; y[i] += __shfl_xor_sync(~0u, y[i], 16); }
        const uint32_t w0 = pack_tag(y[0], y[1], tag << 16), w1 = pack_bf16(y[2], y[3]);
        if (!bad) stg_rlx64(g2w, w0, w1);
      } while (bad);
      if (lane == 0 && warp == 0) LOGV(c, 128 + s, lim);
    }
    if (warp < 3) {
      const uint32_t hf = warp >> 1, hg = warp ? 1024 : 2048, hs = warp ? 1024 : 5120;
      const char* p = args.comm + (g1page((h & 3) * 4 + (warp ? 2 : 1)) + G2_OFF + hf * 2048 + lane * 16);
      const uint32_t aMw = sb + C_M + (warp ? 3072 : 2048) + hf * 5120 + lane * 8;
      int lim = 0; bool bad;
      p += wait_until(t0 + args.tb[warp ? 2 : 1], lane >> 5);
      do { uint4 a[4]; uint32_t m = 0; ++lim;
#pragma unroll
        for (int i = 0; i < 4; i++) a[i] = ldg_rlx128(p + (i & 1) * 512 + (i >> 1) * hg);
#pragma unroll
        for (int i = 0; i < 4; i++) { const uint32_t q = aMw + (i & 1) * 256 + (i >> 1) * hs; sts64(q, a[i].x, a[i].z); sts64(q + 512, a[i].y, a[i].w); m |= (a[i].x ^ tm) | (a[i].z ^ tm); }
        bad = __any_sync(~0u, (m & 0x10000u) && lim < POLL_LIMIT);
      } while (bad);
      if (warp) bar_arrive(BAR_M2, 384); else bar_arrive(BAR_M1, 288);
    }
  }
}

#define PDLAT 2
#define NPROBE 3
#define OPACE 400
constexpr int G_ST = 163840;
constexpr int B_FULL = 64, B_EMPTY = 96, B_WD = 136, B_ROLE = 144, B_PROG = 148, B_WF = 160  ;
enum { BAR_T = 1  , BAR_G = 3  , BAR_V = 5   };
DEVINL uint64_t mkdesc(uint32_t a, uint32_t lbo, uint32_t sbo, uint32_t sw) { return (uint64_t)((a & 0x3FFFF) >> 4) | ((uint64_t)(lbo >> 4) << 16) | ((uint64_t)(sbo >> 4) << 32) | ((uint64_t)sw << 62); }
DEVINL void wgmma_n128(float* d, uint64_t a, uint64_t b, int acc) {
  asm volatile("{.reg .pred p; setp.ne.b32 p, %66, 0; wgmma.mma_async.sync.aligned.m64n128k16.f32.bf16.bf16 {%0,%1,%2,%3,%4,%5,%6,%7,%8,%9,%10,%11,%12,%13,%14,%15,%16,%17,%18,%19,%20,%21,%22,%23,%24,%25,%26,%27,%28,%29,%30,%31,%32,%33,%34,%35,%36,%37,%38,%39,%40,%41,%42,%43,%44,%45,%46,%47,%48,%49,%50,%51,%52,%53,%54,%55,%56,%57,%58,%59,%60,%61,%62,%63}, %64, %65, p, 1, 1, 0, 1;}"
               : "+f"(d[0]),"+f"(d[1]),"+f"(d[2]),"+f"(d[3]),"+f"(d[4]),"+f"(d[5]),"+f"(d[6]),"+f"(d[7]),"+f"(d[8]),"+f"(d[9]),"+f"(d[10]),"+f"(d[11]),"+f"(d[12]),"+f"(d[13]),"+f"(d[14]),"+f"(d[15]),"+f"(d[16]),"+f"(d[17]),"+f"(d[18]),"+f"(d[19]),"+f"(d[20]),"+f"(d[21]),"+f"(d[22]),"+f"(d[23]),"+f"(d[24]),"+f"(d[25]),"+f"(d[26]),"+f"(d[27]),"+f"(d[28]),"+f"(d[29]),"+f"(d[30]),"+f"(d[31]),"+f"(d[32]),"+f"(d[33]),"+f"(d[34]),"+f"(d[35]),"+f"(d[36]),"+f"(d[37]),"+f"(d[38]),"+f"(d[39]),"+f"(d[40]),"+f"(d[41]),"+f"(d[42]),"+f"(d[43]),"+f"(d[44]),"+f"(d[45]),"+f"(d[46]),"+f"(d[47]),"+f"(d[48]),"+f"(d[49]),"+f"(d[50]),"+f"(d[51]),"+f"(d[52]),"+f"(d[53]),"+f"(d[54]),"+f"(d[55]),"+f"(d[56]),"+f"(d[57]),"+f"(d[58]),"+f"(d[59]),"+f"(d[60]),"+f"(d[61]),"+f"(d[62]),"+f"(d[63]) : "l"(a), "l"(b), "r"(acc));
}
DEVINL void wgmma_n80(float* d, uint64_t a, uint64_t b, int acc) {
  asm volatile("{.reg .pred p; setp.ne.b32 p, %42, 0; wgmma.mma_async.sync.aligned.m64n80k16.f32.bf16.bf16 {%0,%1,%2,%3,%4,%5,%6,%7,%8,%9,%10,%11,%12,%13,%14,%15,%16,%17,%18,%19,%20,%21,%22,%23,%24,%25,%26,%27,%28,%29,%30,%31,%32,%33,%34,%35,%36,%37,%38,%39}, %40, %41, p, 1, 1, 0, 1;}"
               : "+f"(d[0]),"+f"(d[1]),"+f"(d[2]),"+f"(d[3]),"+f"(d[4]),"+f"(d[5]),"+f"(d[6]),"+f"(d[7]),"+f"(d[8]),"+f"(d[9]),"+f"(d[10]),"+f"(d[11]),"+f"(d[12]),"+f"(d[13]),"+f"(d[14]),"+f"(d[15]),"+f"(d[16]),"+f"(d[17]),"+f"(d[18]),"+f"(d[19]),"+f"(d[20]),"+f"(d[21]),"+f"(d[22]),"+f"(d[23]),"+f"(d[24]),"+f"(d[25]),"+f"(d[26]),"+f"(d[27]),"+f"(d[28]),"+f"(d[29]),"+f"(d[30]),"+f"(d[31]),"+f"(d[32]),"+f"(d[33]),"+f"(d[34]),"+f"(d[35]),"+f"(d[36]),"+f"(d[37]),"+f"(d[38]),"+f"(d[39]) : "l"(a), "l"(b), "r"(acc));
}

template <int N, int NST, bool HAND>
DEVINL void gemm_tile(float* acc, uint32_t sb, uint32_t px, int wg, uint32_t u0, int rot, bool lead, int wph) {
  const uint64_t db = N == 128 ? mkdesc(sb, 81920, 1024, 1) : mkdesc(sb, 32768, 256, 3);
#pragma unroll
  for (int i = 0; i < N / 2; i++) acc[i] = 0.f;
  bar_sync(BAR_T + wg, 256);
#pragma unroll 1
  for (int st = 0; st < NST; st++) {
    const uint32_t u = u0 + st, slot = u & 3, ks = (st + rot >= NST ? st + rot - NST : st + rot) * 8;
    if (wph >= 0) mbar_wait(sb + S_BAR + B_WF + (N == 128 ? st * 8 : 0), wph);
    mbar_wait(sb + S_BAR + B_FULL + slot * 8, (u >> 2) & 1);
    const uint64_t da = mkdesc(sb + G_ST + slot * 16384, 16, 1024, 1);
    asm volatile("wgmma.fence.sync.aligned;" ::: "memory");
#pragma unroll
    for (int k = 0; k < 8; k++) {
      const uint64_t a = da + (k >> 2) * 512 + (k & 3) * 2;
      if (N == 128) wgmma_n128(acc, a, db + (ks + k) * 128, 1); else wgmma_n80(acc, a, db + (ks + k) * 32, 1);
    }
    asm volatile("wgmma.commit_group.sync.aligned;" ::: "memory");
    if (HAND && st == NST - 1) bar_arrive(BAR_T + (wg ^ 1), 256);
    if (st > 0) {
      asm volatile("wgmma.wait_group.sync.aligned 1;" ::: "memory");
      if (lead) { const uint32_t e = sb + S_BAR + B_EMPTY + ((u - 1) & 3) * 8; mbar_arrive(e); mbar_arrive_remote(e + px); }
    }
  }
  asm volatile("wgmma.wait_group.sync.aligned 0;" ::: "memory");
  if (lead) { const uint32_t e = sb + S_BAR + B_EMPTY + ((u0 + NST - 1) & 3) * 8; mbar_arrive(e); mbar_arrive_remote(e + px); }
}
DEVINL void wg_publish(int wg) { bar_sync(BAR_G + wg, 160); }
DEVINL uint32_t km_known(uint32_t sb) { uint32_t v; asm volatile("ld.acquire.cta.shared.u32 %0, [%1];" : "=r"(v) : "r"(sb + S_BAR + B_PROG) : "memory"); return __reduce_min_sync(~0u, v); }
DEVINL void km_watcher(uint32_t sb, const uint32_t* p) {
  uint32_t v = 0;
#pragma unroll 1
  for (int n = 0; n < 16 * POLL_LIMIT && v < 64; n++) {
    const uint2 q = ldg_rlx64(p);
    if (min(q.x, q.y) != v) { v = min(q.x, q.y); asm volatile("fence.acquire.gpu; st.release.cta.shared.u32 [%0], %1;" ::"r"(sb + S_BAR + B_PROG), "r"(v) : "memory"); }
    __nanosleep(v < 61 ? 300 : 20);
  }
}

template <int HF>
DEVINL void attend(const float* acc, uint4 (*kf)[4], uint4* kmf, uint4* op, const char* kvp, const char* mp, bf16* orow, int lane, int wg, uint32_t sb, int tile, bool& pend) {
  constexpr int NT = HF ? 4 : 2;
  const int g = lane >> 2, t = lane & 3;
  float sc[NT + 1][4];
#pragma unroll
  for (int k = 0; k < 8; k++) {
    uint32_t qa[4];
#pragma unroll
    for (int i = 0; i < 4; i++) { const float* a = acc + 32 * (k >> 2) + 4 * (k & 3) + 16 * (i >> 1) + 2 * (i & 1); qa[i] = pack_bf16(a[0], a[1]); }
#pragma unroll
    for (int kt = 0; kt <= NT; kt++) {
      const uint4 b = kt < NT ? kf[kt][k >> 1] : kmf[k >> 1];
      if (k == 0) mma16816z(sc[kt], qa, b.x, b.y); else if (k & 1) mma16816(sc[kt], qa, b.z, b.w); else mma16816(sc[kt], qa, b.x, b.y);
    }
  }
  SCHED(lane, 70);
  bar_arrive(BAR_T + (wg ^ 1), 256);
  if (pend) {
#pragma unroll
    for (int q = 0; q < 4; q++) { *(uint4*)(orow - 128 * 4096 + q * 32) = op[2 * q]; *(uint4*)(orow - 120 * 4096 + q * 32) = op[2 * q + 1]; }
    wg_publish(wg);
  }
  {
    uint32_t go; asm volatile("{.reg .pred p,q; setp.ne.u32 q, %1, 0; bar.red.and.pred p, %2, 128, q; selp.u32 %0, 1, 0, p;}" : "=r"(go) : "r"((uint32_t)(tile < 30 && km_known(sb) > tile * 2 + 5)), "r"(BAR_V + wg) : "memory");
    pend = __reduce_max_sync(~0u, go); }
  uint4 vf[HF + 1][8]; uint32_t vm[16];
  const char* vp = kvp + 4096 + (g >> 1) * 512 + ((g & 1) * 4 + t) * 16;
  const char* vmp = mp + 2048 + ((8 * (g >> 1) + (g & 1)) * 16 + t * 4);
#pragma unroll
  for (int i = 0; i < 16; i++) vm[i] = ldg_ca32(vmp + (i >> 2) * 512 + (i & 3) * 32);
#pragma unroll
  for (int i = 0; i < 8; i++) vf[0][i] = ldg_ca128(vp + (i >> 2) * 4096 + (i & 3) * 128);
  if (tile < 30) {
#pragma unroll
    for (int i = 0; i < 8; i++) kf[i >> 2][i & 3] = ldg_ca128(kvp + 4 * 32 * 16384 + ((i >> 1) & 1) * 12288 + (i >> 2) * 1024 + (i & 1) * 512 + lane * 16);
  }
  if (pend) {
#pragma unroll
    for (int G = 0; G < 4; G++) kmf[G] = ldg_ca128(mp + 4 * 32 * 4096 + G * 512 + lane * 16);
  }
  if (HF) {
#pragma unroll
    for (int i = 0; i < 8; i++) vf[HF][i] = ldg_cg128(vp + 2048 + (i >> 2) * 4096 + (i & 3) * 128);
    if (tile < 30) {
#pragma unroll
      for (int i = 8; i < 16; i++) kf[i >> 2][i & 3] = ldg_cg128(kvp + 4 * 32 * 16384 + ((i >> 1) & 1) * 12288 + (i >> 2) * 1024 + (i & 1) * 512 + lane * 16);
    }
  }
  const float NINF = __int_as_float(0xff800000);
  if (2 * t > g) { sc[NT - 2][0] = NINF; sc[NT - 1][2] = NINF; }
  if (2 * t + 1 > g) { sc[NT - 2][1] = NINF; sc[NT - 1][3] = NINF; }
  sc[NT - 1][0] = NINF; sc[NT - 1][1] = NINF;
  float m0 = fmaxf(sc[NT][0], sc[NT][1]), m1 = fmaxf(sc[NT][2], sc[NT][3]);
#pragma unroll
  for (int kt = 0; kt < NT; kt++) { m0 = fmaxf(m0, fmaxf(sc[kt][0], sc[kt][1])); m1 = fmaxf(m1, fmaxf(sc[kt][2], sc[kt][3])); }
  m0 = fmaxf(fmaxf(m0, __shfl_xor_sync(~0u, m0, 1)), fmaxf(__shfl_xor_sync(~0u, m0, 2), __shfl_xor_sync(~0u, m0, 3)));
  m1 = fmaxf(fmaxf(m1, __shfl_xor_sync(~0u, m1, 1)), fmaxf(__shfl_xor_sync(~0u, m1, 2), __shfl_xor_sync(~0u, m1, 3)));
  m0 *= -SM_SCALE; m1 *= -SM_SCALE;
  float s0 = 0.f, s1 = 0.f; uint32_t p[NT + 1][2];
#pragma unroll
  for (int kt = 0; kt <= NT; kt++) {
    const float a = ex2(fmaf(sc[kt][0], SM_SCALE, m0)), b = ex2(fmaf(sc[kt][1], SM_SCALE, m0)), c = ex2(fmaf(sc[kt][2], SM_SCALE, m1)), d = ex2(fmaf(sc[kt][3], SM_SCALE, m1));
    s0 += a + b; s1 += c + d; p[kt][0] = pack_bf16(a, b); p[kt][1] = pack_bf16(c, d);
  }
  s0 = (s0 + __shfl_xor_sync(~0u, s0, 1)) + (__shfl_xor_sync(~0u, s0, 2) + __shfl_xor_sync(~0u, s0, 3));
  s1 = (s1 + __shfl_xor_sync(~0u, s1, 1)) + (__shfl_xor_sync(~0u, s1, 2) + __shfl_xor_sync(~0u, s1, 3));
  s0 = rcp(s0); s1 = rcp(s1);
#pragma unroll
  for (int grp = 0; grp < 4; grp++) {
    float o[4][4];
#pragma unroll
    for (int L = 0; L < 4; L++) {
      mma1688z(o[L], p[NT][0], p[NT][1], vm[grp * 4 + L]);
#pragma unroll
      for (int kh = 0; kh <= HF; kh++) {
        const uint4 w = vf[kh][(grp >> 1) * 4 + L]; const uint32_t A[4] = {p[2 * kh][0], p[2 * kh][1], p[2 * kh + 1][0], p[2 * kh + 1][1]};
        if (grp & 1) mma16816(o[L], A, w.z, w.w); else mma16816(o[L], A, w.x, w.y);
      }
    }
    op[2 * grp] = make_uint4(pack_bf16(o[0][0] * s0, o[0][1] * s0), pack_bf16(o[1][0] * s0, o[1][1] * s0), pack_bf16(o[2][0] * s0, o[2][1] * s0), pack_bf16(o[3][0] * s0, o[3][1] * s0));
    op[2 * grp + 1] = make_uint4(pack_bf16(o[0][2] * s1, o[0][3] * s1), pack_bf16(o[1][2] * s1, o[1][3] * s1), pack_bf16(o[2][2] * s1, o[2][3] * s1), pack_bf16(o[3][2] * s1, o[3][3] * s1));
  }
}

DEVINL void gemm_consumer(uint32_t sb, uint32_t px, int wg, int pr, int rank, const ArgsA& args) {
  const int lane = opaque(threadIdx.x & 31), w = __reduce_max_sync(~0u, (threadIdx.x >> 5) & 3);
  const bool lead = lane == 0 && w == 0;
  const int rot5 = pr % 5;
  if (wg == 1) bar_arrive(BAR_T, 256);
  if (threadIdx.x == 0) LOG(64 + pr * 2 + rank, 250);
#pragma unroll 1
  for (int tile = wg; tile < 32; tile += 2) {
    float acc[64];
    gemm_tile<128, 5, true>(acc, sb, px, wg, tile * 5, rot5, lead, tile < 2 ? 0 : -1);
    if (tile >= 30 && lead) mbar_arrive(sb + S_BAR + B_WD);
    char* dst = g_kv + (size_t)((tile * 2 + (w >> 1)) * 32 + pr) * 16384 + (w & 1) * 2048 + lane * 16;
    if (rank == 0) {
#pragma unroll
      for (int G = 0; G < 4; G++)
#pragma unroll
        for (int hh = 0; hh < 2; hh++) {
          const float* a = acc + 32 * (G >> 1) + 8 * (G & 1) + 2 * hh;
          *(uint4*)(dst + (G >> 1) * 12288 + hh * 1024 + (G & 1) * 512) = make_uint4(pack_bf16(a[0], a[1]), pack_bf16(a[16], a[17]), pack_bf16(a[4], a[5]), pack_bf16(a[20], a[21]));
        }
    } else {
#pragma unroll
      for (int i = 0; i < 8; i++) {
        const float* a = acc + (i >> 2) * 32 + (i & 3) * 4;
        *(uint4*)(dst + 4096 + (i >> 2) * 4096 + (i & 3) * 512) = make_uint4(movm(pack_bf16(a[0], a[1])), movm(pack_bf16(a[2], a[3])), movm(pack_bf16(a[16], a[17])), movm(pack_bf16(a[18], a[19])));
      }
    }
    wg_publish(wg);
    if ((threadIdx.x & 127) == 0) LOG(64 + pr * 2 + rank, tile);
  }
  if (threadIdx.x == 0) LOG(64 + pr * 2 + rank, 251);
  if (pr < 16) {
    const int h = 2 * pr + rank;
    flag_wait_warp(args.flags + F_KV + (30 + (lane & 1)) * 32 + h, 2);
    bool pend = false; uint4 op[8], kf[4][4], kmf[4];
#pragma unroll
    for (int i = 0; i < 16; i++) kf[i >> 2][i & 3] = ldg_cg128(g_kv + (size_t)((wg * 2 + (w >> 1)) * 32 + h) * 16384 + ((i >> 1) & 1) * 12288 + (i >> 2) * 1024 + (i & 1) * 512 + lane * 16);
#pragma unroll
    for (int i = 0; i < 8; i++) op[i] = kmf[i & 3] = make_uint4(0, 0, 0, 0);
#pragma unroll 1
    for (int tile = wg; tile < 32; tile += 2) {
      const uint32_t seg = tile * 2 + (w >> 1);
      const char* kvp = g_kv + (size_t)(seg * 32 + h) * 16384;
      const char* mp = g_kvm + (size_t)(seg * 32 + h) * 4096;
      bf16* orow = g_o + (size_t)(tile * 64 + w * 16 + (lane >> 2)) * 4096 + h * 128 + (lane & 3) * 8;
      float acc[64];
      gemm_tile<128, 5, false>(acc, sb, px, wg, 160 + tile * 5, rot5, lead, tile < 2 ? 1 : -1);
      if ((threadIdx.x & 127) == 96) LOG(64 + pr * 2 + rank, 64 + tile);
      if (!pend) {
        int n = 0;
        while (km_known(sb) <= seg && ++n < 16 * POLL_LIMIT) {}
#pragma unroll
        for (int G = 0; G < 4; G++) kmf[G] = ldg_ca128(mp + G * 512 + lane * 16);
      }
      if ((threadIdx.x & 127) == 96) LOG(64 + pr * 2 + rank, 96 + tile);
      if (w & 1) attend<1>(acc, kf, kmf, op, kvp, mp, orow, lane, wg, sb, tile, pend); else attend<0>(acc, kf, kmf, op, kvp, mp, orow, lane, wg, sb, tile, pend);
      if (!pend) {
#pragma unroll
        for (int q = 0; q < 4; q++) { *(uint4*)(orow + q * 32) = op[2 * q]; *(uint4*)(orow + 8 * 4096 + q * 32) = op[2 * q + 1]; }
        wg_publish(wg);
      }
      if ((threadIdx.x & 127) == 0) LOG(64 + pr * 2 + rank, 32 + tile);
    }
  } else {
    const int kq = (pr - 16) >> 2, cg = 2 * (pr & 3) + rank;
#pragma unroll 1
    for (int tile = wg; tile < 32; tile += 2) {
      float acc[40];
      gemm_tile<80, 8, true>(acc, sb, px, wg, 160 + tile * 8, (pr & 3) * 2, lead, tile < 2 ? 1 : -1);
      const bool odd = lane & 1;
      bf16* dst = g_part + (size_t)(kq * 2048 + tile * 64 + w * 16 + (lane >> 2)) * 640 + cg * 80 + (lane & 1) * 8 + (lane & 2) * 2;
#pragma unroll
      for (int q = 0; q < 5; q++)
#pragma unroll
        for (int hh = 0; hh < 2; hh++) {
          const uint32_t A = pack_bf16(acc[8 * q + 2 * hh], acc[8 * q + 2 * hh + 1]), B = pack_bf16(acc[8 * q + 4 + 2 * hh], acc[8 * q + 5 + 2 * hh]);
          const uint32_t x = __shfl_xor_sync(~0u, odd ? A : B, 1);
          *(uint2*)(dst + hh * 8 * 640 + q * 16) = odd ? make_uint2(x, B) : make_uint2(A, x);
        }
      wg_publish(wg);
      if ((threadIdx.x & 127) == 0) LOG(64 + pr * 2 + rank, 32 + tile);
    }
  }
  if (wg == 0) bar_sync(BAR_T, 256);
}

DEVINL void gemm_producer(uint32_t sb, int pr, int rank, const ArgsA& args, const CUtensorMap* tq, const CUtensorMap* tk, const CUtensorMap* tv,
                          const CUtensorMap* to32, const CUtensorMap* tx, const CUtensorMap* tao) {
  const uint32_t bWF = sb + S_BAR + B_WF;
  auto load_w = [&](const CUtensorMap* tm, int col, int st) {
    const int r = ((st + pr) % 5) * 2; mbar_arrive_tx(bWF + st * 8, 32768);
#pragma unroll 1
    for (int i = 0; i < 4; i++) tma_2d(sb + (i & 1) * 81920 + (r + (i >> 1)) * 8192, tm, col + (i & 1) * 64, (r + (i >> 1)) * 64, bWF + st * 8); };
  uint32_t u = 0;
  auto push = [&](const CUtensorMap* tm, int c0, int c1) {
    const uint32_t slot = u & 3, full = sb + S_BAR + B_FULL + slot * 8;
    mbar_wait(sb + S_BAR + B_EMPTY + slot * 8, ((u >> 2) & 1) ^ 1);
    mbar_arrive_tx(full, 16384);
    tma_2d_mc(sb + G_ST + slot * 16384 + rank * 8192, tm, c0 + rank * 64, c1, full);
    u++; };
#pragma unroll 1
  for (int st = 0; st < 5; st++) load_w(rank ? tv : tk, pr * 128, st);
  if (args.layer == 0) { flag_wait(args.flags + F_X, 128); fence_proxy_async(); } else pdl_wait();
#pragma unroll 1
  for (int tile = 0; tile < 32; tile++) {
    l2_prefetch((const char*)g_xn + ((tile + 2) & 31) * 81920 + (pr * 2 + rank) * 1280, 1280);
    if (tile >= 20 && tile < 30) l2_prefetch((rank ? args.wo : args.wq) + (pr * 10 + tile - 20) * 16384, 16384);
#pragma unroll 1
    for (int st = 0; st < 5; st++) push(tx, ((st + pr) % 5) * 128, tile * 64);
  }
  pdl_launch();
  if (pr < 16) {
    load_w(tq, (2 * pr + rank) * 128, 0);
#pragma unroll 1
    for (int tile = 0; tile < 32; tile++) {
      if (tile < 30) {
        l2_prefetch((const char*)g_xn + (tile + 2) * 81920 + (pr * 2 + rank) * 2560, 2560);
        const int q = (tile * 2 + 4) * 32 + 2 * pr + rank;
        l2_prefetch(g_kv + (size_t)q * 16384, 16384); l2_prefetch(g_kv + (size_t)(q + 32) * 16384, 16384);
        if (lds32(sb + S_BAR + B_PROG) > tile * 2 + 5) { l2_prefetch(g_kvm + (size_t)q * 4096, 4096); l2_prefetch(g_kvm + (size_t)(q + 32) * 4096, 4096); }
      }
#pragma unroll 1
      for (int st = 0; st < 5; st++) { push(tx, ((st + pr) % 5) * 128, tile * 64); if (tile == 0 && st < 4) load_w(tq, (2 * pr + rank) * 128, st + 1); }
    }
  } else {
    const int kq = (pr - 16) >> 2, cg = 2 * (pr & 3) + rank;
    mbar_wait(sb + S_BAR + B_WD, 0);
    mbar_arrive_tx(bWF, 163840);
#pragma unroll 1
    for (int i = 0; i < 20; i++) { tma_2d(sb + (i % 5) * 32768 + (i / 5) * 8192, to32, cg * 80 + (i % 5) * 16, kq * 1024 + (i / 5) * 256, bWF); __nanosleep(OPACE); }
#pragma unroll 1
    for (int tile = 0; tile < 32; tile++) {
      flag_wait(args.flags + F_O + tile * 4 + kq, 8);
      fence_proxy_async();
#pragma unroll 1
      for (int st = 0; st < 8; st++) push(tao, kq * 1024 + ((st + (pr & 3) * 2) & 7) * 128, tile * 64);
    }
  }
#pragma unroll 1
  for (int i = 0; i < 4; i++, u++) mbar_wait(sb + S_BAR + B_EMPTY + (u & 3) * 8, ((u >> 2) & 1) ^ 1);
}

DEVINL void gemm_publisher(int wg, int pr, int rank, const ArgsA& args) {
#pragma unroll 1
  for (int i = 0; i < 32; i++) {
    const int tile = (i & 15) * 2 + wg;
    bar_sync(BAR_G + wg, 160);
    if ((threadIdx.x & 31) == 0) {
      flag_add(args.flags + (i < 16 ? F_KV + tile * 32 + pr : pr < 16 ? F_O + tile * 4 + (pr >> 2) : F_P + tile * 32));
    }
    __syncwarp();
  }
}

DEVINL void filter_prep(uint32_t* sm, int part, const ArgsA& args) {
  const int tid = threadIdx.x, lane = tid & 31, w = tid >> 5;
  const unsigned short* wr = (const unsigned short*)args.wr; const unsigned short* wi = (const unsigned short*)args.wi;
#pragma unroll 1
  for (int it = part; it < 32; it += 4) {
#pragma unroll 1
    for (int rr = 0; rr < 8; rr += 2) {
      uint32_t a[2][11], b[2][11];
#pragma unroll
      for (int r = 0; r < 2; r++) {
        const int pos = it * 64 + w * 8 + rr + r, th = (pos >> 2) & 127, v = (pos >> 9) * 4 + (pos & 3);
        const int o = ((th >> 3) + 16 * ((th & 7) + (v & 8)) + 256 * (v & 7)) * 321 + lane;
#pragma unroll
        for (int c = 0; c < 11; c++) if (c < 10 || lane == 0) { a[r][c] = wr[o + c * 32]; b[r][c] = wi[o + c * 32]; }
      }
#pragma unroll
      for (int r = 0; r < 2; r++)
#pragma unroll
        for (int c = 0; c < 11; c++) if (c < 10 || lane == 0) sm[(c * 32 + lane) * 65 + w * 8 + rr + r] = a[r][c] | (b[r][c] << 16);
    }
    bar_sync(1, 256);
#pragma unroll 2
    for (int i = tid; i < 64 * 321; i += 256) g_wt[(i >> 6) * 2048 + it * 64 + (i & 63)] = sm[(i >> 6) * 65 + (i & 63)];
    bar_sync(1, 256);
  }
}

__global__ void __cluster_dims__(2, 1, 1) __launch_bounds__(384, 1)
layer_a_kernel(const __grid_constant__ CUtensorMap tq, const __grid_constant__ CUtensorMap tk, const __grid_constant__ CUtensorMap tv,
               const __grid_constant__ CUtensorMap to, const __grid_constant__ CUtensorMap to32, const __grid_constant__ CUtensorMap tx,
               const __grid_constant__ CUtensorMap tao, const __grid_constant__ ArgsA args) {
  extern __shared__ __align__(1024) char smraw[];
  const uint32_t sb = (smem_u32(smraw) + 1023) & ~1023u;
  uint32_t rank; asm volatile("mov.u32 %0, %%cluster_ctarank;" : "=r"(rank));
  rank = __reduce_max_sync(~0u, rank);
  const uint32_t px = __reduce_max_sync(~0u, mapa(sb, rank ^ 1) - sb);
  if (PDLAT == 0) pdl_launch();
  if (args.layer == 0) LOGK(0, 0);
  uint32_t smid; asm volatile("mov.u32 %0, %%smid;" : "=r"(smid));
  if (threadIdx.x >= 256) {
    const uint32_t b = sb + S_BAR;
    if (threadIdx.x == 320) {
      mbar_init(b + B_W, 1); mbar_init(b + B_W2, 1); mbar_init(b + B_WV, 1); mbar_init(b + B_WO, 1); mbar_init(b + B_S, 9); mbar_init(b + B_KV, 1); mbar_init(b + B_KV + 8, 1);
      for (int i = 0; i < 4; i++) { mbar_init(b + B_FULL + i * 8, 1); mbar_init(b + B_EMPTY + i * 8, 2); }
      for (int i = 0; i < 5; i++) mbar_init(b + B_WF + i * 8, 1);
      mbar_init(b + B_WD, 2); sts32(b + B_PROG, 0);
      asm volatile("fence.mbarrier_init.release.cluster;" ::: "memory");
    }
    if (rank == 0 && threadIdx.x < 320) {
      if (args.layer == 0) {
        uint32_t* p = (uint32_t*)(args.comm + 0x20000 + (threadIdx.x < 288 ? 0x1000 : 0) + (blockIdx.x >> 1) * 32);
        if ((threadIdx.x & 31) < 8) p[threadIdx.x & 31] = 0;
        __syncwarp();
        if ((threadIdx.x & 31) == 0) {
          uint32_t v, best = ~0u;
#pragma unroll 1
          for (int i = 0; i < NPROBE; i++) { const uint32_t t0 = clk(); asm volatile("atom.relaxed.gpu.global.add.u32 %0, [%1], 1;" : "=r"(v) : "l"(p) : "memory"); asm volatile("st.volatile.shared.u32 [%0], %1;" ::"r"(b + 208), "r"(v) : "memory"); best = min(best, clk() - t0); }
          sts32(b + 200 + ((threadIdx.x >> 5) & 1) * 4, best);
        }
        bar_sync(1, 64);
      }
      if (threadIdx.x == 256) {
        int d;
        if (args.layer == 0) { d = (int)(lds32(b + 200) - lds32(b + 204)); g_side[smid & 254] = d; g_side[(smid & 254) + 1] = d; } else d = g_side[smid & 255];
        uint32_t* cnt = args.flags + F_ROLE; uint32_t role;
        if (d < 0) { role = atomicAdd(cnt, 1); if (role >= 32) role = 32 + atomicAdd(cnt + 1, 1); }
        else { role = 32 + atomicAdd(cnt + 1, 1); if (role >= 66) role = atomicAdd(cnt, 1); }
        sts32(b + B_ROLE, role);
      }
    }
  } else if (args.layer == 0 && blockIdx.x < 128) {
    const size_t off = (size_t)(blockIdx.x * 16 + (threadIdx.x >> 4)) * 640 + (threadIdx.x & 15) * 8;
    float f[40];
#pragma unroll
    for (int i = 0; i < 5; i++) unpack8(*(const uint4*)(args.x + off + i * 128), f + 8 * i);
    ln_row(f);
#pragma unroll
    for (int i = 0; i < 5; i++) *(uint4*)(g_xn + off + i * 128) = pack8(f + 8 * i);
  }
  __syncthreads();
  asm volatile("barrier.cluster.arrive.release.aligned;" ::: "memory");
  if (threadIdx.x == 0 && args.layer == 0 && blockIdx.x < 128) flag_add(args.flags + F_X);
  __syncwarp();
  asm volatile("barrier.cluster.wait.acquire.aligned;" ::: "memory");
  uint32_t role; asm volatile("ld.shared::cluster.u32 %0, [%1];" : "=r"(role) : "r"(sb + S_BAR + B_ROLE + (rank ? px : 0)) : "memory");
  role = __reduce_max_sync(~0u, role);
  if (PDLAT == 1 || (PDLAT == 2 && role != 32)) pdl_launch();
  if (role >= 64) cluster_sync();
  const int wg = __reduce_max_sync(~0u, threadIdx.x >> 7);
  auto U = [](uint32_t x) { return __reduce_max_sync(~0u, opaque(x)); };
  if (wg == 2) {
    asm volatile("setmaxnreg.dec.sync.aligned.u32 56;");
    if (role < 32) chain_helper(U(sb), U(px), U(role), U(rank), args, &tq, &tk, &tv, &to);
    else if (role < 64) {
      if (threadIdx.x == 256) gemm_producer(sb, role - 32, rank, args, &tq, &tk, &tv, &to32, &tx, &tao);
      else if (threadIdx.x >= 288 && threadIdx.x < 352) gemm_publisher((threadIdx.x >> 5) - 9, role - 32, rank, args);
      else if (threadIdx.x == 352 && role < 48) km_watcher(sb, args.flags + F_KM + (2 * (role - 32) + rank) * 32);
    }
  } else {
    asm volatile("setmaxnreg.inc.sync.aligned.u32 224;");
    if (role < 32) { if (wg == 0) chain_mma<0>(sb, args); else chain_mma<1>(sb, args); }
    else if (role < 64) gemm_consumer(U(sb), U(px), U(wg), U(role - 32), U(rank), args);
    else if (args.layer == 0) { filter_prep((uint32_t*)smraw, (role - 64) * 2 + rank, args); if (threadIdx.x == 0) LOG(role * 2 + rank, 0); }
  }
}

DEVINL float2 cadd(float2 a, float2 b) { return make_float2(a.x + b.x, a.y + b.y); }
DEVINL float2 csub(float2 a, float2 b) { return make_float2(a.x - b.x, a.y - b.y); }
DEVINL float2 cmul(float2 a, float2 b) { return make_float2(fmaf(a.x, b.x, -a.y * b.y), fmaf(a.x, b.y, a.y * b.x)); }
DEVINL float2 cmulc(float2 a, float2 b) { return make_float2(fmaf(a.x, b.x, a.y * b.y), fmaf(a.y, b.x, -a.x * b.y)); }
template <int INV> DEVINL float2 ctw(float2 a, float2 w) { return INV ? cmulc(a, w) : cmul(a, w); }
template <int INV> DEVINL float2 rot(float2 a) { return INV ? make_float2(-a.y, a.x) : make_float2(a.y, -a.x); }
template <int INV> DEVINL void fft4(float2& a, float2& b, float2& c, float2& d) {
  const float2 s0 = cadd(a, c), d0 = csub(a, c), s1 = cadd(b, d), d1 = rot<INV>(csub(b, d));
  a = cadd(s0, s1); b = cadd(d0, d1); c = csub(s0, s1); d = csub(d0, d1);
}
template <int INV> DEVINL float2 w8(float2 a) { const float h = 0.70710678118654752f; const float2 r = rot<INV>(a); return make_float2((a.x + r.x) * h, (a.y + r.y) * h); }
template <int INV> DEVINL void fft8(float2* x) {
  fft4<INV>(x[0], x[2], x[4], x[6]); fft4<INV>(x[1], x[3], x[5], x[7]);
  const float2 e0 = x[0], e1 = x[2], e2 = x[4], e3 = x[6], o0 = x[1], o1 = w8<INV>(x[3]), o2 = rot<INV>(x[5]), o3 = rot<INV>(w8<INV>(x[7]));
  x[0] = cadd(e0, o0); x[1] = cadd(e1, o1); x[2] = cadd(e2, o2); x[3] = cadd(e3, o3);
  x[4] = csub(e0, o0); x[5] = csub(e1, o1); x[6] = csub(e2, o2); x[7] = csub(e3, o3);
}
template <int INV> DEVINL void fft16(float2* x) {
  const float c = 0.92387953251128674f, s = 0.38268343236508977f;
  const float2 w1 = make_float2(c, -s), w3 = make_float2(s, -c);
#pragma unroll
  for (int i = 0; i < 4; i++) fft4<INV>(x[i], x[i + 4], x[i + 8], x[i + 12]);
  x[5] = ctw<INV>(x[5], w1); x[9] = w8<INV>(x[9]); x[13] = ctw<INV>(x[13], w3);
  x[6] = w8<INV>(x[6]); x[10] = rot<INV>(x[10]); x[14] = rot<INV>(w8<INV>(x[14]));
  x[7] = ctw<INV>(x[7], w3); x[11] = rot<INV>(w8<INV>(x[11])); x[15] = ctw<INV>(x[15], make_float2(-c, s));
#pragma unroll
  for (int k = 0; k < 4; k++) fft4<INV>(x[4 * k], x[4 * k + 1], x[4 * k + 2], x[4 * k + 3]);
#pragma unroll
  for (int k = 0; k < 4; k++)
#pragma unroll
    for (int m = k + 1; m < 4; m++) { const float2 t = x[4 * k + m]; x[4 * k + m] = x[4 * m + k]; x[4 * m + k] = t; }
}
template <int INV> DEVINL void fft5(float2& x0, float2& x1, float2& x2, float2& x3, float2& x4) {
  const float c1 = 0.30901699437494742f, c2 = -0.80901699437494742f, s1 = 0.95105651629515357f, s2 = 0.58778525229247313f;
  const float2 a1 = cadd(x1, x4), a2 = cadd(x2, x3), b1 = rot<INV>(csub(x1, x4)), b2 = rot<INV>(csub(x2, x3));
  const float2 p1 = make_float2(fmaf(c1, a1.x, fmaf(c2, a2.x, x0.x)), fmaf(c1, a1.y, fmaf(c2, a2.y, x0.y)));
  const float2 p2 = make_float2(fmaf(c2, a1.x, fmaf(c1, a2.x, x0.x)), fmaf(c2, a1.y, fmaf(c1, a2.y, x0.y)));
  const float2 q1 = make_float2(fmaf(s1, b1.x, s2 * b2.x), fmaf(s1, b1.y, s2 * b2.y));
  const float2 q2 = make_float2(fmaf(s2, b1.x, -s1 * b2.x), fmaf(s2, b1.y, -s1 * b2.y));
  x0 = cadd(x0, cadd(a1, a2)); x1 = cadd(p1, q1); x4 = csub(p1, q1); x2 = cadd(p2, q2); x3 = csub(p2, q2);
}
template <int INV> DEVINL void fft20(const float2* in, float2* out) {
  float2 t[4][5];
#pragma unroll
  for (int a = 0; a < 4; a++) {
#pragma unroll
    for (int b = 0; b < 5; b++) t[a][b] = in[(5 * a + 4 * b) % 20];
    fft5<INV>(t[a][0], t[a][1], t[a][2], t[a][3], t[a][4]);
  }
#pragma unroll
  for (int d = 0; d < 5; d++) {
    fft4<INV>(t[0][d], t[1][d], t[2][d], t[3][d]);
#pragma unroll
    for (int c = 0; c < 4; c++) out[(5 * c + 16 * d) % 20] = t[c][d];
  }
}
constexpr int ZP = 336;
struct RowSmem { float2 T[320 * 17]; uint32_t Z[16 * ZP]; float2 tw[320]; float2 tp[160]; };
DEVINL float2 cis(int k, int n) {
  float sn, cs; __sincosf((float)(2 * k > n ? k - n : k) * (-6.283185307179586f / (float)n), &sn, &cs); return make_float2(cs, sn);
}
DEVINL void row_tables(RowSmem& sm) {
  const int t = threadIdx.x;
  sm.tw[t] = cis((t >> 4) * (t & 15), 320);
  if (t < 160) sm.tp[t] = cis(t, 640);
}

#define CUNR 1
#define CDRY 0
#define RDRY 1

__global__ void __launch_bounds__(320, 1) rows_fwd_kernel(const bf16* __restrict__ xin, const uint32_t* flags) {
  extern __shared__ __align__(1024) char smraw[]; RowSmem& sm = *(RowSmem*)smraw;
  const int tid = threadIdx.x, s0 = blockIdx.x * 16, wp = __reduce_max_sync(~0u, tid >> 5);
  const uint32_t* flag = flags + F_P + (blockIdx.x >> 2) * 32;
  LOGK(1 + 3 * (xin == g_x), 0);
  if (tid == 0) l2_prefetch(xin + s0 * 640, 20480);
  row_tables(sm);
#pragma unroll 1
  for (int live = !RDRY || wp != 1 || __any_sync(~0u, ldg_rlx32(flag) >= 32); live < 2; live++) {
    if (live) {
      if (wp == 0) { uint32_t v; int n = 0;
        while (true) { asm volatile("ld.acquire.gpu.global.u32 %0, [%1];" : "=r"(v) : "l"(flag) : "memory"); if (__all_sync(~0u, v >= 32 || ++n >= 8 * POLL_LIMIT)) break; __nanosleep(v ? 20 : 200); } }
      __syncthreads();
      pdl_launch();
      LOGK(1 + 3 * (xin == g_x), 1);
    }
    if (wp < 8) {
      const int row = tid >> 4, j = tid & 15; const size_t off = (size_t)(s0 + row) * 640 + j * 8;
      float f[40]; uint4 in[5][5];
#pragma unroll
      for (int i = 0; i < 5; i++) {
#pragma unroll
        for (int q = 0; q < 4; q++) in[i][q] = ldg128_if(g_part + q * 2048 * 640 + off + i * 128, live);
        in[i][4] = ldg128_if(xin + off + i * 128, live);
      }
#pragma unroll
      for (int i = 0; i < 5; i++) {
        float a[8], b[8], c[8], d[8];
        unpack8(in[i][0], a); unpack8(in[i][1], b); unpack8(in[i][2], c); unpack8(in[i][3], d);
#pragma unroll
        for (int e = 0; e < 8; e++) a[e] = (a[e] + b[e]) + (c[e] + d[e]);
        const uint4 o = pack8(a), x = in[i][4];
        const uint4 r = make_uint4(hadd2bf(o.x, x.x), hadd2bf(o.y, x.y), hadd2bf(o.z, x.z), hadd2bf(o.w, x.w));
        stg128_if(g_x + off + i * 128, r, live); unpack8(r, f + 8 * i);
      }
      ln_row(f);
#pragma unroll
      for (int i = 0; i < 5; i++) *(uint4*)(sm.Z + row * ZP + i * 64 + j * 4) = pack8(f + 8 * i);
      __syncwarp();
      float2 z[20], y[20];
#pragma unroll
      for (int n1 = 0; n1 < 20; n1++) { const uint32_t w = sm.Z[row * ZP + n1 * 16 + j]; z[n1] = make_float2(bf_lo(w), bf_hi(w)); }
      fft20<0>(z, y);
#pragma unroll
      for (int k1 = 0; k1 < 20; k1++) sm.T[(k1 * 16 + j) * 17 + row] = k1 ? cmul(y[k1], sm.tw[k1 * 16 + j]) : y[0];
    }
    if (live) __syncthreads();
    const int up = (tid >> 4) & 1, row = tid & 15, k1 = wp ? (up ? 20 - wp : wp) : up * 10;
    float2 x[16];
#pragma unroll
    for (int n2 = 0; n2 < 16; n2++) x[n2] = sm.T[(k1 * 16 + n2) * 17 + row];
    fft16<0>(x);
    uint32_t* ya = g_y + s0 + row + k1 * 2048; uint32_t* yb = g_y + s0 + row + (320 - k1) * 2048;
    stg32_if(g_y + s0 + row + 160 * 2048, pack_f16(2.f * x[8].x, -2.f * x[8].y), live && k1 == 0);
    const int src = (tid & 31) ^ (wp ? 16 : 0);
#pragma unroll
    for (int k2 = 0; k2 < 8; k2++) {
      const float2 c = k1 ? x[15 - k2] : x[(16 - k2) & 15], b = make_float2(__shfl_sync(~0u, c.x, src), __shfl_sync(~0u, c.y, src)), a = x[k2];
      const float2 E = make_float2(a.x + b.x, a.y - b.y), O = cmul(make_float2(a.y + b.y, b.x - a.x), sm.tp[k1 + 20 * k2]);
      stg32_if(ya + k2 * 20 * 2048, pack_f16(E.x + O.x, E.y + O.y), live); stg32_if(yb - k2 * 20 * 2048, pack_f16(E.x - O.x, O.y - E.y), live);
    }
  }
  LOGK(1 + 3 * (xin == g_x), 2);
  if (blockIdx.x == gridDim.x - 1) pdl_wait();
}

__global__ void __launch_bounds__(384) cols_kernel(int layer) {
  extern __shared__ __align__(1024) char smraw[];
  const int sub = threadIdx.x >> 7, tid = threadIdx.x & 127, col = blockIdx.x * 3 + sub, k1 = tid >> 3, j0 = tid & 7;
  float2* sm = (float2*)smraw + sub * (16 * 152);
  float2* tw = (float2*)smraw + 3 * 16 * 152;
  LOGK(2 + 3 * layer, 0);
  pdl_launch();
  uint32_t* y = g_y + col * 2048 + tid;
  if (tid < 2) l2_prefetch((tid ? g_wt : g_y) + col * 2048, 8192);
#pragma unroll 1
  for (int i = threadIdx.x; i < 2176; i += 384) {
    const int a = i < 2048 ? i >> 7 : (i - 2048) >> 3, b = i < 2048 ? i & 127 : i & 7;
    tw[i < 2048 ? a * 136 + b : 2176 + a * 9 + b] = cis(i < 2048 ? a * b : a * b * 16, 2048);
  }
  float2* reg = sm + k1 * 152;
  uint4 wf[4];
#pragma unroll
  for (int q = 0; q < 4; q++) {
    const int live = q >= 0, it = live ? q : q == -3 ? 0 : q == -2 ? 1 : 3;
    float2 x[16];
    if (it == 0) {
      if (live) { __syncthreads(); pdl_wait(); LOGK(2 + 3 * layer, 1); }
#pragma unroll
      for (int i = 0; i < 16; i++) { const uint32_t w = ldg32_if(y + i * 128, live); x[i] = __half22float2(*(const __half2*)&w); }
#pragma unroll
      for (int i = 0; i < 4; i++) wf[i] = ldg128_if(g_wt + col * 2048 + i * 512 + tid * 4, live);
    } else {
      const float2* in = it == 3 ? sm + tid : reg + j0; const int is = it == 1 ? 8 : it == 2 ? 9 : 152;
#pragma unroll
      for (int i = 0; i < 16; i++) x[i] = in[i * is];
    }
    fft16<0>(x);
    if (it == 3) {
      const float sc = 1.f / 4096.f;
#pragma unroll
      for (int i = 0; i < 16; i++) stg32_if(y + i * 128, pack_bf16(x[i].y * sc, x[i].x * sc), live);
    } else {
      const float2* t = it == 0 ? tw + tid : it == 1 ? tw + 2176 + j0 : tw + k1 * 136 + j0; const int ts = it == 0 ? 136 : it == 1 ? 9 : 8;
      float2* o = it == 0 ? sm + tid : reg + j0; const int os = it == 0 ? 152 : it == 1 ? 9 : 8;
      __syncwarp();
#pragma unroll
      for (int k = 0; k < 16; k++) o[k * os] = (CUNR && k == 0 && it < 2) ? x[0] : cmul(x[k], t[k * ts]);
      if (it == 1) {
        __syncwarp();
        float2* r9 = reg + j0 * 9;
#pragma unroll
        for (int i = 0; i < 16; i++) x[i] = r9[(i & 8) * 9 + (i & 7)];
#pragma unroll
        for (int h = 0; h < 2; h++) {
          fft8<0>(x); fft8<0>(x + 8);
          if (h == 0) {
#pragma unroll
            for (int i = 0; i < 16; i++) {
              const uint32_t w = (i & 3) == 0 ? wf[i >> 2].x : (i & 3) == 1 ? wf[i >> 2].y : (i & 3) == 2 ? wf[i >> 2].z : wf[i >> 2].w;
              const float2 v = cmul(x[i], make_float2(bf_lo(w), bf_hi(w))); x[i] = make_float2(v.y, v.x);
            }
          }
        }
        const float2* t9 = tw + 2176 + j0 * 9;
#pragma unroll
        for (int i = 0; i < 16; i++) r9[(i & 8) * 9 + (i & 7)] = (i & 7) ? cmul(x[i], t9[(i & 8) * 9 + (i & 7)]) : x[i];
        __syncwarp();
      } else if (live) bar_sync(sub + 1, 128);
    }
  }
  LOGK(2 + 3 * layer, 2);
}

__global__ void __launch_bounds__(320) rows_inv_kernel(bf16* __restrict__ xout, int do_ln) {
  extern __shared__ __align__(1024) char smraw[]; RowSmem& sm = *(RowSmem*)smraw;
  const int tid = threadIdx.x, s0 = blockIdx.x * 16, wp = __reduce_max_sync(~0u, tid >> 5);
  LOGK(3 + 3 * !do_ln, 0);
  if (tid == 0) l2_prefetch(g_x + s0 * 640, 20480);
  row_tables(sm);
  const size_t off = (size_t)(s0 + ((tid >> 4) & 15)) * 640 + (tid & 15) * 8;
#pragma unroll 1
  for (int live = !RDRY || wp != 1; live < 2; live++) {
    if (live) {
      __syncthreads();
      pdl_wait();
      pdl_launch();
      LOGK(3 + 3 * !do_ln, 1);
    }
    uint4 xr[5];
    {
      const int up = (tid >> 4) & 1, row = tid & 15, k1 = wp ? (up ? 20 - wp : wp) : up * 10;
      const uint32_t* ya = g_y + s0 + row + k1 * 2048; const uint32_t* yb = g_y + s0 + row + (320 - k1) * 2048;
      uint32_t wa[8], wb[8];
#pragma unroll
      for (int k2 = 0; k2 < 8; k2++) { wa[k2] = ldg32_if(ya + k2 * 20 * 2048, live); wb[k2] = ldg32_if(yb - k2 * 20 * 2048, live); }
      const uint32_t wm = ldg32_if(g_y + s0 + row + 160 * 2048, live && k1 == 0);
#pragma unroll
      for (int i = 0; i < 5; i++) xr[i] = ldg128_if(g_x + off + i * 128, live && wp < 8);
      stg32_if(g_flags + blockIdx.x * 320 + tid, 0, live && !do_ln && blockIdx.x * 320 + tid < 2 * F_LAYER);
      if (k1 == 0) { wa[0] &= 0xffffu; wb[0] &= 0xffffu; }
      float2 x[16], r[8];
#pragma unroll
      for (int k2 = 0; k2 < 8; k2++) {
        const float2 a = make_float2(bf_lo(wa[k2]), bf_hi(wa[k2])), b = make_float2(bf_lo(wb[k2]), bf_hi(wb[k2]));
        const float2 E = make_float2(a.x + b.x, a.y - b.y), O = cmulc(make_float2(a.x - b.x, a.y + b.y), sm.tp[k1 + 20 * k2]);
        x[k2] = make_float2(E.x - O.y, E.y + O.x); r[k2] = make_float2(E.x + O.y, O.x - E.y);
      }
      if (k1 == 0) r[0] = make_float2(2.f * bf_lo(wm), -2.f * bf_hi(wm));
      const int src = (tid & 31) ^ (wp ? 16 : 0);
#pragma unroll
      for (int i = 8; i < 16; i++) { const float2 c = k1 ? r[15 - i] : r[(16 - i) & 7]; x[i] = make_float2(__shfl_sync(~0u, c.x, src), __shfl_sync(~0u, c.y, src)); }
      fft16<1>(x);
#pragma unroll
      for (int n2 = 0; n2 < 16; n2++) sm.T[(k1 * 16 + n2) * 17 + row] = x[n2];
    }
    if (live) __syncthreads();
    if (wp < 8) {
      const int row = tid >> 4, n2 = tid & 15;
      float2 z[20], y[20];
#pragma unroll
      for (int k1 = 0; k1 < 20; k1++) { const float2 t = sm.T[(k1 * 16 + n2) * 17 + row]; z[k1] = k1 ? cmulc(t, sm.tw[k1 * 16 + n2]) : t; }
      fft20<1>(z, y);
      const float sc = 1.f / 640.f;
#pragma unroll
      for (int n1 = 0; n1 < 20; n1++) sm.Z[row * ZP + n1 * 16 + n2] = pack_bf16(y[n1].x * sc, y[n1].y * sc);
      __syncwarp();
      float f[40];
#pragma unroll
      for (int i = 0; i < 5; i++) {
        const uint4 o = *(const uint4*)(sm.Z + row * ZP + i * 64 + n2 * 4), x = xr[i];
        const uint4 r = make_uint4(hadd2bf(o.x, x.x), hadd2bf(o.y, x.y), hadd2bf(o.z, x.z), hadd2bf(o.w, x.w));
        stg128_if(xout + off + i * 128, r, live); unpack8(r, f + 8 * i);
      }
      if (do_ln) {
        ln_row(f);
#pragma unroll
        for (int i = 0; i < 5; i++) stg128_if(g_xn + off + i * 128, pack8(f + 8 * i), live);
      }
    }
  }
  LOGK(3 + 3 * !do_ln, 2);
}

typedef CUresult (*EncFn)(CUtensorMap*, CUtensorMapDataType, cuuint32_t, void*, const cuuint64_t*, const cuuint64_t*, const cuuint32_t*, const cuuint32_t*,
                          CUtensorMapInterleave, CUtensorMapSwizzle, CUtensorMapL2promotion, CUtensorMapFloatOOBfill);
static void make_map(EncFn fn, CUtensorMap* m, const void* p, uint64_t cols, uint64_t rows, uint32_t bc, uint32_t br, CUtensorMapSwizzle sw) {
  cuuint64_t gd[2] = {cols, rows}, gs[1] = {cols * 2}; cuuint32_t bd[2] = {bc, br}, es[2] = {1, 1};
  fn(m, CU_TENSOR_MAP_DATA_TYPE_BFLOAT16, 2, (void*)p, gd, gs, bd, es, CU_TENSOR_MAP_INTERLEAVE_NONE, sw, CU_TENSOR_MAP_L2_PROMOTION_L2_128B, CU_TENSOR_MAP_FLOAT_OOB_FILL_NONE);
}
template <class... P, class... A>
static void launch(void (*k)(P...), int grid, int block, int smem, bool pdl, A... a) {
  cudaLaunchConfig_t cfg = {}; cfg.gridDim = dim3(grid); cfg.blockDim = dim3(block); cfg.dynamicSmemBytes = smem; cfg.stream = cudaStreamPerThread;
  cudaLaunchAttribute at[1]; at[0].id = cudaLaunchAttributeProgrammaticStreamSerialization; at[0].val.programmaticStreamSerializationAllowed = 1;
  cfg.attrs = at; cfg.numAttrs = pdl ? 1 : 0;
  cudaLaunchKernelEx(&cfg, k, a...);
}
static const int tune_t[6] = {1740, 1980, 2160, 2490, 2850, 2860}; constexpr int dev_stop = 100, dev_pdl = 1;

extern "C" void kernel_launch(void* const* d_in, const int* in_sizes, int n_in, void* d_out, int out_size) {
  const bf16 *x = (const bf16*)d_in[0], *mem0 = (const bf16*)d_in[1], *Wq = (const bf16*)d_in[2], *Wk = (const bf16*)d_in[3], *Wv = (const bf16*)d_in[4], *Wo = (const bf16*)d_in[5];
  const bf16 *wr = (const bf16*)d_in[8], *wi = (const bf16*)d_in[9];
  constexpr int SM_A = S_END + 1024, SM_R = sizeof(RowSmem), SM_C = 76 * 1024, SM_I = 116 * 1024;
  void *p_xn, *p_o, *p_x, *p_comm, *p_flags, *fn; cudaDriverEntryPointQueryResult qr;
  cudaGetSymbolAddress(&p_xn, g_xn); cudaGetSymbolAddress(&p_o, g_o); cudaGetSymbolAddress(&p_x, g_x); cudaGetSymbolAddress(&p_comm, g_comm); cudaGetSymbolAddress(&p_flags, g_flags);
  cudaGetDriverEntryPoint("cuTensorMapEncodeTiled", &fn, cudaEnableDefault, &qr);
  cudaFuncSetAttribute(layer_a_kernel, cudaFuncAttributeMaxDynamicSharedMemorySize, SM_A);
  cudaFuncSetAttribute(rows_fwd_kernel, cudaFuncAttributeMaxDynamicSharedMemorySize, SM_R);
  cudaFuncSetAttribute(rows_inv_kernel, cudaFuncAttributeMaxDynamicSharedMemorySize, SM_I);
  cudaFuncSetAttribute(cols_kernel, cudaFuncAttributeMaxDynamicSharedMemorySize, SM_C);
  cudaFuncSetAttribute(rows_fwd_kernel, cudaFuncAttributePreferredSharedMemoryCarveout, 100);
  cudaFuncSetAttribute(cols_kernel, cudaFuncAttributePreferredSharedMemoryCarveout, 100);
  cudaFuncSetAttribute(rows_inv_kernel, cudaFuncAttributePreferredSharedMemoryCarveout, 100);
  CUtensorMap tq, tk, tv, to, to32, tx, tao; EncFn enc = (EncFn)fn;
  make_map(enc, &tq, Wq, 4096, 640, 64, 64, CU_TENSOR_MAP_SWIZZLE_128B); make_map(enc, &tk, Wk, 4096, 640, 64, 64, CU_TENSOR_MAP_SWIZZLE_128B);
  make_map(enc, &tv, Wv, 4096, 640, 64, 64, CU_TENSOR_MAP_SWIZZLE_128B); make_map(enc, &to, Wo, 640, 4096, 64, 64, CU_TENSOR_MAP_SWIZZLE_128B);
  make_map(enc, &to32, Wo, 640, 4096, 16, 256, CU_TENSOR_MAP_SWIZZLE_32B);
  make_map(enc, &tx, p_xn, 640, 2048, 64, 64, CU_TENSOR_MAP_SWIZZLE_128B); make_map(enc, &tao, p_o, 4096, 2048, 64, 64, CU_TENSOR_MAP_SWIZZLE_128B);
  char* comm = (char*)(((uintptr_t)p_comm + (2 << 20) - 1) & ~(uintptr_t)((2 << 20) - 1));
  const bool pdl = dev_pdl;
#define L0PDL 0
  for (int l = 0; l < 2; l++) {
    ArgsA a{x, mem0, comm, (uint32_t*)p_flags + l * F_LAYER, wr, wi, (const char*)Wq, (const char*)Wo, l, {tune_t[0], tune_t[1], tune_t[2]}, {tune_t[3], tune_t[4], tune_t[5]}};
    if (dev_stop > 4 * l + 0) launch(layer_a_kernel, 132, 384, SM_A, pdl && (l || L0PDL), tq, tk, tv, to, to32, tx, tao, a);
    if (dev_stop > 4 * l + 1) launch(rows_fwd_kernel, 128, 320, SM_R, pdl, l ? (const bf16*)p_x : x, (const uint32_t*)a.flags);
    if (dev_stop > 4 * l + 2) launch(cols_kernel, 107, 384, SM_C, pdl, l);
    if (dev_stop > 4 * l + 3) launch(rows_inv_kernel, 128, 320, SM_I, pdl, l ? (bf16*)d_out : (bf16*)p_x, l == 0);
  }
}
```

```cpp
#include <cuda_runtime.h>
#include <cuda_bf16.h>
#include <cuda_fp16.h>
#include <cuda.h>
#include <stdint.h>

typedef __nv_bfloat16 bf16;
#define DEVINL __device__ __forceinline__

__device__ __align__(1024) bf16 g_xn[2048 * 640];
__device__ __align__(1024) bf16 g_x[2048 * 640];
__device__ __align__(1024) char g_kv[64 * 32 * 16384];
__device__ __align__(1024) char g_kvm[64 * 32 * 4096];
__device__ __align__(1024) bf16 g_o[2048 * 4096];
__device__ __align__(1024) bf16 g_part[4 * 2048 * 640];
__device__ __align__(1024) uint32_t g_y[321 * 2048];
__device__ __align__(1024) uint32_t g_wt[321 * 2048];
__device__ __align__(4096) char g_comm[4 << 20];
constexpr int F_KV = 0, F_KM = 1024, F_O = F_KM + 1024, F_P = F_O + 128, F_ROLE = F_P + 32 * 32, F_X = F_ROLE + 64, F_LAYER = F_X + 32;
__device__ __align__(1024) uint32_t g_flags[2 * F_LAYER];
__device__ int g_side[256];

template <int V> struct IC { static constexpr int value = V; };
template <int B, int E, class F> DEVINL void static_for(F&& f) { if constexpr (B < E) { f(IC<B>{}); static_for<B + 1, E>(f); } }

#define POLL_LIMIT (1 << 17)
DEVINL uint32_t smem_u32(const void* p) { return (uint32_t)__cvta_generic_to_shared(p); }
DEVINL uint32_t mapa(uint32_t a, uint32_t r) { uint32_t o; asm volatile("mapa.shared::cluster.u32 %0, %1, %2;" : "=r"(o) : "r"(a), "r"(r)); return o; }
DEVINL uint32_t clk() { uint32_t v; asm volatile("{.reg .b64 w; mov.u64 w, %%clock64; cvt.u32.u64 %0, w;}" : "=r"(v)::"memory"); return v; }
DEVINL void mbar_init(uint32_t bar, uint32_t cnt) { asm volatile("mbarrier.init.shared::cta.b64 [%0], %1;" ::"r"(bar), "r"(cnt) : "memory"); }
DEVINL void mbar_arrive(uint32_t bar) { asm volatile("mbarrier.arrive.shared::cta.b64 _, [%0];" ::"r"(bar) : "memory"); }
DEVINL void mbar_arrive_remote(uint32_t bar) { asm volatile("mbarrier.arrive.shared::cluster.b64 _, [%0];" ::"r"(bar) : "memory"); }
DEVINL void mbar_arrive_tx(uint32_t bar, uint32_t tx) { asm volatile("mbarrier.arrive.expect_tx.shared::cta.b64 _, [%0], %1;" ::"r"(bar), "r"(tx) : "memory"); }
DEVINL void mbar_wait(uint32_t bar, uint32_t ph) {
  asm volatile("{.reg .pred p,q; .reg .b32 c; mov.b32 c, 0;\n"
               "W0: add.u32 c,c,1; setp.lt.u32 q,c,0x100000; mbarrier.try_wait.parity.shared::cta.b64 p, [%0], %1; not.pred p,p; and.pred p,p,q; @p bra W0;}" ::"r"(bar), "r"(ph) : "memory");
}
DEVINL void bar_sync(int id, int n) { asm volatile("bar.sync %0, %1;" ::"r"(id), "r"(n) : "memory"); }
DEVINL void bar_arrive(int id, int n) { asm volatile("bar.arrive %0, %1;" ::"r"(id), "r"(n) : "memory"); }
DEVINL void cluster_sync() { asm volatile("barrier.cluster.arrive.release.aligned; barrier.cluster.wait.acquire.aligned;" ::: "memory"); }
DEVINL void tma_2d(uint32_t dst, const CUtensorMap* tm, int c0, int c1, uint32_t bar) {
  asm volatile("cp.async.bulk.tensor.2d.shared::cluster.global.mbarrier::complete_tx::bytes [%0], [%1, {%2, %3}], [%4];" ::"r"(dst), "l"(tm), "r"(c0), "r"(c1), "r"(bar) : "memory");
}
DEVINL void tma_2d_mc(uint32_t dst, const CUtensorMap* tm, int c0, int c1, uint32_t bar) {
  asm volatile("cp.async.bulk.tensor.2d.shared::cluster.global.mbarrier::complete_tx::bytes.multicast::cluster [%0], [%1, {%2, %3}], [%4], %5;" ::"r"(dst), "l"(tm), "r"(c0), "r"(c1), "r"(bar), "h"((uint16_t)3) : "memory");
}
DEVINL void bulk_g2s(uint32_t dst, const void* src, uint32_t bytes, uint32_t bar) {
  asm volatile("cp.async.bulk.shared::cluster.global.mbarrier::complete_tx::bytes [%0], [%1], %2, [%3];" ::"r"(dst), "l"(src), "r"(bytes), "r"(bar) : "memory");
}
DEVINL void l2_prefetch(const void* p, uint32_t bytes) { asm volatile("cp.async.bulk.prefetch.L2.global [%0], %1;" ::"l"(p), "r"(bytes) : "memory"); }
DEVINL void fence_proxy_async() { asm volatile("fence.proxy.async.global;" ::: "memory"); }
DEVINL void ldsm4t(uint32_t* r, uint32_t a) { asm volatile("ldmatrix.sync.aligned.m8n8.x4.trans.shared.b16 {%0,%1,%2,%3}, [%4];" : "=r"(r[0]), "=r"(r[1]), "=r"(r[2]), "=r"(r[3]) : "r"(a) : "memory"); }
DEVINL void stsm4(uint32_t a, uint32_t r0, uint32_t r1, uint32_t r2, uint32_t r3) { asm volatile("stmatrix.sync.aligned.m8n8.x4.shared.b16 [%0], {%1,%2,%3,%4};" ::"r"(a), "r"(r0), "r"(r1), "r"(r2), "r"(r3) : "memory"); }
DEVINL void mma16816(float* d, const uint32_t* a, uint32_t b0, uint32_t b1) {
  asm volatile("mma.sync.aligned.m16n8k16.row.col.f32.bf16.bf16.f32 {%0,%1,%2,%3}, {%4,%5,%6,%7}, {%8,%9}, {%0,%1,%2,%3};"
               : "+f"(d[0]), "+f"(d[1]), "+f"(d[2]), "+f"(d[3]) : "r"(a[0]), "r"(a[1]), "r"(a[2]), "r"(a[3]), "r"(b0), "r"(b1));
}
DEVINL void mma16816z(float* d, const uint32_t* a, uint32_t b0, uint32_t b1) {
  asm volatile("mma.sync.aligned.m16n8k16.row.col.f32.bf16.bf16.f32 {%0,%1,%2,%3}, {%4,%5,%6,%7}, {%8,%9}, {%10,%10,%10,%10};"
               : "=f"(d[0]), "=f"(d[1]), "=f"(d[2]), "=f"(d[3]) : "r"(a[0]), "r"(a[1]), "r"(a[2]), "r"(a[3]), "r"(b0), "r"(b1), "f"(0.f));
}
DEVINL void mma1688z(float* d, uint32_t a0, uint32_t a1, uint32_t b0) {
  asm volatile("mma.sync.aligned.m16n8k8.row.col.f32.bf16.bf16.f32 {%0,%1,%2,%3}, {%4,%5}, {%6}, {%7,%7,%7,%7};"
               : "=f"(d[0]), "=f"(d[1]), "=f"(d[2]), "=f"(d[3]) : "r"(a0), "r"(a1), "r"(b0), "f"(0.f));
}
DEVINL uint32_t movm(uint32_t a) { uint32_t r; asm volatile("movmatrix.sync.aligned.m8n8.trans.b16 %0, %1;" : "=r"(r) : "r"(a)); return r; }
DEVINL uint32_t pack_bf16(float lo, float hi) { uint32_t r; asm("cvt.rn.bf16x2.f32 %0, %1, %2;" : "=r"(r) : "f"(hi), "f"(lo)); return r; }
DEVINL uint32_t pack_f16(float lo, float hi) { uint32_t r; asm("cvt.rn.f16x2.f32 %0, %1, %2;" : "=r"(r) : "f"(hi), "f"(lo)); return r; }
DEVINL float bf_lo(uint32_t w) { return __uint_as_float(w << 16); }
DEVINL float bf_hi(uint32_t w) { return __uint_as_float(w & 0xffff0000u); }
DEVINL uint32_t hadd2bf(uint32_t a, uint32_t b) { uint32_t r; asm("add.rn.bf16x2 %0, %1, %2;" : "=r"(r) : "r"(a), "r"(b)); return r; }
DEVINL uint32_t hmax2bf(uint32_t a, uint32_t b) { uint32_t r; asm("max.bf16x2 %0, %1, %2;" : "=r"(r) : "r"(a), "r"(b)); return r; }
DEVINL uint32_t lds32(uint32_t a) { uint32_t v; asm volatile("ld.shared.u32 %0, [%1];" : "=r"(v) : "r"(a) : "memory"); return v; }
DEVINL uint2 lds64(uint32_t a) { uint2 v; asm volatile("ld.shared.v2.u32 {%0,%1}, [%2];" : "=r"(v.x), "=r"(v.y) : "r"(a) : "memory"); return v; }
DEVINL uint4 lds128(uint32_t a) { uint4 v; asm volatile("ld.shared.v4.u32 {%0,%1,%2,%3}, [%4];" : "=r"(v.x), "=r"(v.y), "=r"(v.z), "=r"(v.w) : "r"(a) : "memory"); return v; }
DEVINL void sts32(uint32_t a, uint32_t v) { asm volatile("st.shared.u32 [%0], %1;" ::"r"(a), "r"(v) : "memory"); }
DEVINL void sts64(uint32_t a, uint32_t x, uint32_t y) { asm volatile("st.shared.v2.u32 [%0], {%1,%2};" ::"r"(a), "r"(x), "r"(y) : "memory"); }
DEVINL void sts128(uint32_t a, uint4 v) { asm volatile("st.shared.v4.u32 [%0], {%1,%2,%3,%4};" ::"r"(a), "r"(v.x), "r"(v.y), "r"(v.z), "r"(v.w) : "memory"); }
DEVINL void stasync64(uint32_t a, uint32_t x, uint32_t y, uint32_t bar) { asm volatile("st.async.weak.shared::cluster.mbarrier::complete_tx::bytes.v2.b32 [%0], {%1,%2}, [%3];" ::"r"(a), "r"(x), "r"(y), "r"(bar) : "memory"); }
DEVINL uint4 ldg_rlx128(const void* p) { uint4 v; asm volatile("{.reg .b64 a,b; ld.relaxed.gpu.global.v2.b64 {a,b}, [%4]; mov.b64 {%0,%1}, a; mov.b64 {%2,%3}, b;}" : "=r"(v.x), "=r"(v.y), "=r"(v.z), "=r"(v.w) : "l"(p) : "memory"); return v; }
DEVINL uint2 ldg_rlx64(const void* p) { uint2 v; asm volatile("ld.relaxed.gpu.global.v2.u32 {%0,%1}, [%2];" : "=r"(v.x), "=r"(v.y) : "l"(p) : "memory"); return v; }
DEVINL void stg_rlx64(void* p, uint32_t x, uint32_t y) { asm volatile("{.reg .b64 a; mov.b64 a, {%1,%2}; st.relaxed.gpu.global.b64 [%0], a;}" ::"l"(p), "r"(x), "r"(y) : "memory"); }
DEVINL void stg_rlx128(void* p, uint32_t x, uint32_t y, uint32_t z, uint32_t w) { asm volatile("{.reg .b64 a,b; mov.b64 a, {%1,%2}; mov.b64 b, {%3,%4}; st.relaxed.gpu.global.v2.b64 [%0], {a,b};}" ::"l"(p), "r"(x), "r"(y), "r"(z), "r"(w) : "memory"); }
DEVINL void stg_rlx32(void* p, uint32_t x) { asm volatile("st.relaxed.gpu.global.u32 [%0], %1;" ::"l"(p), "r"(x) : "memory"); }
DEVINL uint4 ldg_cg128(const void* p) { uint4 v; asm volatile("ld.global.cg.v4.u32 {%0,%1,%2,%3}, [%4];" : "=r"(v.x), "=r"(v.y), "=r"(v.z), "=r"(v.w) : "l"(p) : "memory"); return v; }
DEVINL uint32_t ldg_cg32(const void* p) { uint32_t v; asm volatile("ld.global.cg.u32 %0, [%1];" : "=r"(v) : "l"(p) : "memory"); return v; }
DEVINL uint32_t ldg32_if(const void* p, int on) { uint32_t v; asm volatile("{.reg .pred q; setp.ne.s32 q, %2, 0; mov.u32 %0, 0; @q ld.global.cg.u32 %0, [%1];}" : "=r"(v) : "l"(p), "r"(on) : "memory"); return v; }
DEVINL uint4 ldg128_if(const void* p, int on) { uint4 v; asm volatile("{.reg .pred q; setp.ne.s32 q, %5, 0; mov.u32 %0, 0; mov.u32 %1, 0; mov.u32 %2, 0; mov.u32 %3, 0; @q ld.global.cg.v4.u32 {%0,%1,%2,%3}, [%4];}" : "=r"(v.x), "=r"(v.y), "=r"(v.z), "=r"(v.w) : "l"(p), "r"(on) : "memory"); return v; }
DEVINL void stg32_if(void* p, uint32_t v, int on) { asm volatile("{.reg .pred q; setp.ne.s32 q, %2, 0; @q st.global.u32 [%0], %1;}" ::"l"(p), "r"(v), "r"(on) : "memory"); }
DEVINL void stg128_if(void* p, uint4 v, int on) { asm volatile("{.reg .pred q; setp.ne.s32 q, %5, 0; @q st.global.v4.u32 [%0], {%1,%2,%3,%4};}" ::"l"(p), "r"(v.x), "r"(v.y), "r"(v.z), "r"(v.w), "r"(on) : "memory"); }
DEVINL uint4 ldg_ca128(const void* p) { uint4 v; asm volatile("ld.global.ca.v4.u32 {%0,%1,%2,%3}, [%4];" : "=r"(v.x), "=r"(v.y), "=r"(v.z), "=r"(v.w) : "l"(p) : "memory"); return v; }
DEVINL uint32_t ldg_ca32(const void* p) { uint32_t v; asm volatile("ld.global.ca.u32 %0, [%1];" : "=r"(v) : "l"(p) : "memory"); return v; }
DEVINL void flag_wait(const uint32_t* p, uint32_t want) {
  uint32_t v;
#pragma unroll 1
  for (int n = 0; n < POLL_LIMIT; n++) { asm volatile("ld.acquire.gpu.global.u32 %0, [%1];" : "=r"(v) : "l"(p) : "memory"); if (v >= want) break; __nanosleep(40); }
}
DEVINL void flag_wait_warp(const uint32_t* p, uint32_t want) {
  uint32_t v; int n = 0;
  do { asm volatile("ld.acquire.gpu.global.u32 %0, [%1];" : "=r"(v) : "l"(p) : "memory"); } while (__any_sync(~0u, v < want && ++n < POLL_LIMIT));
}
DEVINL void flag_add(uint32_t* p) { asm volatile("red.release.gpu.global.add.u32 [%0], 1;" ::"l"(p) : "memory"); }
DEVINL void flag_set(uint32_t* p, uint32_t v) { asm volatile("fence.acq_rel.gpu; st.relaxed.gpu.global.u32 [%0], %1;" ::"l"(p), "r"(v) : "memory"); }
DEVINL uint32_t ldg_rlx32(const void* p) { uint32_t v; asm volatile("ld.relaxed.gpu.global.u32 %0, [%1];" : "=r"(v) : "l"(p) : "memory"); return v; }
DEVINL float ex2(float x) { float y; asm("ex2.approx.ftz.f32 %0, %1;" : "=f"(y) : "f"(x)); return y; }
DEVINL float rcp(float x) { float y; asm("rcp.approx.ftz.f32 %0, %1;" : "=f"(y) : "f"(x)); return y; }
DEVINL uint32_t opaque(uint32_t x) { return __shfl_sync(~0u, x, threadIdx.x & 31); }
DEVINL uint32_t launder(uint32_t x) { asm volatile("" : "+r"(x)); return x; }
DEVINL void pdl_wait() { asm volatile("griddepcontrol.wait;" ::: "memory"); }
DEVINL void pdl_launch() { asm volatile("griddepcontrol.launch_dependents;" ::: "memory"); }
#define LOGS(cta, i)
#define LOGK(k, i)
#define LOG(cta, i)
#define LOGV(cta, i, v)
#define EV(i, v)
constexpr float SM_SCALE = 0.08838834764831845f * 1.4426950408889634f;

DEVINL void unpack8(uint4 v, float* f) { f[0] = bf_lo(v.x); f[1] = bf_hi(v.x); f[2] = bf_lo(v.y); f[3] = bf_hi(v.y); f[4] = bf_lo(v.z); f[5] = bf_hi(v.z); f[6] = bf_lo(v.w); f[7] = bf_hi(v.w); }
DEVINL uint4 pack8(const float* f) { return make_uint4(pack_bf16(f[0], f[1]), pack_bf16(f[2], f[3]), pack_bf16(f[4], f[5]), pack_bf16(f[6], f[7])); }
DEVINL void ln_row(float* f) {
  float s = 0.f;
#pragma unroll
  for (int i = 0; i < 40; i++) s += f[i];
#pragma unroll
  for (int o = 1; o < 16; o <<= 1) s += __shfl_xor_sync(~0u, s, o);
  const float mean = s * (1.f / 640.f); float q = 0.f;
#pragma unroll
  for (int i = 0; i < 40; i++) { f[i] -= mean; q = fmaf(f[i], f[i], q); }
#pragma unroll
  for (int o = 1; o < 16; o <<= 1) q += __shfl_xor_sync(~0u, q, o);
  const float rs = rsqrtf(q * (1.f / 640.f) + 1e-5f);
#pragma unroll
  for (int i = 0; i < 40; i++) f[i] *= rs;
}

struct ArgsA {
  const bf16* x; const bf16* mem0; char* comm; uint32_t* flags; const bf16* wr; const bf16* wi; const char* wq; const char* wo;
  int layer; int ta[4], tb[4], tc[2];
};

#define VP 4
#define HELD 0x2557
#define PRE 4
#define VPRE 8
#define R0 2
#define TRK 30
#define TEXP 200
#define TRD 0
#define TKV 300
#define KB1 5
#define W2D 0
#define WD 4
#define VPW 1
#define P1F 1
#define W0D 0
#define XD 0
#define TSF 0
#define W1D 60
constexpr int C_WV = 0;
constexpr int C_WO = 81920;
constexpr int C_KV = 163840;
constexpr int C_M  = C_KV + 24576;
constexpr int C_QK = C_M + 10240;
constexpr int C_VP = C_QK + 4096;
constexpr int C_S  = C_VP + 4096;
constexpr int C_O  = C_S + 2048;
constexpr int C_R  = C_O + 2048;
constexpr int C_T  = C_R + 256;
constexpr int S_BAR = 229376;
constexpr int S_END = S_BAR + 256;
enum { BAR_QK = 2, BAR_O = 3, BAR_H = 4, BAR_X = 5, BAR_W = 7  , BAR_E = 9, BAR_M1 = 10, BAR_M2 = 11, BAR_M3 = 12 };
constexpr int B_W = 0, B_S = 8, B_W2 = 16, B_KV = 24, B_WV = 40, B_WO = 48;
constexpr int G2_OFF = 0x130000, TS_OFF = 0x11000;

#define FEN() asm volatile("pmevent 0;" ::: "memory")
#define SCHED(x, c) asm volatile("{.reg .pred p; setp.eq.u32 p, %0, %1; @p exit;}" ::"r"(x), "r"(0x7fff0001u + 2 * (c)) : "memory")
DEVINL uint32_t g1page(uint32_t L) { L = ((L & 7) | ((L & 24) << 2)) << 1; return (L | (__popc(L & 0xb2) & 1)) << 12; }
DEVINL void spin_until(uint32_t t) {
  asm volatile("{.reg .pred p; .reg .b32 c; .reg .b64 w;\nS0: mov.u64 w, %%clock64; cvt.u32.u64 c, w; sub.u32 c, %0, c; setp.lt.u32 p, c, 16384; @p bra S0;}" ::"r"(t) : "memory");
}
DEVINL uint32_t wait_until(uint32_t t, uint32_t z) { uint32_t r;
  asm volatile("{.reg .pred p; .reg .b32 c,x,y; .reg .b64 w;\nT0: .branchtargets L0, L1, L2, L3, L4, L5, L6, L7, L8, L9, L10;\n mov.u32 x, %2;\n"
               "mov.u64 w, %%clock64; cvt.u32.u64 c, w; sub.u32 c, %1, c; setp.ge.u32 p, c, 16384; @p bra.uni L0;\n"
               "S0: mov.u64 w, %%clock64; cvt.u32.u64 c, w; sub.u32 c, %1, c; setp.gt.s32 p, c, 40; @p bra.uni S0;\n"
               "mad.lo.s32 c, c, 37, 1200; shr.s32 c, c, 8; max.s32 c, c, 0;\nbrx.idx.uni c, T0;\n"
               "L10: mul.lo.u32 x, x, x; L9: mul.lo.u32 x, x, x; L8: mul.lo.u32 x, x, x; L7: mul.lo.u32 x, x, x; L6: mul.lo.u32 x, x, x; L5: mul.lo.u32 x, x, x; L4: mul.lo.u32 x, x, x; L3: mul.lo.u32 x, x, x; L2: mul.lo.u32 x, x, x; L1: mul.lo.u32 x, x, x; L0: mov.u32 %0, x;}" : "=r"(r) : "r"(t), "r"(z) : "memory"); return r;
}
DEVINL void gtime(uint32_t& G16, uint32_t& C) {
  asm volatile("{.reg .b64 w; .reg .b32 g,g0,a;\n mov.u64 w, %%clock64; cvt.u32.u64 %1, w; mov.u64 w, %%globaltimer; cvt.u32.u64 g0, w; mul.lo.u32 a, g0, -11;\n"
               "mov.u64 w, %%globaltimer; cvt.u32.u64 g, w; add.u32 a, a, g; mov.u64 w, %%globaltimer; cvt.u32.u64 g, w; add.u32 a, a, g; mov.u64 w, %%globaltimer; cvt.u32.u64 g, w; add.u32 a, a, g; mov.u64 w, %%globaltimer; cvt.u32.u64 g, w; add.u32 a, a, g; mov.u64 w, %%globaltimer; cvt.u32.u64 g, w; add.u32 a, a, g; mov.u64 w, %%globaltimer; cvt.u32.u64 g, w; add.u32 a, a, g; mov.u64 w, %%globaltimer; cvt.u32.u64 g, w; add.u32 a, a, g; mov.u64 w, %%globaltimer; cvt.u32.u64 g, w; add.u32 a, a, g; mov.u64 w, %%globaltimer; cvt.u32.u64 g, w; add.u32 a, a, g; mov.u64 w, %%globaltimer; cvt.u32.u64 g, w; add.u32 a, a, g; mov.u64 w, %%globaltimer; cvt.u32.u64 g, w; add.u32 a, a, g; \n mul.lo.u32 a, a, 341; shr.u32 a, a, 8; mad.lo.u32 %0, g0, 16, a;}" : "=r"(G16), "=r"(C)::"memory");
}
DEVINL uint32_t pack_tag(float lo, float hi, uint32_t tg) {
  const uint32_t w = pack_bf16(lo, __uint_as_float(tg | 0x3F800000u)), a = __float_as_uint(hi) + (tg ^ 0x10000u); uint32_t r;
  asm("lop3.b32 %0, %1, %2, 0xFFFE0000, 0xE4;" : "=r"(r) : "r"(a), "r"(w)); return r;
}
DEVINL void load_kv(uint32_t sb, int h, int j, int s) {
  asm volatile("{.reg .pred p; elect.sync _|p, 0xffffffff;\n fence.proxy.async.global;\n @p mbarrier.arrive.expect_tx.shared::cta.b64 _, [%2], 12288;\n"
               " @p cp.async.bulk.shared::cluster.global.mbarrier::complete_tx::bytes [%0], [%1], 12288, [%2];}"
               ::"r"(sb + C_KV + (s & 1) * 12288), "l"(g_kv + (size_t)(s * 32 + h) * 16384 + j * 4096), "r"(sb + S_BAR + B_KV + (s & 1) * 8) : "memory");
}

template <int KH>
DEVINL void chain_mma(uint32_t sb0, const ArgsA& args) {
  const int lane = threadIdx.x & 31, mg = (threadIdx.x >> 5) & 3, mi = lane >> 3, r = lane & 7;
  const uint32_t aW = opaque(sb0 + (uint32_t)(((mi >> 1) * 8 + r) * 128 + (((mg + 4 * (mi & 1)) ^ r) << 4)));
  const uint32_t aL = opaque(sb0 + lane * 16);
  const uint32_t aLm = opaque(sb0 + mg * 512 + lane * 16);
#define sb (launder(aL) & ~511u)
  constexpr int OV = C_WV + KH * 40960, OM = C_M + KH * 5120, NF = KH ? 16 : 24;
  auto owo = [](int f) { return C_WO + (KH + 2 * (f >> 3)) * 16384 + (f & 7) * 2048; };
  auto held = [](int k) { return (HELD >> k) & 1; };
  auto rank = [](int k) { return __popc(HELD & ((1 << k) - 1)); };
  uint32_t wq[20][4], wk[20][4];
  mbar_wait(sb + S_BAR + B_W, 0);
#pragma unroll
  for (int k = 0; k < 12; k++) { ldsm4t(wq[k], aW + OV + k * 2048); ldsm4t(wk[k], aW + C_WO + KH * 40960 + k * 2048); }
  bar_arrive(BAR_H, 288);
  mbar_wait(sb + S_BAR + B_W2, 0);
#pragma unroll
  for (int k = 12; k < 20; k++) { ldsm4t(wq[k], aW + OV + k * 2048); ldsm4t(wk[k], aW + C_WO + KH * 40960 + k * 2048); }
  bar_sync(BAR_E, 384);
  mbar_wait(sb + S_BAR + B_WV, 0);
  uint32_t sx = args.layer << 16;
#pragma unroll 1
  while (true) {
    uint32_t v[20][4], b[10][4];
    {
      const uint32_t o = launder(aLm) - sb, on = (sx >> 16) != (uint32_t)args.layer;
      const char* p = args.comm + lds32(sb + C_T + KH * 1024 + 4 + (o >> 1));
      const uint32_t am = sb + OM + (o & 0x400) + ((o & 0x3f0) >> 1);
      { const uint32_t zero = (uint32_t)(uintptr_t)p & 1; uint32_t a = aW;
#pragma unroll
        for (int k = 0; k < 20; k++) if (held(k) && rank(k) < VPRE) { ldsm4t(v[k], a + OV + k * 2048); if (rank(k) % VPW == VPW - 1) a = aW + (v[k][0] & zero); } }
      p += wait_until(lds32(sb + C_R + 48) + args.tb[0], am & 1);
      uint4 a = ldg_rlx128(p);
      __syncwarp();
#pragma unroll
      for (int k = 0; k < 20; k++) if (held(k) && rank(k) >= VPRE) ldsm4t(v[k], aW + OV + k * 2048);
      SCHED(am ^ on, 29);
      if (__builtin_expect(__any_sync(~0u, on && (((a.x ^ sx) | (a.z ^ sx)) & 0x10000u)), 0)) {
        int lim = 0;
        do a = ldg_rlx128(p); while (__any_sync(~0u, (((a.x ^ sx) | (a.z ^ sx)) & 0x10000u) && ++lim < POLL_LIMIT));
      }
      if (on) { sts64(am, a.x, a.z); sts64(am + 512, a.y, a.w); }
      bar_sync(BAR_W + KH, 128);
      ldsm4t(b[0], aL + OM); ldsm4t(b[1], aL + OM + 512);
    }
    float cq[4], ck[4], cv[4];
    static_for<0, 20>([&](auto I) {
      constexpr int k = I.value, p = k >> 1;
      const uint32_t b0 = b[p][(k & 1) * 2], b1 = b[p][(k & 1) * 2 + 1];
      if (k == 0) { mma16816z(cv, v[0], b0, b1); mma16816z(cq, wq[k], b0, b1); mma16816z(ck, wk[k], b0, b1); }
      else { if (k < 20 - VP) mma16816(cv, v[k], b0, b1); mma16816(cq, wq[k], b0, b1); mma16816(ck, wk[k], b0, b1); }
      if (k == KB1) bar_sync(BAR_M1, 288);
      if (k == KB1 + 4) bar_sync(BAR_M2, 288);
      if (k == KB1 + 8) bar_sync(BAR_M3, 352);
      { constexpr int q = (k + 8 - KB1) >> 1; if constexpr (((k - KB1) & 1) == 0 && q >= 2 && q < 10) ldsm4t(b[q], aL + OM + q * 512); }
      if constexpr (k + 3 < 20 - VP && !((HELD >> (k + 3)) & 1)) ldsm4t(v[k + 3], aW + OV + (k + 3) * 2048);
      if (k >= 20 - VP && k < 20 - VP + PRE && !held(k)) ldsm4t(v[k], aW + OV + k * 2048);
      if (P1F && (k & 1) && k < 19) FEN();
    });
    stsm4(aLm + C_QK + KH * 2048, pack_bf16(cq[0], cq[1]), pack_bf16(cq[2], cq[3]), pack_bf16(ck[0], ck[1]), pack_bf16(ck[2], ck[3]));
    bar_arrive(BAR_QK, 384);
    FEN();
    const uint32_t l8 = (launder(aL) & 511) >> 1, px = lds32(sb + C_R + 80);
#pragma unroll
    for (int k = 20 - VP + PRE; k < 20; k++) if (!held(k)) ldsm4t(v[k], aW + OV + k * 2048);
#pragma unroll
    for (int k = 20 - VP; k < 20; k++) {
      const int p = k >> 1, q = k - 20 + VP; const uint32_t b0 = b[p][(k & 1) * 2], b1 = b[p][(k & 1) * 2 + 1];
      if (q % 3 == 0) mma16816(cv, v[k], b0, b1); else if (q == 1) mma16816z(cq, v[k], b0, b1); else if (q == 2) mma16816z(ck, v[k], b0, b1);
      else if (q % 3 == 1) mma16816(cq, v[k], b0, b1); else mma16816(ck, v[k], b0, b1);
    }
    if (VP >= 3) {
#pragma unroll
      for (int i = 0; i < 4; i++) cv[i] += cq[i] + ck[i];
    }
    { const uint32_t vx = pack_bf16(cv[0], cv[1]), vy = pack_bf16(cv[2], cv[3]);
      const uint32_t av = aLm - l8 + C_VP + KH * 256;
      stasync64(av + 2048 + px, vx, vy, sb + S_BAR + B_S + px);
      sts64(av, vx, vy);
      __syncwarp();
      if (l8 == 0) mbar_arrive(sb + S_BAR + B_S); }
    sx += 0x10000;
    if ((sx >> 16) == args.layer + 64u) break;
    uint32_t w[NF][4];
    {
      const uint32_t zero = px & 1; uint32_t a = aW;
      const bool tsw = KH == 1 && __any_sync(~0u, launder(aLm) == aL); uint2 ts = make_uint2(0, 0); uint4 cal = make_uint4(0, 0, 0, 0);
      if ((sx >> 16) == args.layer + 1u) mbar_wait(sb + S_BAR + B_WO, 0);
#pragma unroll
      for (int f = 0; f < 8; f++) { ldsm4t(w[f], a + owo(f));
        if (KH == 1 && f == TSF && tsw) { ts = ldg_rlx64(args.comm + TS_OFF + l8); cal = lds128(sb + C_R + 64); }
        uint32_t d = w[f][0] & zero;
#pragma unroll
        for (int q = 0; q < TRD; q++) d = __popc(d);
        a = aW + d; }
      if (KH == 1 && tsw) {
        const uint32_t d0 = ts.x - cal.x, d1 = ts.y - cal.x;
        const int dt = (int)__reduce_max_sync(~0u, max(d0 < 32768u ? d0 : 0u, d1 < 32768u ? d1 : 0u));
        sts32(sb + C_R + 48, cal.y + min((dt * cal.z) >> 16, 8192u));
      }
    }
    const uint32_t go = lds32(sb + C_T + KH * 1024 + ((launder(aLm) - sb) >> 1));
    SCHED(go, 30);
    bar_sync(BAR_O, 384);
    uint32_t ob[16];
#pragma unroll
    for (int p = 0; p < 4; p++) ldsm4t(ob + 4 * p, aL + C_O + p * 512);
    __syncwarp();
    float r0, r1;
    { const uint2 rr = lds64(sb + C_R + 128 + ((launder(aL) >> 1) & 24)); r0 = rcp(__uint_as_float(rr.x)); r1 = rcp(__uint_as_float(rr.y)); }
    constexpr int RA = KH ? 0 : R0;
    static_for<0, NF>([&](auto I) {
      constexpr int f = I.value, k = f & 7; const uint32_t* A = w[f];
      if (k == 0) mma16816z(cq, A, ob[0], ob[1]); else if (k == 1) mma16816z(ck, A, ob[2], ob[3]);
      else if (k & 1) mma16816(ck, A, ob[2 * k], ob[2 * k + 1]); else mma16816(cq, A, ob[2 * k], ob[2 * k + 1]);
      if (f == 5 && RA) {
#pragma unroll
        for (int q = 0; q < RA; q++) ldsm4t(w[8 + q], aW + owo(8 + q));
        FEN();
      }
      if constexpr (f >= 8 && f + WD < NF) ldsm4t(w[f + WD], aW + owo(f + WD));
      if constexpr (XD != 0) { if (f == 15) spin_until(clk() + XD); }
      if (k == 7) stg_rlx64(args.comm + go + (f < 8 ? 0 : f < 16 ? 0x30000 : 0x100000), pack_tag((cq[0] + ck[0]) * r0, (cq[1] + ck[1]) * r1, sx & 0x10000u), pack_bf16((cq[2] + ck[2]) * r0, (cq[3] + ck[3]) * r1));
      if (f == 7) {
        if constexpr ((KH ? W1D : W0D) != 0) spin_until(clk() + (KH ? W1D : W0D)); else FEN();
#pragma unroll
        for (int q = RA; q < WD; q++) ldsm4t(w[8 + q], aW + owo(8 + q));
      }
      if (f >= 7 && (f & 1)) FEN();
    });
  }
}

#undef sb
DEVINL void chain_helper(uint32_t sb, uint32_t px, int h, int j, const ArgsA& args, const CUtensorMap* tq, const CUtensorMap* tk, const CUtensorMap* tv, const CUtensorMap* to) {
  const int c = 2 * h + j;
  const uint32_t bW = sb + S_BAR + B_W, bS = sb + S_BAR + B_S, bKV = sb + S_BAR + B_KV;
  const uint32_t lane0 = opaque(threadIdx.x & 31);
  const uint32_t warp = __reduce_max_sync(~0u, (threadIdx.x >> 5) & 3);
  uint32_t G0, C0;
  { const int tid = threadIdx.x - 256;
    if (tid == 0) { mbar_arrive_tx(bW, 98304); mbar_arrive_tx(bW + B_W2, 65536); mbar_arrive_tx(bW + B_WV, 81920); mbar_arrive_tx(bW + B_WO, 81920);
#pragma unroll 1
      for (int q = 0; q < 10; q++) { const int i = (q & 1) * 5 + (q >> 1); const uint32_t bar = q < 6 ? bW : bW + B_W2;
        tma_2d(sb + C_WV + i * 8192, tq, h * 128 + j * 64, i * 64, bar); tma_2d(sb + C_WO + i * 8192, tk, h * 128 + j * 64, i * 64, bar); } }
    gtime(G0, C0);
    { const uint32_t g = lane0 >> 2, t = lane0 & 3;
      sts128(sb + C_T + 2048 + tid * 16, make_uint4(g1page(c >> 1) + (c & 1) * 2048 + (warp == 0 ? 0 : warp == 1 ? 0x30000 : 0x100000) + ((g >> 2) * 4 + t) * 64 + (g & 3) * 16,
                                                    g1page(((t >> 1) + (g >> 2) * 2) * 4 + warp) + G2_OFF + c * 64 + (g & 3) * 16 + (t & 1) * 8,
                                                    g1page((h & 3) * 4 + 1 + (warp >> 1)) + G2_OFF + (warp & 1) * 1024 + lane0 * 16, (g & 1) ? 0x3F800000u : 0x00003F80u)); }
    sts32(sb + C_R + 80, px); sts32(sb + C_R + 48, C0 - 65536);
#pragma unroll
    for (int kh = 0; kh < 2; kh++)
      sts64(sb + C_T + kh * 1024 + tid * 8, g1page(j * 16 + kh * 8 + (tid >> 4)) + (tid & 8) * 256 + h * 64 + (tid & 7) * 8, g1page((h & 3) * 4) + G2_OFF + kh * 2048 + tid * 16);
#pragma unroll
    for (int i = 0; i < 5; i++) { const int q = tid + i * 128, n = q & 7, d0 = (q >> 3) * 8; const uint4 v = *(const uint4*)(args.mem0 + n * 640 + d0); const uint32_t w[4] = {v.x, v.y, v.z, v.w};
#pragma unroll
      for (int e = 0; e < 8; e++) asm volatile("st.shared.u16 [%0], %1;" ::"r"(sb + C_M + (d0 + e) * 16 + n * 2), "h"((unsigned short)(w[e >> 1] >> ((e & 1) * 16))) : "memory"); }
    auto round2 = [&](int q0, int q1) {
#pragma unroll 1
      for (int q = q0; q < q1; q++) { const int i = (q & 1) * 5 + (q >> 1); tma_2d(sb + C_WV + i * 8192, tv, h * 128 + j * 64, i * 64, bW + B_WV); }
#pragma unroll 1
      for (int q = q0; q < q1; q++) { const int i = (q & 1) * 5 + (q >> 1); tma_2d(sb + C_WO + i * 8192, to, j * 320 + (i >> 1) * 64, h * 128 + ((i & 1) ^ j) * 64, bW + B_WO); } };
    if (warp == 0) { bar_sync(BAR_H, 288); if (tid == 0) round2(0, 6); __syncwarp(); }
    bar_sync(BAR_E, 384);
    if (tid == 0) round2(6, 10);
    if (warp == 3) {
      if (tid == 96) LOG(c, 250);
      flag_wait_warp(args.flags + F_KV + h, 2);
      load_kv(sb, h, j, 0); load_kv(sb, h, j, 1); if (tid == 96) LOG(c, 251);
    }
  }
  auto calib = [&]() { uint32_t G, C; gtime(G, C);
    const float rt = (float)(C - C0) * rcp((float)(G - G0));
    sts128(sb + C_R + 32, make_uint4(G, C, __float2uint_rn(rt * 65536.f) & 0xffffu, __float_as_uint(rcp(rt)))); __syncwarp(); };
  auto do_export = [&](int s, uint32_t lane, bool arrive) {
    uint32_t k0[2][4], k1[2][4]; uint2 a[4], b[4];
    const uint32_t ak = sb + C_QK + 256 + (lane >> 4) * 512 + (lane & 15) * 16, av = sb + C_VP + (lane >> 3) * 512 + (lane & 7) * 8;
#pragma unroll
    for (int i = 0; i < 2; i++) { ldsm4t(k0[i], ak + i * 1024); ldsm4t(k1[i], ak + i * 1024 + 2048); }
#pragma unroll
    for (int i = 0; i < 4; i++) { a[i] = lds64(av + i * 64); b[i] = lds64(av + i * 64 + 256); }
    char* dst = g_kvm + ((s * 32 + h) * 4096 + j * 1024 + lane * 16);
    const uint32_t tg = (args.layer ^ 1) << 16;
    auto put = [&](char* q, uint32_t x, uint32_t y, uint32_t z, uint32_t w) { stg_rlx128(q, (x & ~0x10000u) | tg, y, (z & ~0x10000u) | tg, w); };
#pragma unroll
    for (int i = 0; i < 2; i++) put(dst + i * 512, hadd2bf(k0[i][0], k1[i][0]), hadd2bf(k0[i][1], k1[i][1]), hadd2bf(k0[i][2], k1[i][2]), hadd2bf(k0[i][3], k1[i][3]));
    put(dst + 2048, hadd2bf(a[0].x, b[0].x), hadd2bf(a[1].x, b[1].x), hadd2bf(a[2].x, b[2].x), hadd2bf(a[3].x, b[3].x));
    put(dst + 2560, hadd2bf(a[0].y, b[0].y), hadd2bf(a[1].y, b[1].y), hadd2bf(a[2].y, b[2].y), hadd2bf(a[3].y, b[3].y));
    if (arrive) bar_arrive(BAR_M3, 352);
    stg_rlx32(args.flags + F_KM + h * 32 + j, s + 1);
  };
  if (warp == 0) { calib(); bar_arrive(BAR_M1, 288); } else if (warp == 1) bar_arrive(BAR_M2, 288); else bar_arrive(BAR_M3, 352);
  bool kv_all = false;
#pragma unroll 1
  for (int s = 0;; s++) {
    const uint32_t ph = s & 1, kvb = sb + C_KV + ph * 12288;
    uint32_t lane = __shfl_sync(~0u, lane0, lane0);
    if (warp == 0) {
      if (lane == 0) mbar_arrive_tx(bS, s < 63 ? 3072 : 2048);
      const uint4 cal = lds128(sb + C_R + 32);
      bar_sync(BAR_M3, 352);
      sts32(sb + C_R + 52, 0);
      const uint32_t E = clk();
      if (lane == 0) { const uint32_t e16 = cal.x + (uint32_t)__float2int_rn((float)(int)(E - cal.y) * __uint_as_float(cal.w));
        stg_rlx32(args.comm + TS_OFF + c * 4, e16); sts128(sb + C_R + 64, make_uint4(e16, E, cal.z, 0)); }
      __syncwarp();
    }
    if (s == 63) { bar_sync(BAR_QK, 384); mbar_wait(bS, 1); if (warp == 3) do_export(63, lane, false); break; }
    mbar_wait(bKV + ph * 8, (s >> 1) & 1);
    const uint32_t mi = lane >> 3, r = lane & 7, zero = lane >> 5;
    {
      uint32_t qa[4][4], km[4]; uint2 kb[4]; float s0[4], s1[4], s2[4];
      const uint32_t aK = kvb + j * 8192 + warp * 1024 + lane * 16, aQ = sb + C_QK + (mi & 1) * 2048 + ((mi >> 1) * 8 + r) * 16;
      const uint32_t aKm = sb + C_QK + 256 + warp * 512 + (lane >> 4) * 2048 + (lane & 15) * 16;
#pragma unroll
      for (int i = 0; i < 4; i++) kb[i] = lds64(aK + ((warp ^ i) >> 1) * 512 + ((warp ^ i) & 1) * 8);
      const uint32_t aH = sb + C_S + warp * 256 + lane * 8, aR = aH + 1024 + px;
      SCHED(aQ ^ aR ^ aKm ^ ((kb[0].x ^ kb[1].x ^ kb[2].x ^ kb[3].x) & zero), 60);
      bar_sync(BAR_QK, 384);
      ldsm4t(qa[0], aQ + warp * 512); ldsm4t(km, aKm); ldsm4t(qa[1], aQ + (warp ^ 1) * 512); ldsm4t(qa[2], aQ + (warp ^ 2) * 512); ldsm4t(qa[3], aQ + (warp ^ 3) * 512);
      mma16816z(s0, qa[0], kb[0].x, kb[0].y); mma16816z(s2, qa[0], km[0], km[1]); mma16816z(s1, qa[1], kb[1].x, kb[1].y);
      mma16816(s2, qa[0], km[2], km[3]); mma16816(s0, qa[2], kb[2].x, kb[2].y); mma16816(s1, qa[3], kb[3].x, kb[3].y);
      const uint32_t w0 = pack_bf16((s0[0] + s0[2]) + (s1[0] + s1[2]), (s0[1] + s0[3]) + (s1[1] + s1[3]));
      const uint32_t w1 = pack_bf16(s2[0] + s2[2], s2[1] + s2[3]);
      stasync64(aR, w0, w1, bS + px);
      sts64(aH, w0, w1);
    }
    {
      uint32_t vx[4][4], sl[5];
      const uint32_t aVx = kvb + 4096 + (warp >> 1) * (j ? -4096 : 4096) + (warp & 1) * 1024 + lane * 16;
      const uint32_t a8 = sb + lane * 8, av = a8 + C_VP + warp * 1024;
      const uint32_t aO = sb + C_O + ((warp >> 1) * 64 + (warp & 1) * 16 + (mi & 1) * 32 + (mi >> 1) * 8 + r) * 16, aR = sb + C_R + (lane & 28);
      bar_sync(BAR_X, 128);
      { uint2 t[4];
#pragma unroll
        for (int u = 0; u < 4; u++) t[u] = lds64(a8 + C_S + u * 256);
#pragma unroll
        for (int i = 0; i < 4; i++) { const uint4 q = lds128(aVx + (i & 1) * 2048 + (i >> 1) * 512); vx[i][0] = q.x; vx[i][1] = q.z ^ zero; vx[i][2] = q.y ^ zero; vx[i][3] = q.w; }
#pragma unroll
        for (int u = 0; u < 4; u++) sl[u] = t[u].x;
        sl[4] = pack_bf16((bf_lo(t[0].y) + bf_lo(t[1].y)) + (bf_lo(t[2].y) + bf_lo(t[3].y)), (bf_hi(t[0].y) + bf_hi(t[1].y)) + (bf_hi(t[2].y) + bf_hi(t[3].y))); }
      mbar_wait(bS, ph);
      uint32_t vm[2][4];
      { uint2 t[4];
#pragma unroll
        for (int u = 0; u < 4; u++) t[u] = lds64(a8 + C_S + 1024 + u * 256);
#pragma unroll
        for (int u = 0; u < 4; u++) sl[u] = hadd2bf(sl[u], t[u].x);
        sl[4] = hadd2bf(hadd2bf(hadd2bf(sl[4], t[0].y), t[1].y), hadd2bf(t[2].y, t[3].y)); }
      uint32_t m2 = hmax2bf(hmax2bf(hmax2bf(sl[0], sl[1]), hmax2bf(sl[2], sl[3])), sl[4]);
      const uint32_t x1 = __shfl_xor_sync(~0u, m2, 1), x2 = __shfl_xor_sync(~0u, m2, 2), x3 = __shfl_xor_sync(~0u, m2, 3);
#pragma unroll
      for (int i = 0; i < 4; i++) { const uint2 q = lds64(av + i * 256); vm[i >> 1][(i & 1) * 2] = q.x; vm[i >> 1][(i & 1) * 2 + 1] = q.y; }
      float sv[10];
#pragma unroll
      for (int u = 0; u < 5; u++) { sv[2 * u] = bf_lo(sl[u]) * SM_SCALE; sv[2 * u + 1] = bf_hi(sl[u]) * SM_SCALE; }
      m2 = hmax2bf(hmax2bf(m2, x1), hmax2bf(x2, x3));
      const float mx = fmaxf(bf_lo(m2), bf_hi(m2));
      float o0[4], o1[4];
      sv[8] = ex2(fmaf(mx, -SM_SCALE, sv[8])); sv[9] = ex2(fmaf(mx, -SM_SCALE, sv[9]));
      { const uint32_t p = pack_bf16(sv[8], sv[9]); mma16816z(o0, vm[0], p, p); mma16816z(o1, vm[1], p, p); }
#pragma unroll
      for (int i = 0; i < 4; i++) sv[i] = ex2(fmaf(mx, -SM_SCALE, sv[i]));
      { const uint32_t p0 = pack_bf16(sv[0], sv[1]), p1 = pack_bf16(sv[2], sv[3]); mma16816(o0, vx[0], p0, p1); mma16816(o1, vx[2], p0, p1); }
#pragma unroll
      for (int i = 4; i < 8; i++) sv[i] = ex2(fmaf(mx, -SM_SCALE, sv[i]));
      { const uint32_t p0 = pack_bf16(sv[4], sv[5]), p1 = pack_bf16(sv[6], sv[7]); mma16816(o0, vx[1], p0, p1); mma16816(o1, vx[3], p0, p1); }
      float su = (((sv[8] + sv[9]) + ((sv[0] + sv[1]) + (sv[2] + sv[3]))) + (sv[4] + sv[5])) + (sv[6] + sv[7]);
      { const float a1 = __shfl_xor_sync(~0u, su, 1), a2 = __shfl_xor_sync(~0u, su, 2), a3 = __shfl_xor_sync(~0u, su, 3); su = (su + a1) + (a2 + a3); }
      sts32(aR + 128, __float_as_uint(su));
      stsm4(aO, pack_bf16(o0[0], o0[1]), pack_bf16(o0[2], o0[3]), pack_bf16(o1[0], o1[1]), pack_bf16(o1[2], o1[3]));
      bar_sync(BAR_O, 384);
    }
    const uint32_t t0 = lds32(sb + C_R + 48);
    const uint4 xo = lds128(sb + C_T + 2048 + warp * 512 + lane * 16);
    const uint32_t tag = (s + args.layer + 1) & 1, tm = 0u - tag;
    if (warp == 3) {
      if (lane == 0) { LOGS(c, s); LOGV(c, 192 + (s >> 1), clk()); }
      const bool chk = !ph && !kv_all;
      const uint32_t* f = args.flags + F_KV + (lane < 2 ? 30 + lane : min((s + 2) >> 1, 31)) * 32 + h;
      uint32_t rdy = 2;
      if (chk) rdy = ldg_rlx32(f);
      spin_until(t0 + args.tc[0]);
      do_export(s, lane, true);
      spin_until(t0 + args.tc[1]);
      if (chk) {
        int n = 0;
        while (__any_sync(~0u, lane >= 2 && rdy < 2 && ++n < POLL_LIMIT)) rdy = ldg_rlx32(f);
        kv_all = __all_sync(~0u, rdy >= 2);
        asm volatile("fence.acquire.gpu;" ::: "memory");
      }
      if (s < 61) load_kv(sb, h, j, s + 2);
      if (lane == 0) LOG(c, 64 + s);
    }
    if (warp == 2) calib();
    if (warp < 2 || (warp == 2 && !(c & 16))) {
      const char* p = args.comm + xo.x; char* g2w = args.comm + xo.y;
      const uint32_t s0 = (lane & 8) ? 0u : xo.w, s1 = (lane & 8) ? xo.w : 0u;
      int lim = 0; bool bad;
      p += wait_until(t0 + args.ta[warp == 0 ? 0 : warp == 2 ? 3 : 1 + ((c >> 4) & 1)], lane >> 5);
      do {
        uint4 a[4]; float z0[4], z1[4], y[4];
#pragma unroll
        for (int i = 0; i < 4; i++) a[i] = ldg_rlx128(p + i * 512);
        ++lim;
        { const uint32_t A[4] = {a[0].x, a[0].y, a[0].z, a[0].w}; mma16816z(z0, A, s0, s1); }
        { const uint32_t A[4] = {a[1].x, a[1].y, a[1].z, a[1].w}; mma16816z(z1, A, s0, s1); }
        { const uint32_t A[4] = {a[2].x, a[2].y, a[2].z, a[2].w}; mma16816(z0, A, s0, s1); }
        { const uint32_t A[4] = {a[3].x, a[3].y, a[3].z, a[3].w}; mma16816(z1, A, s0, s1); }
        const uint32_t m0 = launder((a[0].x ^ tm) | (a[0].z ^ tm)), m1 = launder((a[1].x ^ tm) | (a[1].z ^ tm)), m2 = launder((a[2].x ^ tm) | (a[2].z ^ tm)), m3 = launder((a[3].x ^ tm) | (a[3].z ^ tm));
        bad = __any_sync(~0u, ((launder(m0 | m1 | m2) | m3) & 0x10000u) && lim < POLL_LIMIT);
#pragma unroll
        for (int i = 0; i < 4; i++) { y[i] = z0[i] + z1[i]; y[i] += __shfl_xor_sync(~0u, y[i], 16); }
        const uint32_t w0 = pack_tag(y[0], y[1], tag << 16), w1 = pack_bf16(y[2], y[3]);
        if (!bad) stg_rlx64(g2w, w0, w1);
      } while (bad);
      if (lane == 0 && warp == 0) LOGV(c, 128 + s, lim);
      if (lane == 0) { EV(warp, clk() - t0); EV(3 + warp, lim); }
    }
    if (warp < 3) {
      constexpr uint32_t hg = 2048, hs = 5120;
      const char* p = args.comm + xo.z;
      const uint32_t aMw = sb + C_M + 2048 + warp * 1024 + lane * 8;
      int lim = 0; bool bad;
      p += wait_until(t0 + args.tb[warp + 1], lane >> 5);
      do { uint4 a[4]; uint32_t m = 0; ++lim;
#pragma unroll
        for (int i = 0; i < 4; i++) a[i] = ldg_rlx128(p + (i & 1) * 512 + (i >> 1) * hg);
#pragma unroll
        for (int i = 0; i < 4; i++) { const uint32_t q = aMw + (i & 1) * 256 + (i >> 1) * hs; sts64(q, a[i].x, a[i].z); sts64(q + 512, a[i].y, a[i].w); m |= (a[i].x ^ tm) | (a[i].z ^ tm); }
        bad = __any_sync(~0u, (m & 0x10000u) && lim < POLL_LIMIT);
      } while (bad);
      bar_arrive(BAR_M1 + warp, warp == 2 ? 352 : 288);
      if (lane == 0) { EV(6 + warp, clk() - t0); EV(9 + warp, lim); }
    }
  }
}

#define PDLAT 2
#define NPROBE 3
#define OPACE 400
constexpr int G_ST = 163840;
constexpr int B_FULL = 64, B_EMPTY = 96, B_WD = 136, B_ROLE = 144, B_PROG = 148, B_WF = 160  ;
enum { BAR_T = 1  , BAR_G = 3  , BAR_V = 5   };
DEVINL uint64_t mkdesc(uint32_t a, uint32_t lbo, uint32_t sbo, uint32_t sw) { return (uint64_t)((a & 0x3FFFF) >> 4) | ((uint64_t)(lbo >> 4) << 16) | ((uint64_t)(sbo >> 4) << 32) | ((uint64_t)sw << 62); }
DEVINL void wgmma_n128(float* d, uint64_t a, uint64_t b, int acc) {
  asm volatile("{.reg .pred p; setp.ne.b32 p, %66, 0; wgmma.mma_async.sync.aligned.m64n128k16.f32.bf16.bf16 {%0,%1,%2,%3,%4,%5,%6,%7,%8,%9,%10,%11,%12,%13,%14,%15,%16,%17,%18,%19,%20,%21,%22,%23,%24,%25,%26,%27,%28,%29,%30,%31,%32,%33,%34,%35,%36,%37,%38,%39,%40,%41,%42,%43,%44,%45,%46,%47,%48,%49,%50,%51,%52,%53,%54,%55,%56,%57,%58,%59,%60,%61,%62,%63}, %64, %65, p, 1, 1, 0, 1;}"
               : "+f"(d[0]),"+f"(d[1]),"+f"(d[2]),"+f"(d[3]),"+f"(d[4]),"+f"(d[5]),"+f"(d[6]),"+f"(d[7]),"+f"(d[8]),"+f"(d[9]),"+f"(d[10]),"+f"(d[11]),"+f"(d[12]),"+f"(d[13]),"+f"(d[14]),"+f"(d[15]),"+f"(d[16]),"+f"(d[17]),"+f"(d[18]),"+f"(d[19]),"+f"(d[20]),"+f"(d[21]),"+f"(d[22]),"+f"(d[23]),"+f"(d[24]),"+f"(d[25]),"+f"(d[26]),"+f"(d[27]),"+f"(d[28]),"+f"(d[29]),"+f"(d[30]),"+f"(d[31]),"+f"(d[32]),"+f"(d[33]),"+f"(d[34]),"+f"(d[35]),"+f"(d[36]),"+f"(d[37]),"+f"(d[38]),"+f"(d[39]),"+f"(d[40]),"+f"(d[41]),"+f"(d[42]),"+f"(d[43]),"+f"(d[44]),"+f"(d[45]),"+f"(d[46]),"+f"(d[47]),"+f"(d[48]),"+f"(d[49]),"+f"(d[50]),"+f"(d[51]),"+f"(d[52]),"+f"(d[53]),"+f"(d[54]),"+f"(d[55]),"+f"(d[56]),"+f"(d[57]),"+f"(d[58]),"+f"(d[59]),"+f"(d[60]),"+f"(d[61]),"+f"(d[62]),"+f"(d[63]) : "l"(a), "l"(b), "r"(acc));
}
DEVINL void wgmma_n80(float* d, uint64_t a, uint64_t b, int acc) {
  asm volatile("{.reg .pred p; setp.ne.b32 p, %42, 0; wgmma.mma_async.sync.aligned.m64n80k16.f32.bf16.bf16 {%0,%1,%2,%3,%4,%5,%6,%7,%8,%9,%10,%11,%12,%13,%14,%15,%16,%17,%18,%19,%20,%21,%22,%23,%24,%25,%26,%27,%28,%29,%30,%31,%32,%33,%34,%35,%36,%37,%38,%39}, %40, %41, p, 1, 1, 0, 1;}"
               : "+f"(d[0]),"+f"(d[1]),"+f"(d[2]),"+f"(d[3]),"+f"(d[4]),"+f"(d[5]),"+f"(d[6]),"+f"(d[7]),"+f"(d[8]),"+f"(d[9]),"+f"(d[10]),"+f"(d[11]),"+f"(d[12]),"+f"(d[13]),"+f"(d[14]),"+f"(d[15]),"+f"(d[16]),"+f"(d[17]),"+f"(d[18]),"+f"(d[19]),"+f"(d[20]),"+f"(d[21]),"+f"(d[22]),"+f"(d[23]),"+f"(d[24]),"+f"(d[25]),"+f"(d[26]),"+f"(d[27]),"+f"(d[28]),"+f"(d[29]),"+f"(d[30]),"+f"(d[31]),"+f"(d[32]),"+f"(d[33]),"+f"(d[34]),"+f"(d[35]),"+f"(d[36]),"+f"(d[37]),"+f"(d[38]),"+f"(d[39]) : "l"(a), "l"(b), "r"(acc));
}

template <int N, int NST, bool HAND>
DEVINL void gemm_tile(float* acc, uint32_t sb, uint32_t px, int wg, uint32_t u0, int rot, bool lead, int wph) {
  const uint64_t db = N == 128 ? mkdesc(sb, 81920, 1024, 1) : mkdesc(sb, 32768, 256, 3);
#pragma unroll
  for (int i = 0; i < N / 2; i++) acc[i] = 0.f;
  bar_sync(BAR_T + wg, 256);
#pragma unroll 1
  for (int st = 0; st < NST; st++) {
    const uint32_t u = u0 + st, slot = u & 3, ks = (st + rot >= NST ? st + rot - NST : st + rot) * 8;
    if (wph >= 0) mbar_wait(sb + S_BAR + B_WF + (N == 128 ? st * 8 : 0), wph);
    mbar_wait(sb + S_BAR + B_FULL + slot * 8, (u >> 2) & 1);
    const uint64_t da = mkdesc(sb + G_ST + slot * 16384, 16, 1024, 1);
    asm volatile("wgmma.fence.sync.aligned;" ::: "memory");
#pragma unroll
    for (int k = 0; k < 8; k++) {
      const uint64_t a = da + (k >> 2) * 512 + (k & 3) * 2;
      if (N == 128) wgmma_n128(acc, a, db + (ks + k) * 128, 1); else wgmma_n80(acc, a, db + (ks + k) * 32, 1);
    }
    asm volatile("wgmma.commit_group.sync.aligned;" ::: "memory");
    if (HAND && st == NST - 1) bar_arrive(BAR_T + (wg ^ 1), 256);
    if (st > 0) {
      asm volatile("wgmma.wait_group.sync.aligned 1;" ::: "memory");
      if (lead) { const uint32_t e = sb + S_BAR + B_EMPTY + ((u - 1) & 3) * 8; mbar_arrive(e); mbar_arrive_remote(e + px); }
    }
  }
  asm volatile("wgmma.wait_group.sync.aligned 0;" ::: "memory");
  if (lead) { const uint32_t e = sb + S_BAR + B_EMPTY + ((u0 + NST - 1) & 3) * 8; mbar_arrive(e); mbar_arrive_remote(e + px); }
}
DEVINL void wg_publish(int wg) { bar_sync(BAR_G + wg, 160); }
DEVINL uint32_t km_known(uint32_t sb) { uint32_t v; asm volatile("ld.volatile.shared.u32 %0, [%1];" : "=r"(v) : "r"(sb + S_BAR + B_PROG) : "memory"); return __reduce_min_sync(~0u, v); }
DEVINL void km_load(uint4* f, const char* p) {
#pragma unroll
  for (int G = 0; G < 4; G++) f[G] = ldg_rlx128(p + G * 512);
}
DEVINL void km_check(uint4* f, const char* p, uint32_t tg) {
  int n = 0;
  while (__any_sync(~0u, (((f[0].x ^ tg) | (f[0].z ^ tg) | (f[1].x ^ tg) | (f[1].z ^ tg) | (f[2].x ^ tg) | (f[2].z ^ tg) | (f[3].x ^ tg) | (f[3].z ^ tg)) & 0x10000u) && ++n < POLL_LIMIT)) km_load(f, p);
}
DEVINL void km_watcher(uint32_t sb, const uint32_t* p) {
  uint32_t v = 0;
#pragma unroll 1
  for (int n = 0; n < 16 * POLL_LIMIT && v < 64; n++) {
    const uint2 q = ldg_rlx64(p);
    if (min(q.x, q.y) != v) { v = min(q.x, q.y); asm volatile("st.volatile.shared.u32 [%0], %1;" ::"r"(sb + S_BAR + B_PROG), "r"(v) : "memory"); }
    __nanosleep(v < 61 ? 300 : 20);
  }
}

template <int HF>
DEVINL void attend(const float* acc, uint4 (*kf)[4], uint4* kmf, uint4* op, const char* kvp, const char* mp, bf16* orow, int lane, int wg, uint32_t sb, int tile, bool& pend, uint32_t tg) {
  constexpr int NT = HF ? 4 : 2;
  const int g = lane >> 2, t = lane & 3;
  km_check(kmf, mp + lane * 16, tg);
  float sc[NT + 1][4];
#pragma unroll
  for (int k = 0; k < 8; k++) {
    uint32_t qa[4];
#pragma unroll
    for (int i = 0; i < 4; i++) { const float* a = acc + 32 * (k >> 2) + 4 * (k & 3) + 16 * (i >> 1) + 2 * (i & 1); qa[i] = pack_bf16(a[0], a[1]); }
#pragma unroll
    for (int kt = 0; kt <= NT; kt++) {
      const uint4 b = kt < NT ? kf[kt][k >> 1] : kmf[k >> 1];
      if (k == 0) mma16816z(sc[kt], qa, b.x, b.y); else if (k & 1) mma16816(sc[kt], qa, b.z, b.w); else mma16816(sc[kt], qa, b.x, b.y);
    }
  }
  FEN();
  bar_arrive(BAR_T + (wg ^ 1), 256);
  if (pend) {
#pragma unroll
    for (int q = 0; q < 4; q++) { *(uint4*)(orow - 128 * 4096 + q * 32) = op[2 * q]; *(uint4*)(orow - 120 * 4096 + q * 32) = op[2 * q + 1]; }
    wg_publish(wg);
  }
  {
    uint32_t go; asm volatile("{.reg .pred p,q; setp.ne.u32 q, %1, 0; bar.red.and.pred p, %2, 128, q; selp.u32 %0, 1, 0, p;}" : "=r"(go) : "r"((uint32_t)(tile < 30 && km_known(sb) > tile * 2 + 5)), "r"(BAR_V + wg) : "memory");
    pend = __reduce_max_sync(~0u, go); }
  uint4 vf[HF + 1][8], vm[4];
  const char* vp = kvp + 4096 + (g >> 1) * 512 + ((g & 1) * 4 + t) * 16;
  km_load(vm, mp + 2048 + lane * 16);
#pragma unroll
  for (int i = 0; i < 8; i++) vf[0][i] = ldg_ca128(vp + (i >> 2) * 4096 + (i & 3) * 128);
  if (tile < 30) {
#pragma unroll
    for (int i = 0; i < 8; i++) kf[i >> 2][i & 3] = ldg_ca128(kvp + 4 * 32 * 16384 + ((i >> 1) & 1) * 12288 + (i >> 2) * 1024 + (i & 1) * 512 + lane * 16);
  }
  if (pend) km_load(kmf, mp + 4 * 32 * 4096 + lane * 16);
  if (HF) {
#pragma unroll
    for (int i = 0; i < 8; i++) vf[HF][i] = ldg_cg128(vp + 2048 + (i >> 2) * 4096 + (i & 3) * 128);
    if (tile < 30) {
#pragma unroll
      for (int i = 8; i < 16; i++) kf[i >> 2][i & 3] = ldg_cg128(kvp + 4 * 32 * 16384 + ((i >> 1) & 1) * 12288 + (i >> 2) * 1024 + (i & 1) * 512 + lane * 16);
    }
  }
  const float NINF = __int_as_float(0xff800000);
  if (2 * t > g) { sc[NT - 2][0] = NINF; sc[NT - 1][2] = NINF; }
  if (2 * t + 1 > g) { sc[NT - 2][1] = NINF; sc[NT - 1][3] = NINF; }
  sc[NT - 1][0] = NINF; sc[NT - 1][1] = NINF;
  float m0 = fmaxf(sc[NT][0], sc[NT][1]), m1 = fmaxf(sc[NT][2], sc[NT][3]);
#pragma unroll
  for (int kt = 0; kt < NT; kt++) { m0 = fmaxf(m0, fmaxf(sc[kt][0], sc[kt][1])); m1 = fmaxf(m1, fmaxf(sc[kt][2], sc[kt][3])); }
  m0 = fmaxf(fmaxf(m0, __shfl_xor_sync(~0u, m0, 1)), fmaxf(__shfl_xor_sync(~0u, m0, 2), __shfl_xor_sync(~0u, m0, 3)));
  m1 = fmaxf(fmaxf(m1, __shfl_xor_sync(~0u, m1, 1)), fmaxf(__shfl_xor_sync(~0u, m1, 2), __shfl_xor_sync(~0u, m1, 3)));
  m0 *= -SM_SCALE; m1 *= -SM_SCALE;
  float s0 = 0.f, s1 = 0.f; uint32_t p[NT + 1][2];
#pragma unroll
  for (int kt = 0; kt <= NT; kt++) {
    const float a = ex2(fmaf(sc[kt][0], SM_SCALE, m0)), b = ex2(fmaf(sc[kt][1], SM_SCALE, m0)), c = ex2(fmaf(sc[kt][2], SM_SCALE, m1)), d = ex2(fmaf(sc[kt][3], SM_SCALE, m1));
    s0 += a + b; s1 += c + d; p[kt][0] = pack_bf16(a, b); p[kt][1] = pack_bf16(c, d);
  }
  s0 = (s0 + __shfl_xor_sync(~0u, s0, 1)) + (__shfl_xor_sync(~0u, s0, 2) + __shfl_xor_sync(~0u, s0, 3));
  s1 = (s1 + __shfl_xor_sync(~0u, s1, 1)) + (__shfl_xor_sync(~0u, s1, 2) + __shfl_xor_sync(~0u, s1, 3));
  s0 = rcp(s0); s1 = rcp(s1);
  km_check(vm, mp + 2048 + lane * 16, tg);
#pragma unroll
  for (int grp = 0; grp < 4; grp++) {
    float o[4][4];
#pragma unroll
    for (int L = 0; L < 4; L++) {
      mma1688z(o[L], p[NT][0], p[NT][1], L == 0 ? vm[grp].x : L == 1 ? vm[grp].y : L == 2 ? vm[grp].z : vm[grp].w);
#pragma unroll
      for (int kh = 0; kh <= HF; kh++) {
        const uint4 w = vf[kh][(grp >> 1) * 4 + L]; const uint32_t A[4] = {p[2 * kh][0], p[2 * kh][1], p[2 * kh + 1][0], p[2 * kh + 1][1]};
        if (grp & 1) mma16816(o[L], A, w.z, w.w); else mma16816(o[L], A, w.x, w.y);
      }
    }
    op[2 * grp] = make_uint4(pack_bf16(o[0][0] * s0, o[0][1] * s0), pack_bf16(o[1][0] * s0, o[1][1] * s0), pack_bf16(o[2][0] * s0, o[2][1] * s0), pack_bf16(o[3][0] * s0, o[3][1] * s0));
    op[2 * grp + 1] = make_uint4(pack_bf16(o[0][2] * s1, o[0][3] * s1), pack_bf16(o[1][2] * s1, o[1][3] * s1), pack_bf16(o[2][2] * s1, o[2][3] * s1), pack_bf16(o[3][2] * s1, o[3][3] * s1));
  }
}

DEVINL void gemm_consumer(uint32_t sb, uint32_t px, int wg, int pr, int rank, const ArgsA& args) {
  const int lane = opaque(threadIdx.x & 31), w = __reduce_max_sync(~0u, (threadIdx.x >> 5) & 3);
  const bool lead = lane == 0 && w == 0;
  const int rot5 = pr % 5;
  if (wg == 1) bar_arrive(BAR_T, 256);
  if (threadIdx.x == 0) LOG(64 + pr * 2 + rank, 250);
#pragma unroll 1
  for (int tile = wg; tile < 32; tile += 2) {
    float acc[64];
    gemm_tile<128, 5, true>(acc, sb, px, wg, tile * 5, rot5, lead, tile < 2 ? 0 : -1);
    if (tile >= 30 && lead) mbar_arrive(sb + S_BAR + B_WD);
    char* dst = g_kv + (size_t)((tile * 2 + (w >> 1)) * 32 + pr) * 16384 + (w & 1) * 2048 + lane * 16;
    if (rank == 0) {
#pragma unroll
      for (int G = 0; G < 4; G++)
#pragma unroll
        for (int hh = 0; hh < 2; hh++) {
          const float* a = acc + 32 * (G >> 1) + 8 * (G & 1) + 2 * hh;
          *(uint4*)(dst + (G >> 1) * 12288 + hh * 1024 + (G & 1) * 512) = make_uint4(pack_bf16(a[0], a[1]), pack_bf16(a[16], a[17]), pack_bf16(a[4], a[5]), pack_bf16(a[20], a[21]));
        }
    } else {
#pragma unroll
      for (int i = 0; i < 8; i++) {
        const float* a = acc + (i >> 2) * 32 + (i & 3) * 4;
        *(uint4*)(dst + 4096 + (i >> 2) * 4096 + (i & 3) * 512) = make_uint4(movm(pack_bf16(a[0], a[1])), movm(pack_bf16(a[2], a[3])), movm(pack_bf16(a[16], a[17])), movm(pack_bf16(a[18], a[19])));
      }
    }
    wg_publish(wg);
    if ((threadIdx.x & 127) == 0) LOG(64 + pr * 2 + rank, tile);
  }
  if (threadIdx.x == 0) LOG(64 + pr * 2 + rank, 251);
  if (pr < 16) {
    const int h = 2 * pr + rank;
    flag_wait_warp(args.flags + F_KV + (16 + (lane & 1)) * 32 + h, 2);
    bool pend = false; uint4 op[8], kf[4][4], kmf[4];
#pragma unroll
    for (int i = 0; i < 16; i++) kf[i >> 2][i & 3] = ldg_cg128(g_kv + (size_t)((wg * 2 + (w >> 1)) * 32 + h) * 16384 + ((i >> 1) & 1) * 12288 + (i >> 2) * 1024 + (i & 1) * 512 + lane * 16);
#pragma unroll
    for (int i = 0; i < 8; i++) op[i] = kmf[i & 3] = make_uint4(0, 0, 0, 0);
#pragma unroll 1
    for (int tile = wg; tile < 32; tile += 2) {
      const uint32_t seg = tile * 2 + (w >> 1);
      const char* kvp = g_kv + (size_t)(seg * 32 + h) * 16384;
      const char* mp = g_kvm + (size_t)(seg * 32 + h) * 4096;
      bf16* orow = g_o + (size_t)(tile * 64 + w * 16 + (lane >> 2)) * 4096 + h * 128 + (lane & 3) * 8;
      if ((tile >> 1) == 6) flag_wait_warp(args.flags + F_KV + (30 + (lane & 1)) * 32 + h, 2);
      float acc[64];
      gemm_tile<128, 5, false>(acc, sb, px, wg, 160 + tile * 5, rot5, lead, tile < 2 ? 1 : -1);
      if ((threadIdx.x & 127) == 96) LOG(64 + pr * 2 + rank, 64 + tile);
      if (!pend) {
        int n = 0;
        while (km_known(sb) <= seg && ++n < 16 * POLL_LIMIT) {}
        km_load(kmf, mp + lane * 16);
      }
      if ((threadIdx.x & 127) == 96) LOG(64 + pr * 2 + rank, 96 + tile);
      if (w & 1) attend<1>(acc, kf, kmf, op, kvp, mp, orow, lane, wg, sb, tile, pend, (args.layer ^ 1) << 16); else attend<0>(acc, kf, kmf, op, kvp, mp, orow, lane, wg, sb, tile, pend, (args.layer ^ 1) << 16);
      if (!pend) {
#pragma unroll
        for (int q = 0; q < 4; q++) { *(uint4*)(orow + q * 32) = op[2 * q]; *(uint4*)(orow + 8 * 4096 + q * 32) = op[2 * q + 1]; }
        wg_publish(wg);
      }
      if ((threadIdx.x & 127) == 0) LOG(64 + pr * 2 + rank, 32 + tile);
    }
  } else {
    const int kq = (pr - 16) >> 2, cg = 2 * (pr & 3) + rank;
#pragma unroll 1
    for (int tile = wg; tile < 32; tile += 2) {
      float acc[40];
      gemm_tile<80, 8, true>(acc, sb, px, wg, 160 + tile * 8, (pr & 3) * 2, lead, tile < 2 ? 1 : -1);
      const bool odd = lane & 1;
      bf16* dst = g_part + (size_t)(kq * 2048 + tile * 64 + w * 16 + (lane >> 2)) * 640 + cg * 80 + (lane & 1) * 8 + (lane & 2) * 2;
#pragma unroll
      for (int q = 0; q < 5; q++)
#pragma unroll
        for (int hh = 0; hh < 2; hh++) {
          const uint32_t A = pack_bf16(acc[8 * q + 2 * hh], acc[8 * q + 2 * hh + 1]), B = pack_bf16(acc[8 * q + 4 + 2 * hh], acc[8 * q + 5 + 2 * hh]);
          const uint32_t x = __shfl_xor_sync(~0u, odd ? A : B, 1);
          *(uint2*)(dst + hh * 8 * 640 + q * 16) = odd ? make_uint2(x, B) : make_uint2(A, x);
        }
      wg_publish(wg);
      if ((threadIdx.x & 127) == 0) LOG(64 + pr * 2 + rank, 32 + tile);
    }
  }
  if (wg == 0) bar_sync(BAR_T, 256);
}

DEVINL void gemm_producer(uint32_t sb, int pr, int rank, const ArgsA& args, const CUtensorMap* tq, const CUtensorMap* tk, const CUtensorMap* tv,
                          const CUtensorMap* to32, const CUtensorMap* tx, const CUtensorMap* tao) {
  const uint32_t bWF = sb + S_BAR + B_WF;
  auto load_w = [&](const CUtensorMap* tm, int col, int st) {
    const int r = ((st + pr) % 5) * 2; mbar_arrive_tx(bWF + st * 8, 32768);
#pragma unroll 1
    for (int i = 0; i < 4; i++) tma_2d(sb + (i & 1) * 81920 + (r + (i >> 1)) * 8192, tm, col + (i & 1) * 64, (r + (i >> 1)) * 64, bWF + st * 8); };
  uint32_t u = 0;
  auto push = [&](const CUtensorMap* tm, int c0, int c1) {
    const uint32_t slot = u & 3, full = sb + S_BAR + B_FULL + slot * 8;
    mbar_wait(sb + S_BAR + B_EMPTY + slot * 8, ((u >> 2) & 1) ^ 1);
    mbar_arrive_tx(full, 16384);
    tma_2d_mc(sb + G_ST + slot * 16384 + rank * 8192, tm, c0 + rank * 64, c1, full);
    u++; };
#pragma unroll 1
  for (int st = 0; st < 5; st++) load_w(rank ? tv : tk, pr * 128, st);
  if (args.layer == 0) { flag_wait(args.flags + F_X, 128); fence_proxy_async(); } else pdl_wait();
#pragma unroll 1
  for (int tile = 0; tile < 32; tile++) {
    l2_prefetch((const char*)g_xn + ((tile + 2) & 31) * 81920 + (pr * 2 + rank) * 1280, 1280);
    if (tile >= 20 && tile < 30) l2_prefetch((rank ? args.wo : args.wq) + (pr * 10 + tile - 20) * 16384, 16384);
#pragma unroll 1
    for (int st = 0; st < 5; st++) push(tx, ((st + pr) % 5) * 128, tile * 64);
  }
  pdl_launch();
  if (pr < 16) {
    load_w(tq, (2 * pr + rank) * 128, 0);
#pragma unroll 1
    for (int tile = 0; tile < 32; tile++) {
      if (tile < 30) {
        l2_prefetch((const char*)g_xn + (tile + 2) * 81920 + (pr * 2 + rank) * 2560, 2560);
        const int q = (tile * 2 + 4) * 32 + 2 * pr + rank;
        l2_prefetch(g_kv + (size_t)q * 16384, 16384); l2_prefetch(g_kv + (size_t)(q + 32) * 16384, 16384);
        if (lds32(sb + S_BAR + B_PROG) > tile * 2 + 5) { l2_prefetch(g_kvm + (size_t)q * 4096, 4096); l2_prefetch(g_kvm + (size_t)(q + 32) * 4096, 4096); }
      }
#pragma unroll 1
      for (int st = 0; st < 5; st++) { push(tx, ((st + pr) % 5) * 128, tile * 64); if (tile == 0 && st < 4) load_w(tq, (2 * pr + rank) * 128, st + 1); }
    }
  } else {
    const int kq = (pr - 16) >> 2, cg = 2 * (pr & 3) + rank;
    mbar_wait(sb + S_BAR + B_WD, 0);
    mbar_arrive_tx(bWF, 163840);
#pragma unroll 1
    for (int i = 0; i < 20; i++) { tma_2d(sb + (i % 5) * 32768 + (i / 5) * 8192, to32, cg * 80 + (i % 5) * 16, kq * 1024 + (i / 5) * 256, bWF); __nanosleep(OPACE); }
#pragma unroll 1
    for (int tile = 0; tile < 32; tile++) {
      flag_wait(args.flags + F_O + tile * 4 + kq, 8);
      fence_proxy_async();
#pragma unroll 1
      for (int st = 0; st < 8; st++) push(tao, kq * 1024 + ((st + (pr & 3) * 2) & 7) * 128, tile * 64);
    }
  }
#pragma unroll 1
  for (int i = 0; i < 4; i++, u++) mbar_wait(sb + S_BAR + B_EMPTY + (u & 3) * 8, ((u >> 2) & 1) ^ 1);
}

DEVINL void gemm_publisher(int wg, int pr, int rank, const ArgsA& args) {
#pragma unroll 1
  for (int i = 0; i < 32; i++) {
    const int tile = (i & 15) * 2 + wg;
    bar_sync(BAR_G + wg, 160);
    if ((threadIdx.x & 31) == 0) {
      flag_add(args.flags + (i < 16 ? F_KV + tile * 32 + pr : pr < 16 ? F_O + tile * 4 + (pr >> 2) : F_P + tile * 32));
    }
    __syncwarp();
  }
}

DEVINL void filter_prep(uint32_t* sm, int part, const ArgsA& args) {
  const int tid = threadIdx.x, lane = tid & 31, w = tid >> 5;
  const unsigned short* wr = (const unsigned short*)args.wr; const unsigned short* wi = (const unsigned short*)args.wi;
#pragma unroll 1
  for (int it = part; it < 32; it += 4) {
#pragma unroll 1
    for (int rr = 0; rr < 8; rr += 2) {
      uint32_t a[2][11], b[2][11];
#pragma unroll
      for (int r = 0; r < 2; r++) {
        const int pos = it * 64 + w * 8 + rr + r, th = (pos >> 2) & 127, v = (pos >> 9) * 4 + (pos & 3);
        const int o = ((th >> 3) + 16 * ((th & 7) + (v & 8)) + 256 * (v & 7)) * 321 + lane;
#pragma unroll
        for (int c = 0; c < 11; c++) if (c < 10 || lane == 0) { a[r][c] = wr[o + c * 32]; b[r][c] = wi[o + c * 32]; }
      }
#pragma unroll
      for (int r = 0; r < 2; r++)
#pragma unroll
        for (int c = 0; c < 11; c++) if (c < 10 || lane == 0) sm[(c * 32 + lane) * 65 + w * 8 + rr + r] = a[r][c] | (b[r][c] << 16);
    }
    bar_sync(1, 256);
#pragma unroll 2
    for (int i = tid; i < 64 * 321; i += 256) g_wt[(i >> 6) * 2048 + it * 64 + (i & 63)] = sm[(i >> 6) * 65 + (i & 63)];
    bar_sync(1, 256);
  }
}

__global__ void __cluster_dims__(2, 1, 1) __launch_bounds__(384, 1)
layer_a_kernel(const __grid_constant__ CUtensorMap tq, const __grid_constant__ CUtensorMap tk, const __grid_constant__ CUtensorMap tv,
               const __grid_constant__ CUtensorMap to, const __grid_constant__ CUtensorMap to32, const __grid_constant__ CUtensorMap tx,
               const __grid_constant__ CUtensorMap tao, const __grid_constant__ ArgsA args) {
  extern __shared__ __align__(1024) char smraw[];
  const uint32_t sb = (smem_u32(smraw) + 1023) & ~1023u;
  uint32_t rank; asm volatile("mov.u32 %0, %%cluster_ctarank;" : "=r"(rank));
  rank = __reduce_max_sync(~0u, rank);
  const uint32_t px = __reduce_max_sync(~0u, mapa(sb, rank ^ 1) - sb);
  if (PDLAT == 0) pdl_launch();
  if (args.layer == 0) LOGK(0, 0);
  uint32_t smid; asm volatile("mov.u32 %0, %%smid;" : "=r"(smid));
  if (threadIdx.x >= 256) {
    const uint32_t b = sb + S_BAR;
    if (threadIdx.x == 320) {
      mbar_init(b + B_W, 1); mbar_init(b + B_W2, 1); mbar_init(b + B_WV, 1); mbar_init(b + B_WO, 1); mbar_init(b + B_S, 9); mbar_init(b + B_KV, 1); mbar_init(b + B_KV + 8, 1);
      for (int i = 0; i < 4; i++) { mbar_init(b + B_FULL + i * 8, 1); mbar_init(b + B_EMPTY + i * 8, 2); }
      for (int i = 0; i < 5; i++) mbar_init(b + B_WF + i * 8, 1);
      mbar_init(b + B_WD, 2); sts32(b + B_PROG, 0);
      asm volatile("fence.mbarrier_init.release.cluster;" ::: "memory");
    }
    if (rank == 0 && threadIdx.x < 320) {
      if (args.layer == 0) {
        uint32_t* p = (uint32_t*)(args.comm + 0x20000 + (threadIdx.x < 288 ? 0x1000 : 0) + (blockIdx.x >> 1) * 32);
        if ((threadIdx.x & 31) < 8) p[threadIdx.x & 31] = 0;
        __syncwarp();
        if ((threadIdx.x & 31) == 0) {
          uint32_t v, best = ~0u;
#pragma unroll 1
          for (int i = 0; i < NPROBE; i++) { const uint32_t t0 = clk(); asm volatile("atom.relaxed.gpu.global.add.u32 %0, [%1], 1;" : "=r"(v) : "l"(p) : "memory"); asm volatile("st.volatile.shared.u32 [%0], %1;" ::"r"(b + 208), "r"(v) : "memory"); best = min(best, clk() - t0); }
          sts32(b + 200 + ((threadIdx.x >> 5) & 1) * 4, best);
        }
        bar_sync(1, 64);
      }
      if (threadIdx.x == 256) {
        int d;
        if (args.layer == 0) { d = (int)(lds32(b + 200) - lds32(b + 204)); g_side[smid & 254] = d; g_side[(smid & 254) + 1] = d; } else d = g_side[smid & 255];
        uint32_t* cnt = args.flags + F_ROLE; uint32_t role;
        if (d < 0) { role = atomicAdd(cnt, 1); if (role >= 32) role = 32 + atomicAdd(cnt + 1, 1); }
        else { role = 32 + atomicAdd(cnt + 1, 1); if (role >= 66) role = atomicAdd(cnt, 1); }
        sts32(b + B_ROLE, role);
      }
    }
  } else if (args.layer == 0 && blockIdx.x < 128) {
    const size_t off = (size_t)(blockIdx.x * 16 + (threadIdx.x >> 4)) * 640 + (threadIdx.x & 15) * 8;
    float f[40];
#pragma unroll
    for (int i = 0; i < 5; i++) unpack8(*(const uint4*)(args.x + off + i * 128), f + 8 * i);
    ln_row(f);
#pragma unroll
    for (int i = 0; i < 5; i++) *(uint4*)(g_xn + off + i * 128) = pack8(f + 8 * i);
  }
  __syncthreads();
  asm volatile("barrier.cluster.arrive.release.aligned;" ::: "memory");
  if (threadIdx.x == 0 && args.layer == 0 && blockIdx.x < 128) flag_add(args.flags + F_X);
  __syncwarp();
  asm volatile("barrier.cluster.wait.acquire.aligned;" ::: "memory");
  uint32_t role; asm volatile("ld.shared::cluster.u32 %0, [%1];" : "=r"(role) : "r"(sb + S_BAR + B_ROLE + (rank ? px : 0)) : "memory");
  role = __reduce_max_sync(~0u, role);
  if (PDLAT == 1 || (PDLAT == 2 && role != 32)) pdl_launch();
  if (role >= 64) cluster_sync();
  const int wg = __reduce_max_sync(~0u, threadIdx.x >> 7);
  auto U = [](uint32_t x) { return __reduce_max_sync(~0u, opaque(x)); };
  if (wg < 2) {
    asm volatile("setmaxnreg.inc.sync.aligned.u32 224;");
    if (role >= 32) {
      if (role >= 64) { if (args.layer == 0) { filter_prep((uint32_t*)smraw, (role - 64) * 2 + rank, args); if (threadIdx.x == 0) LOG(role * 2 + rank, 0); } }
      else gemm_consumer(U(sb), U(px), U(wg), U(role - 32), U(rank), args);
    } else { if (wg == 0) chain_mma<0>(sb, args); else chain_mma<1>(sb, args); }
  } else {
    asm volatile("setmaxnreg.dec.sync.aligned.u32 56;");
    if (role >= 32) {
      if (role < 64) {
        if (threadIdx.x == 256) gemm_producer(sb, role - 32, rank, args, &tq, &tk, &tv, &to32, &tx, &tao);
        else if (threadIdx.x >= 288 && threadIdx.x < 352) gemm_publisher((threadIdx.x >> 5) - 9, role - 32, rank, args);
        else if (threadIdx.x == 352 && role < 48) km_watcher(sb, args.flags + F_KM + (2 * (role - 32) + rank) * 32);
      }
    } else chain_helper(U(sb), U(px), U(role), U(rank), args, &tq, &tk, &tv, &to);
  }
}

DEVINL float2 cadd(float2 a, float2 b) { return make_float2(a.x + b.x, a.y + b.y); }
DEVINL float2 csub(float2 a, float2 b) { return make_float2(a.x - b.x, a.y - b.y); }
DEVINL float2 cmul(float2 a, float2 b) { return make_float2(fmaf(a.x, b.x, -a.y * b.y), fmaf(a.x, b.y, a.y * b.x)); }
DEVINL float2 cmulc(float2 a, float2 b) { return make_float2(fmaf(a.x, b.x, a.y * b.y), fmaf(a.y, b.x, -a.x * b.y)); }
template <int INV> DEVINL float2 ctw(float2 a, float2 w) { return INV ? cmulc(a, w) : cmul(a, w); }
template <int INV> DEVINL float2 rot(float2 a) { return INV ? make_float2(-a.y, a.x) : make_float2(a.y, -a.x); }
template <int INV> DEVINL void fft4(float2& a, float2& b, float2& c, float2& d) {
  const float2 s0 = cadd(a, c), d0 = csub(a, c), s1 = cadd(b, d), d1 = rot<INV>(csub(b, d));
  a = cadd(s0, s1); b = cadd(d0, d1); c = csub(s0, s1); d = csub(d0, d1);
}
template <int INV> DEVINL float2 w8(float2 a) { const float h = 0.70710678118654752f; const float2 r = rot<INV>(a); return make_float2((a.x + r.x) * h, (a.y + r.y) * h); }
template <int INV> DEVINL void fft8(float2* x) {
  fft4<INV>(x[0], x[2], x[4], x[6]); fft4<INV>(x[1], x[3], x[5], x[7]);
  const float2 e0 = x[0], e1 = x[2], e2 = x[4], e3 = x[6], o0 = x[1], o1 = w8<INV>(x[3]), o2 = rot<INV>(x[5]), o3 = rot<INV>(w8<INV>(x[7]));
  x[0] = cadd(e0, o0); x[1] = cadd(e1, o1); x[2] = cadd(e2, o2); x[3] = cadd(e3, o3);
  x[4] = csub(e0, o0); x[5] = csub(e1, o1); x[6] = csub(e2, o2); x[7] = csub(e3, o3);
}
template <int INV> DEVINL void fft16(float2* x) {
  const float c = 0.92387953251128674f, s = 0.38268343236508977f;
  const float2 w1 = make_float2(c, -s), w3 = make_float2(s, -c);
#pragma unroll
  for (int i = 0; i < 4; i++) fft4<INV>(x[i], x[i + 4], x[i + 8], x[i + 12]);
  x[5] = ctw<INV>(x[5], w1); x[9] = w8<INV>(x[9]); x[13] = ctw<INV>(x[13], w3);
  x[6] = w8<INV>(x[6]); x[10] = rot<INV>(x[10]); x[14] = rot<INV>(w8<INV>(x[14]));
  x[7] = ctw<INV>(x[7], w3); x[11] = rot<INV>(w8<INV>(x[11])); x[15] = ctw<INV>(x[15], make_float2(-c, s));
#pragma unroll
  for (int k = 0; k < 4; k++) fft4<INV>(x[4 * k], x[4 * k + 1], x[4 * k + 2], x[4 * k + 3]);
#pragma unroll
  for (int k = 0; k < 4; k++)
#pragma unroll
    for (int m = k + 1; m < 4; m++) { const float2 t = x[4 * k + m]; x[4 * k + m] = x[4 * m + k]; x[4 * m + k] = t; }
}
template <int INV> DEVINL void fft5(float2& x0, float2& x1, float2& x2, float2& x3, float2& x4) {
  const float c1 = 0.30901699437494742f, c2 = -0.80901699437494742f, s1 = 0.95105651629515357f, s2 = 0.58778525229247313f;
  const float2 a1 = cadd(x1, x4), a2 = cadd(x2, x3), b1 = rot<INV>(csub(x1, x4)), b2 = rot<INV>(csub(x2, x3));
  const float2 p1 = make_float2(fmaf(c1, a1.x, fmaf(c2, a2.x, x0.x)), fmaf(c1, a1.y, fmaf(c2, a2.y, x0.y)));
  const float2 p2 = make_float2(fmaf(c2, a1.x, fmaf(c1, a2.x, x0.x)), fmaf(c2, a1.y, fmaf(c1, a2.y, x0.y)));
  const float2 q1 = make_float2(fmaf(s1, b1.x, s2 * b2.x), fmaf(s1, b1.y, s2 * b2.y));
  const float2 q2 = make_float2(fmaf(s2, b1.x, -s1 * b2.x), fmaf(s2, b1.y, -s1 * b2.y));
  x0 = cadd(x0, cadd(a1, a2)); x1 = cadd(p1, q1); x4 = csub(p1, q1); x2 = cadd(p2, q2); x3 = csub(p2, q2);
}
template <int INV> DEVINL void fft20(const float2* in, float2* out) {
  float2 t[4][5];
#pragma unroll
  for (int a = 0; a < 4; a++) {
#pragma unroll
    for (int b = 0; b < 5; b++) t[a][b] = in[(5 * a + 4 * b) % 20];
    fft5<INV>(t[a][0], t[a][1], t[a][2], t[a][3], t[a][4]);
  }
#pragma unroll
  for (int d = 0; d < 5; d++) {
    fft4<INV>(t[0][d], t[1][d], t[2][d], t[3][d]);
#pragma unroll
    for (int c = 0; c < 4; c++) out[(5 * c + 16 * d) % 20] = t[c][d];
  }
}
constexpr int ZP = 336;
struct RowSmem { float2 T[320 * 17]; uint32_t Z[16 * ZP]; float2 tw[320]; float2 tp[160]; };
DEVINL float2 cis(int k, int n) {
  float sn, cs; __sincosf((float)(2 * k > n ? k - n : k) * (-6.283185307179586f / (float)n), &sn, &cs); return make_float2(cs, sn);
}
DEVINL void row_tables(RowSmem& sm) {
  const int t = threadIdx.x;
  sm.tw[t] = cis((t >> 4) * (t & 15), 320);
  if (t < 160) sm.tp[t] = cis(t, 640);
}

#define CUNR 1
#define CDRY 0
#define RDRY 1

__global__ void __launch_bounds__(320, 1) rows_fwd_kernel(const bf16* __restrict__ xin, const uint32_t* flags) {
  extern __shared__ __align__(1024) char smraw[]; RowSmem& sm = *(RowSmem*)smraw;
  const int tid = threadIdx.x, s0 = blockIdx.x * 16, wp = __reduce_max_sync(~0u, tid >> 5);
  const uint32_t* flag = flags + F_P + (blockIdx.x >> 2) * 32;
  LOGK(1 + 3 * (xin == g_x), 0);
  if (tid == 0) l2_prefetch(xin + s0 * 640, 20480);
  row_tables(sm);
#pragma unroll 1
  for (int live = !RDRY || wp != 1 || __any_sync(~0u, ldg_rlx32(flag) >= 32); live < 2; live++) {
    if (live) {
      if (wp == 0) { uint32_t v; int n = 0;
        while (true) { asm volatile("ld.acquire.gpu.global.u32 %0, [%1];" : "=r"(v) : "l"(flag) : "memory"); if (__all_sync(~0u, v >= 32 || ++n >= 8 * POLL_LIMIT)) break; __nanosleep(v ? 20 : 200); } }
      __syncthreads();
      pdl_launch();
      LOGK(1 + 3 * (xin == g_x), 1);
    }
    if (wp < 8) {
      const int row = tid >> 4, j = tid & 15; const size_t off = (size_t)(s0 + row) * 640 + j * 8;
      float f[40]; uint4 in[5][5];
#pragma unroll
      for (int i = 0; i < 5; i++) {
#pragma unroll
        for (int q = 0; q < 4; q++) in[i][q] = ldg128_if(g_part + q * 2048 * 640 + off + i * 128, live);
        in[i][4] = ldg128_if(xin + off + i * 128, live);
      }
#pragma unroll
      for (int i = 0; i < 5; i++) {
        float a[8], b[8], c[8], d[8];
        unpack8(in[i][0], a); unpack8(in[i][1], b); unpack8(in[i][2], c); unpack8(in[i][3], d);
#pragma unroll
        for (int e = 0; e < 8; e++) a[e] = (a[e] + b[e]) + (c[e] + d[e]);
        const uint4 o = pack8(a), x = in[i][4];
        const uint4 r = make_uint4(hadd2bf(o.x, x.x), hadd2bf(o.y, x.y), hadd2bf(o.z, x.z), hadd2bf(o.w, x.w));
        stg128_if(g_x + off + i * 128, r, live); unpack8(r, f + 8 * i);
      }
      ln_row(f);
#pragma unroll
      for (int i = 0; i < 5; i++) *(uint4*)(sm.Z + row * ZP + i * 64 + j * 4) = pack8(f + 8 * i);
      __syncwarp();
      float2 z[20], y[20];
#pragma unroll
      for (int n1 = 0; n1 < 20; n1++) { const uint32_t w = sm.Z[row * ZP + n1 * 16 + j]; z[n1] = make_float2(bf_lo(w), bf_hi(w)); }
      fft20<0>(z, y);
#pragma unroll
      for (int k1 = 0; k1 < 20; k1++) sm.T[(k1 * 16 + j) * 17 + row] = k1 ? cmul(y[k1], sm.tw[k1 * 16 + j]) : y[0];
    }
    if (live) __syncthreads();
    const int up = (tid >> 4) & 1, row = tid & 15, k1 = wp ? (up ? 20 - wp : wp) : up * 10;
    float2 x[16];
#pragma unroll
    for (int n2 = 0; n2 < 16; n2++) x[n2] = sm.T[(k1 * 16 + n2) * 17 + row];
    fft16<0>(x);
    uint32_t* ya = g_y + s0 + row + k1 * 2048; uint32_t* yb = g_y + s0 + row + (320 - k1) * 2048;
    stg32_if(g_y + s0 + row + 160 * 2048, pack_f16(2.f * x[8].x, -2.f * x[8].y), live && k1 == 0);
    const int src = (tid & 31) ^ (wp ? 16 : 0);
#pragma unroll
    for (int k2 = 0; k2 < 8; k2++) {
      const float2 c = k1 ? x[15 - k2] : x[(16 - k2) & 15], b = make_float2(__shfl_sync(~0u, c.x, src), __shfl_sync(~0u, c.y, src)), a = x[k2];
      const float2 E = make_float2(a.x + b.x, a.y - b.y), O = cmul(make_float2(a.y + b.y, b.x - a.x), sm.tp[k1 + 20 * k2]);
      stg32_if(ya + k2 * 20 * 2048, pack_f16(E.x + O.x, E.y + O.y), live); stg32_if(yb - k2 * 20 * 2048, pack_f16(E.x - O.x, O.y - E.y), live);
    }
  }
  LOGK(1 + 3 * (xin == g_x), 2);
  if (blockIdx.x == gridDim.x - 1) pdl_wait();
}

__global__ void __launch_bounds__(384) cols_kernel(int layer) {
  extern __shared__ __align__(1024) char smraw[];
  const int sub = threadIdx.x >> 7, tid = threadIdx.x & 127, col = blockIdx.x * 3 + sub, k1 = tid >> 3, j0 = tid & 7;
  float2* sm = (float2*)smraw + sub * (16 * 152);
  float2* tw = (float2*)smraw + 3 * 16 * 152;
  LOGK(2 + 3 * layer, 0);
  pdl_launch();
  uint32_t* y = g_y + col * 2048 + tid;
  if (tid < 2) l2_prefetch((tid ? g_wt : g_y) + col * 2048, 8192);
#pragma unroll 1
  for (int i = threadIdx.x; i < 2176; i += 384) {
    const int a = i < 2048 ? i >> 7 : (i - 2048) >> 3, b = i < 2048 ? i & 127 : i & 7;
    tw[i < 2048 ? a * 136 + b : 2176 + a * 9 + b] = cis(i < 2048 ? a * b : a * b * 16, 2048);
  }
  float2* reg = sm + k1 * 152;
  uint4 wf[4];
#pragma unroll
  for (int q = 0; q < 4; q++) {
    const int live = q >= 0, it = live ? q : q == -3 ? 0 : q == -2 ? 1 : 3;
    float2 x[16];
    if (it == 0) {
      if (live) { __syncthreads(); pdl_wait(); LOGK(2 + 3 * layer, 1); }
#pragma unroll
      for (int i = 0; i < 16; i++) { const uint32_t w = ldg32_if(y + i * 128, live); x[i] = __half22float2(*(const __half2*)&w); }
#pragma unroll
      for (int i = 0; i < 4; i++) wf[i] = ldg128_if(g_wt + col * 2048 + i * 512 + tid * 4, live);
    } else {
      const float2* in = it == 3 ? sm + tid : reg + j0; const int is = it == 1 ? 8 : it == 2 ? 9 : 152;
#pragma unroll
      for (int i = 0; i < 16; i++) x[i] = in[i * is];
    }
    fft16<0>(x);
    if (it == 3) {
      const float sc = 1.f / 4096.f;
#pragma unroll
      for (int i = 0; i < 16; i++) stg32_if(y + i * 128, pack_bf16(x[i].y * sc, x[i].x * sc), live);
    } else {
      const float2* t = it == 0 ? tw + tid : it == 1 ? tw + 2176 + j0 : tw + k1 * 136 + j0; const int ts = it == 0 ? 136 : it == 1 ? 9 : 8;
      float2* o = it == 0 ? sm + tid : reg + j0; const int os = it == 0 ? 152 : it == 1 ? 9 : 8;
      __syncwarp();
#pragma unroll
      for (int k = 0; k < 16; k++) o[k * os] = (CUNR && k == 0 && it < 2) ? x[0] : cmul(x[k], t[k * ts]);
      if (it == 1) {
        __syncwarp();
        float2* r9 = reg + j0 * 9;
#pragma unroll
        for (int i = 0; i < 16; i++) x[i] = r9[(i & 8) * 9 + (i & 7)];
#pragma unroll
        for (int h = 0; h < 2; h++) {
          fft8<0>(x); fft8<0>(x + 8);
          if (h == 0) {
#pragma unroll
            for (int i = 0; i < 16; i++) {
              const uint32_t w = (i & 3) == 0 ? wf[i >> 2].x : (i & 3) == 1 ? wf[i >> 2].y : (i & 3) == 2 ? wf[i >> 2].z : wf[i >> 2].w;
              const float2 v = cmul(x[i], make_float2(bf_lo(w), bf_hi(w))); x[i] = make_float2(v.y, v.x);
            }
          }
        }
        const float2* t9 = tw + 2176 + j0 * 9;
#pragma unroll
        for (int i = 0; i < 16; i++) r9[(i & 8) * 9 + (i & 7)] = (i & 7) ? cmul(x[i], t9[(i & 8) * 9 + (i & 7)]) : x[i];
        __syncwarp();
      } else if (live) bar_sync(sub + 1, 128);
    }
  }
  LOGK(2 + 3 * layer, 2);
}

__global__ void __launch_bounds__(320) rows_inv_kernel(bf16* __restrict__ xout, int do_ln) {
  extern __shared__ __align__(1024) char smraw[]; RowSmem& sm = *(RowSmem*)smraw;
  const int tid = threadIdx.x, s0 = blockIdx.x * 16, wp = __reduce_max_sync(~0u, tid >> 5);
  LOGK(3 + 3 * !do_ln, 0);
  if (tid == 0) l2_prefetch(g_x + s0 * 640, 20480);
  row_tables(sm);
  const size_t off = (size_t)(s0 + ((tid >> 4) & 15)) * 640 + (tid & 15) * 8;
#pragma unroll 1
  for (int live = !RDRY || wp != 1; live < 2; live++) {
    if (live) {
      __syncthreads();
      pdl_wait();
      pdl_launch();
      LOGK(3 + 3 * !do_ln, 1);
    }
    uint4 xr[5];
    {
      const int up = (tid >> 4) & 1, row = tid & 15, k1 = wp ? (up ? 20 - wp : wp) : up * 10;
      const uint32_t* ya = g_y + s0 + row + k1 * 2048; const uint32_t* yb = g_y + s0 + row + (320 - k1) * 2048;
      uint32_t wa[8], wb[8];
#pragma unroll
      for (int k2 = 0; k2 < 8; k2++) { wa[k2] = ldg32_if(ya + k2 * 20 * 2048, live); wb[k2] = ldg32_if(yb - k2 * 20 * 2048, live); }
      const uint32_t wm = ldg32_if(g_y + s0 + row + 160 * 2048, live && k1 == 0);
#pragma unroll
      for (int i = 0; i < 5; i++) xr[i] = ldg128_if(g_x + off + i * 128, live && wp < 8);
      stg32_if(g_flags + blockIdx.x * 320 + tid, 0, live && !do_ln && blockIdx.x * 320 + tid < 2 * F_LAYER);
      if (k1 == 0) { wa[0] &= 0xffffu; wb[0] &= 0xffffu; }
      float2 x[16], r[8];
#pragma unroll
      for (int k2 = 0; k2 < 8; k2++) {
        const float2 a = make_float2(bf_lo(wa[k2]), bf_hi(wa[k2])), b = make_float2(bf_lo(wb[k2]), bf_hi(wb[k2]));
        const float2 E = make_float2(a.x + b.x, a.y - b.y), O = cmulc(make_float2(a.x - b.x, a.y + b.y), sm.tp[k1 + 20 * k2]);
        x[k2] = make_float2(E.x - O.y, E.y + O.x); r[k2] = make_float2(E.x + O.y, O.x - E.y);
      }
      if (k1 == 0) r[0] = make_float2(2.f * bf_lo(wm), -2.f * bf_hi(wm));
      const int src = (tid & 31) ^ (wp ? 16 : 0);
#pragma unroll
      for (int i = 8; i < 16; i++) { const float2 c = k1 ? r[15 - i] : r[(16 - i) & 7]; x[i] = make_float2(__shfl_sync(~0u, c.x, src), __shfl_sync(~0u, c.y, src)); }
      fft16<1>(x);
#pragma unroll
      for (int n2 = 0; n2 < 16; n2++) sm.T[(k1 * 16 + n2) * 17 + row] = x[n2];
    }
    if (live) __syncthreads();
    if (wp < 8) {
      const int row = tid >> 4, n2 = tid & 15;
      float2 z[20], y[20];
#pragma unroll
      for (int k1 = 0; k1 < 20; k1++) { const float2 t = sm.T[(k1 * 16 + n2) * 17 + row]; z[k1] = k1 ? cmulc(t, sm.tw[k1 * 16 + n2]) : t; }
      fft20<1>(z, y);
      const float sc = 1.f / 640.f;
#pragma unroll
      for (int n1 = 0; n1 < 20; n1++) sm.Z[row * ZP + n1 * 16 + n2] = pack_bf16(y[n1].x * sc, y[n1].y * sc);
      __syncwarp();
      float f[40];
#pragma unroll
      for (int i = 0; i < 5; i++) {
        const uint4 o = *(const uint4*)(sm.Z + row * ZP + i * 64 + n2 * 4), x = xr[i];
        const uint4 r = make_uint4(hadd2bf(o.x, x.x), hadd2bf(o.y, x.y), hadd2bf(o.z, x.z), hadd2bf(o.w, x.w));
        stg128_if(xout + off + i * 128, r, live); unpack8(r, f + 8 * i);
      }
      if (do_ln) {
        ln_row(f);
#pragma unroll
        for (int i = 0; i < 5; i++) stg128_if(g_xn + off + i * 128, pack8(f + 8 * i), live);
      }
    }
  }
  LOGK(3 + 3 * !do_ln, 2);
}

typedef CUresult (*EncFn)(CUtensorMap*, CUtensorMapDataType, cuuint32_t, void*, const cuuint64_t*, const cuuint64_t*, const cuuint32_t*, const cuuint32_t*,
                          CUtensorMapInterleave, CUtensorMapSwizzle, CUtensorMapL2promotion, CUtensorMapFloatOOBfill);
static void make_map(EncFn fn, CUtensorMap* m, const void* p, uint64_t cols, uint64_t rows, uint32_t bc, uint32_t br, CUtensorMapSwizzle sw) {
  cuuint64_t gd[2] = {cols, rows}, gs[1] = {cols * 2}; cuuint32_t bd[2] = {bc, br}, es[2] = {1, 1};
  fn(m, CU_TENSOR_MAP_DATA_TYPE_BFLOAT16, 2, (void*)p, gd, gs, bd, es, CU_TENSOR_MAP_INTERLEAVE_NONE, sw, CU_TENSOR_MAP_L2_PROMOTION_L2_128B, CU_TENSOR_MAP_FLOAT_OOB_FILL_NONE);
}
template <class... P, class... A>
static void launch(void (*k)(P...), int grid, int block, int smem, bool pdl, A... a) {
  cudaLaunchConfig_t cfg = {}; cfg.gridDim = dim3(grid); cfg.blockDim = dim3(block); cfg.dynamicSmemBytes = smem; cfg.stream = cudaStreamPerThread;
  cudaLaunchAttribute at[1]; at[0].id = cudaLaunchAttributeProgrammaticStreamSerialization; at[0].val.programmaticStreamSerializationAllowed = 1;
  cfg.attrs = at; cfg.numAttrs = pdl ? 1 : 0;
  cudaLaunchKernelEx(&cfg, k, a...);
}
static const int tune_t[10] = {1580, 1800, 1930, 2080, 2380, 2480, 2710, 2860, 2598, 2700}; constexpr int dev_stop = 100, dev_pdl = 1;

extern "C" void kernel_launch(void* const* d_in, const int* in_sizes, int n_in, void* d_out, int out_size) {
  const bf16 *x = (const bf16*)d_in[0], *mem0 = (const bf16*)d_in[1], *Wq = (const bf16*)d_in[2], *Wk = (const bf16*)d_in[3], *Wv = (const bf16*)d_in[4], *Wo = (const bf16*)d_in[5];
  const bf16 *wr = (const bf16*)d_in[8], *wi = (const bf16*)d_in[9];
  constexpr int SM_A = S_END + 1024, SM_R = sizeof(RowSmem), SM_C = 76 * 1024, SM_I = 116 * 1024;
  void *p_xn, *p_o, *p_x, *p_comm, *p_flags, *fn; cudaDriverEntryPointQueryResult qr;
  cudaGetSymbolAddress(&p_xn, g_xn); cudaGetSymbolAddress(&p_o, g_o); cudaGetSymbolAddress(&p_x, g_x); cudaGetSymbolAddress(&p_comm, g_comm); cudaGetSymbolAddress(&p_flags, g_flags);
  cudaGetDriverEntryPoint("cuTensorMapEncodeTiled", &fn, cudaEnableDefault, &qr);
  cudaFuncSetAttribute(layer_a_kernel, cudaFuncAttributeMaxDynamicSharedMemorySize, SM_A);
  cudaFuncSetAttribute(rows_fwd_kernel, cudaFuncAttributeMaxDynamicSharedMemorySize, SM_R);
  cudaFuncSetAttribute(rows_inv_kernel, cudaFuncAttributeMaxDynamicSharedMemorySize, SM_I);
  cudaFuncSetAttribute(cols_kernel, cudaFuncAttributeMaxDynamicSharedMemorySize, SM_C);
  cudaFuncSetAttribute(rows_fwd_kernel, cudaFuncAttributePreferredSharedMemoryCarveout, 100);
  cudaFuncSetAttribute(cols_kernel, cudaFuncAttributePreferredSharedMemoryCarveout, 100);
  cudaFuncSetAttribute(rows_inv_kernel, cudaFuncAttributePreferredSharedMemoryCarveout, 100);
  CUtensorMap tq, tk, tv, to, to32, tx, tao; EncFn enc = (EncFn)fn;
  make_map(enc, &tq, Wq, 4096, 640, 64, 64, CU_TENSOR_MAP_SWIZZLE_128B); make_map(enc, &tk, Wk, 4096, 640, 64, 64, CU_TENSOR_MAP_SWIZZLE_128B);
  make_map(enc, &tv, Wv, 4096, 640, 64, 64, CU_TENSOR_MAP_SWIZZLE_128B); make_map(enc, &to, Wo, 640, 4096, 64, 64, CU_TENSOR_MAP_SWIZZLE_128B);
  make_map(enc, &to32, Wo, 640, 4096, 16, 256, CU_TENSOR_MAP_SWIZZLE_32B);
  make_map(enc, &tx, p_xn, 640, 2048, 64, 64, CU_TENSOR_MAP_SWIZZLE_128B); make_map(enc, &tao, p_o, 4096, 2048, 64, 64, CU_TENSOR_MAP_SWIZZLE_128B);
  char* comm = (char*)(((uintptr_t)p_comm + (2 << 20) - 1) & ~(uintptr_t)((2 << 20) - 1));
  const bool pdl = dev_pdl;
#define L0PDL 0
  for (int l = 0; l < 2; l++) {
    ArgsA a{x, mem0, comm, (uint32_t*)p_flags + l * F_LAYER, wr, wi, (const char*)Wq, (const char*)Wo, l, {tune_t[0], tune_t[1], tune_t[2], tune_t[3]}, {tune_t[4], tune_t[5], tune_t[6], tune_t[7]}, {tune_t[8], tune_t[9]}};
    if (dev_stop > 4 * l + 0) launch(layer_a_kernel, 132, 384, SM_A, pdl && (l || L0PDL), tq, tk, tv, to, to32, tx, tao, a);
    if (dev_stop > 4 * l + 1) launch(rows_fwd_kernel, 128, 320, SM_R, pdl, l ? (const bf16*)p_x : x, (const uint32_t*)a.flags);
    if (dev_stop > 4 * l + 2) launch(cols_kernel, 107, 384, SM_C, pdl, l);
    if (dev_stop > 4 * l + 3) launch(rows_inv_kernel, 128, 320, SM_I, pdl, l ? (bf16*)d_out : (bf16*)p_x, l == 0);
  }
}
```

```cpp
#include <cuda_runtime.h>
#include <cuda_bf16.h>
#include <cuda_fp16.h>
#include <cuda.h>
#include <stdint.h>

typedef __nv_bfloat16 bf16;
#define DEVINL __device__ __forceinline__

__device__ __align__(1024) bf16 g_xn[2048 * 640];
__device__ __align__(1024) bf16 g_x[2048 * 640];
__device__ __align__(1024) char g_kv[64 * 32 * 16384];
__device__ __align__(1024) char g_kvm[64 * 32 * 4096];
__device__ __align__(1024) bf16 g_o[2048 * 4096];
__device__ __align__(1024) bf16 g_part[4 * 2048 * 640];
__device__ __align__(1024) uint32_t g_y[321 * 2048];
__device__ __align__(1024) uint32_t g_wt[321 * 2048];
__device__ __align__(4096) char g_comm[4 << 20];
constexpr int F_KV = 0, F_KM = 1024, F_O = F_KM + 1024, F_P = F_O + 128, F_ROLE = F_P + 32 * 32, F_X = F_ROLE + 64, F_LAYER = F_X + 32;
__device__ __align__(1024) uint32_t g_flags[2 * F_LAYER];
__device__ int g_side[256];

template <int V> struct IC { static constexpr int value = V; };
template <int B, int E, class F> DEVINL void static_for(F&& f) { if constexpr (B < E) { f(IC<B>{}); static_for<B + 1, E>(f); } }

#define POLL_LIMIT (1 << 17)
DEVINL uint32_t smem_u32(const void* p) { return (uint32_t)__cvta_generic_to_shared(p); }
DEVINL uint32_t mapa(uint32_t a, uint32_t r) { uint32_t o; asm volatile("mapa.shared::cluster.u32 %0, %1, %2;" : "=r"(o) : "r"(a), "r"(r)); return o; }
DEVINL uint32_t clk() { uint32_t v; asm volatile("{.reg .b64 w; mov.u64 w, %%clock64; cvt.u32.u64 %0, w;}" : "=r"(v)::"memory"); return v; }
DEVINL void mbar_init(uint32_t bar, uint32_t cnt) { asm volatile("mbarrier.init.shared::cta.b64 [%0], %1;" ::"r"(bar), "r"(cnt) : "memory"); }
DEVINL void mbar_arrive(uint32_t bar) { asm volatile("mbarrier.arrive.shared::cta.b64 _, [%0];" ::"r"(bar) : "memory"); }
DEVINL void mbar_arrive_remote(uint32_t bar) { asm volatile("mbarrier.arrive.shared::cluster.b64 _, [%0];" ::"r"(bar) : "memory"); }
DEVINL void mbar_arrive_tx(uint32_t bar, uint32_t tx) { asm volatile("mbarrier.arrive.expect_tx.shared::cta.b64 _, [%0], %1;" ::"r"(bar), "r"(tx) : "memory"); }
DEVINL void mbar_wait(uint32_t bar, uint32_t ph) {
  asm volatile("{.reg .pred p; .reg .b32 c,q; shl.b32 c, %1, 20;\n"
               "W0: bfe.u32 q, c, 20, 1; mbarrier.try_wait.parity.shared::cta.b64 p, [%0], q; add.u32 c,c,1; @!p bra.uni W0;}" ::"r"(bar), "r"(ph) : "memory");
}
DEVINL void bar_sync(int id, int n) { asm volatile("bar.sync %0, %1;" ::"r"(id), "r"(n) : "memory"); }
DEVINL void bar_arrive(int id, int n) { asm volatile("bar.arrive %0, %1;" ::"r"(id), "r"(n) : "memory"); }
DEVINL void cluster_sync() { asm volatile("barrier.cluster.arrive.release.aligned; barrier.cluster.wait.acquire.aligned;" ::: "memory"); }
DEVINL void tma_2d(uint32_t dst, const CUtensorMap* tm, int c0, int c1, uint32_t bar) {
  asm volatile("cp.async.bulk.tensor.2d.shared::cluster.global.mbarrier::complete_tx::bytes [%0], [%1, {%2, %3}], [%4];" ::"r"(dst), "l"(tm), "r"(c0), "r"(c1), "r"(bar) : "memory");
}
DEVINL void tma_2d_mc(uint32_t dst, const CUtensorMap* tm, int c0, int c1, uint32_t bar) {
  asm volatile("cp.async.bulk.tensor.2d.shared::cluster.global.mbarrier::complete_tx::bytes.multicast::cluster [%0], [%1, {%2, %3}], [%4], %5;" ::"r"(dst), "l"(tm), "r"(c0), "r"(c1), "r"(bar), "h"((uint16_t)3) : "memory");
}
DEVINL void bulk_g2s(uint32_t dst, const void* src, uint32_t bytes, uint32_t bar) {
  asm volatile("cp.async.bulk.shared::cluster.global.mbarrier::complete_tx::bytes [%0], [%1], %2, [%3];" ::"r"(dst), "l"(src), "r"(bytes), "r"(bar) : "memory");
}
DEVINL void l2_prefetch(const void* p, uint32_t bytes) { asm volatile("cp.async.bulk.prefetch.L2.global [%0], %1;" ::"l"(p), "r"(bytes) : "memory"); }
DEVINL void fence_proxy_async() { asm volatile("fence.proxy.async.global;" ::: "memory"); }
DEVINL void ldsm4t(uint32_t* r, uint32_t a) { asm volatile("ldmatrix.sync.aligned.m8n8.x4.trans.shared.b16 {%0,%1,%2,%3}, [%4];" : "=r"(r[0]), "=r"(r[1]), "=r"(r[2]), "=r"(r[3]) : "r"(a) : "memory"); }
DEVINL void stsm4(uint32_t a, uint32_t r0, uint32_t r1, uint32_t r2, uint32_t r3) { asm volatile("stmatrix.sync.aligned.m8n8.x4.shared.b16 [%0], {%1,%2,%3,%4};" ::"r"(a), "r"(r0), "r"(r1), "r"(r2), "r"(r3) : "memory"); }
DEVINL void mma16816(float* d, const uint32_t* a, uint32_t b0, uint32_t b1) {
  asm volatile("mma.sync.aligned.m16n8k16.row.col.f32.bf16.bf16.f32 {%0,%1,%2,%3}, {%4,%5,%6,%7}, {%8,%9}, {%0,%1,%2,%3};"
               : "+f"(d[0]), "+f"(d[1]), "+f"(d[2]), "+f"(d[3]) : "r"(a[0]), "r"(a[1]), "r"(a[2]), "r"(a[3]), "r"(b0), "r"(b1));
}
DEVINL void mma16816z(float* d, const uint32_t* a, uint32_t b0, uint32_t b1) {
  asm volatile("mma.sync.aligned.m16n8k16.row.col.f32.bf16.bf16.f32 {%0,%1,%2,%3}, {%4,%5,%6,%7}, {%8,%9}, {%10,%10,%10,%10};"
               : "=f"(d[0]), "=f"(d[1]), "=f"(d[2]), "=f"(d[3]) : "r"(a[0]), "r"(a[1]), "r"(a[2]), "r"(a[3]), "r"(b0), "r"(b1), "f"(0.f));
}
DEVINL void mma1688z(float* d, uint32_t a0, uint32_t a1, uint32_t b0) {
  asm volatile("mma.sync.aligned.m16n8k8.row.col.f32.bf16.bf16.f32 {%0,%1,%2,%3}, {%4,%5}, {%6}, {%7,%7,%7,%7};"
               : "=f"(d[0]), "=f"(d[1]), "=f"(d[2]), "=f"(d[3]) : "r"(a0), "r"(a1), "r"(b0), "f"(0.f));
}
DEVINL uint32_t movm(uint32_t a) { uint32_t r; asm volatile("movmatrix.sync.aligned.m8n8.trans.b16 %0, %1;" : "=r"(r) : "r"(a)); return r; }
DEVINL uint32_t pack_bf16(float lo, float hi) { uint32_t r; asm("cvt.rn.bf16x2.f32 %0, %1, %2;" : "=r"(r) : "f"(hi), "f"(lo)); return r; }
DEVINL uint32_t pack_f16(float lo, float hi) { uint32_t r; asm("cvt.rn.f16x2.f32 %0, %1, %2;" : "=r"(r) : "f"(hi), "f"(lo)); return r; }
DEVINL float bf_lo(uint32_t w) { return __uint_as_float(w << 16); }
DEVINL float bf_hi(uint32_t w) { return __uint_as_float(w & 0xffff0000u); }
DEVINL uint32_t hadd2bf(uint32_t a, uint32_t b) { uint32_t r; asm("add.rn.bf16x2 %0, %1, %2;" : "=r"(r) : "r"(a), "r"(b)); return r; }
DEVINL uint32_t hmax2bf(uint32_t a, uint32_t b) { uint32_t r; asm("max.bf16x2 %0, %1, %2;" : "=r"(r) : "r"(a), "r"(b)); return r; }
DEVINL uint32_t lds32(uint32_t a) { uint32_t v; asm volatile("ld.shared.u32 %0, [%1];" : "=r"(v) : "r"(a) : "memory"); return v; }
DEVINL uint2 lds64(uint32_t a) { uint2 v; asm volatile("ld.shared.v2.u32 {%0,%1}, [%2];" : "=r"(v.x), "=r"(v.y) : "r"(a) : "memory"); return v; }
DEVINL uint4 lds128(uint32_t a) { uint4 v; asm volatile("ld.shared.v4.u32 {%0,%1,%2,%3}, [%4];" : "=r"(v.x), "=r"(v.y), "=r"(v.z), "=r"(v.w) : "r"(a) : "memory"); return v; }
DEVINL void sts32(uint32_t a, uint32_t v) { asm volatile("st.shared.u32 [%0], %1;" ::"r"(a), "r"(v) : "memory"); }
DEVINL void sts64(uint32_t a, uint32_t x, uint32_t y) { asm volatile("st.shared.v2.u32 [%0], {%1,%2};" ::"r"(a), "r"(x), "r"(y) : "memory"); }
DEVINL void sts128(uint32_t a, uint4 v) { asm volatile("st.shared.v4.u32 [%0], {%1,%2,%3,%4};" ::"r"(a), "r"(v.x), "r"(v.y), "r"(v.z), "r"(v.w) : "memory"); }
DEVINL void stasync64(uint32_t a, uint32_t x, uint32_t y, uint32_t bar) { asm volatile("st.async.weak.shared::cluster.mbarrier::complete_tx::bytes.v2.b32 [%0], {%1,%2}, [%3];" ::"r"(a), "r"(x), "r"(y), "r"(bar) : "memory"); }
DEVINL uint4 ldg_rlx128(const void* p) { uint4 v; asm volatile("{.reg .b64 a,b; ld.relaxed.gpu.global.v2.b64 {a,b}, [%4]; mov.b64 {%0,%1}, a; mov.b64 {%2,%3}, b;}" : "=r"(v.x), "=r"(v.y), "=r"(v.z), "=r"(v.w) : "l"(p) : "memory"); return v; }
DEVINL uint2 ldg_rlx64(const void* p) { uint2 v; asm volatile("ld.relaxed.gpu.global.v2.u32 {%0,%1}, [%2];" : "=r"(v.x), "=r"(v.y) : "l"(p) : "memory"); return v; }
DEVINL void stg_rlx64(void* p, uint32_t x, uint32_t y) { asm volatile("{.reg .b64 a; mov.b64 a, {%1,%2}; st.relaxed.gpu.global.b64 [%0], a;}" ::"l"(p), "r"(x), "r"(y) : "memory"); }
DEVINL void stg_rlx128(void* p, uint32_t x, uint32_t y, uint32_t z, uint32_t w) { asm volatile("{.reg .b64 a,b; mov.b64 a, {%1,%2}; mov.b64 b, {%3,%4}; st.relaxed.gpu.global.v2.b64 [%0], {a,b};}" ::"l"(p), "r"(x), "r"(y), "r"(z), "r"(w) : "memory"); }
DEVINL void stg_rlx32(void* p, uint32_t x) { asm volatile("st.relaxed.gpu.global.u32 [%0], %1;" ::"l"(p), "r"(x) : "memory"); }
DEVINL uint4 ldg_cg128(const void* p) { uint4 v; asm volatile("ld.global.cg.v4.u32 {%0,%1,%2,%3}, [%4];" : "=r"(v.x), "=r"(v.y), "=r"(v.z), "=r"(v.w) : "l"(p) : "memory"); return v; }
DEVINL uint32_t ldg_cg32(const void* p) { uint32_t v; asm volatile("ld.global.cg.u32 %0, [%1];" : "=r"(v) : "l"(p) : "memory"); return v; }
DEVINL uint32_t ldg32_if(const void* p, int on) { uint32_t v; asm volatile("{.reg .pred q; setp.ne.s32 q, %2, 0; mov.u32 %0, 0; @q ld.global.cg.u32 %0, [%1];}" : "=r"(v) : "l"(p), "r"(on) : "memory"); return v; }
DEVINL uint4 ldg128_if(const void* p, int on) { uint4 v; asm volatile("{.reg .pred q; setp.ne.s32 q, %5, 0; mov.u32 %0, 0; mov.u32 %1, 0; mov.u32 %2, 0; mov.u32 %3, 0; @q ld.global.cg.v4.u32 {%0,%1,%2,%3}, [%4];}" : "=r"(v.x), "=r"(v.y), "=r"(v.z), "=r"(v.w) : "l"(p), "r"(on) : "memory"); return v; }
DEVINL void stg32_if(void* p, uint32_t v, int on) { asm volatile("{.reg .pred q; setp.ne.s32 q, %2, 0; @q st.global.u32 [%0], %1;}" ::"l"(p), "r"(v), "r"(on) : "memory"); }
DEVINL void stg128_if(void* p, uint4 v, int on) { asm volatile("{.reg .pred q; setp.ne.s32 q, %5, 0; @q st.global.v4.u32 [%0], {%1,%2,%3,%4};}" ::"l"(p), "r"(v.x), "r"(v.y), "r"(v.z), "r"(v.w), "r"(on) : "memory"); }
DEVINL uint4 ldg_ca128(const void* p) { uint4 v; asm volatile("ld.global.ca.v4.u32 {%0,%1,%2,%3}, [%4];" : "=r"(v.x), "=r"(v.y), "=r"(v.z), "=r"(v.w) : "l"(p) : "memory"); return v; }
DEVINL uint32_t ldg_ca32(const void* p) { uint32_t v; asm volatile("ld.global.ca.u32 %0, [%1];" : "=r"(v) : "l"(p) : "memory"); return v; }
DEVINL void flag_wait(const uint32_t* p, uint32_t want) {
  uint32_t v;
#pragma unroll 1
  for (int n = 0; n < POLL_LIMIT; n++) { asm volatile("ld.acquire.gpu.global.u32 %0, [%1];" : "=r"(v) : "l"(p) : "memory"); if (v >= want) break; __nanosleep(40); }
}
DEVINL void flag_wait_warp(const uint32_t* p, uint32_t want) {
  uint32_t v; int n = 0;
  do { asm volatile("ld.acquire.gpu.global.u32 %0, [%1];" : "=r"(v) : "l"(p) : "memory"); } while (__any_sync(~0u, v < want && ++n < POLL_LIMIT));
}
DEVINL void flag_add(uint32_t* p) { asm volatile("red.release.gpu.global.add.u32 [%0], 1;" ::"l"(p) : "memory"); }
DEVINL void flag_set(uint32_t* p, uint32_t v) { asm volatile("fence.acq_rel.gpu; st.relaxed.gpu.global.u32 [%0], %1;" ::"l"(p), "r"(v) : "memory"); }
DEVINL uint32_t ldg_rlx32(const void* p) { uint32_t v; asm volatile("ld.relaxed.gpu.global.u32 %0, [%1];" : "=r"(v) : "l"(p) : "memory"); return v; }
DEVINL float ex2(float x) { float y; asm("ex2.approx.ftz.f32 %0, %1;" : "=f"(y) : "f"(x)); return y; }
DEVINL float rcp(float x) { float y; asm("rcp.approx.ftz.f32 %0, %1;" : "=f"(y) : "f"(x)); return y; }
DEVINL uint32_t opaque(uint32_t x) { return __shfl_sync(~0u, x, threadIdx.x & 31); }
DEVINL uint32_t launder(uint32_t x) { asm volatile("" : "+r"(x)); return x; }
DEVINL void pdl_wait() { asm volatile("griddepcontrol.wait;" ::: "memory"); }
DEVINL void pdl_launch() { asm volatile("griddepcontrol.launch_dependents;" ::: "memory"); }
#define LOGS(cta, i)
#define LOGK(k, i)
#define LOG(cta, i)
#define LOGV(cta, i, v)
#define EV(i, v)
constexpr float SM_SCALE = 0.08838834764831845f * 1.4426950408889634f;

DEVINL void unpack8(uint4 v, float* f) { f[0] = bf_lo(v.x); f[1] = bf_hi(v.x); f[2] = bf_lo(v.y); f[3] = bf_hi(v.y); f[4] = bf_lo(v.z); f[5] = bf_hi(v.z); f[6] = bf_lo(v.w); f[7] = bf_hi(v.w); }
DEVINL uint4 pack8(const float* f) { return make_uint4(pack_bf16(f[0], f[1]), pack_bf16(f[2], f[3]), pack_bf16(f[4], f[5]), pack_bf16(f[6], f[7])); }
DEVINL void ln_row(float* f) {
  float s = 0.f;
#pragma unroll
  for (int i = 0; i < 40; i++) s += f[i];
#pragma unroll
  for (int o = 1; o < 16; o <<= 1) s += __shfl_xor_sync(~0u, s, o);
  const float mean = s * (1.f / 640.f); float q = 0.f;
#pragma unroll
  for (int i = 0; i < 40; i++) { f[i] -= mean; q = fmaf(f[i], f[i], q); }
#pragma unroll
  for (int o = 1; o < 16; o <<= 1) q += __shfl_xor_sync(~0u, q, o);
  const float rs = rsqrtf(q * (1.f / 640.f) + 1e-5f);
#pragma unroll
  for (int i = 0; i < 40; i++) f[i] *= rs;
}

struct ArgsA {
  const bf16* x; const bf16* mem0; char* comm; uint32_t* flags; const bf16* wr; const bf16* wi; const char* wq; const char* wo;
  int layer; int ta[4], tb[4], tc[2];
};

#define VP 4
#define HELD 0x2557
#define PRE 4
#define VPRE0 2
#define VPRE1 4
#define R0 2
#define TRK 30
#define TEXP 200
#define TRD 0
#define TKV 300
#define KB1 5
#define W2D 0
#define WD 4
#define VPW 2
#define P1F 1
#define W0D 0
#define XD 0
#define TSF 1
#define W1D 60
constexpr int C_WV = 0;
constexpr int C_WO = 81920;
constexpr int C_KV = 163840;
constexpr int C_M  = C_KV + 24576;
constexpr int C_QK = C_M + 10240;
constexpr int C_VP = C_QK + 4096;
constexpr int C_S  = C_VP + 4096;
constexpr int C_O  = C_S + 2048;
constexpr int C_R  = C_O + 2048;
constexpr int C_T  = C_R + 256;
constexpr int S_BAR = 229376;
constexpr int S_END = S_BAR + 256;
enum { BAR_QK = 2, BAR_O = 3, BAR_H = 4, BAR_X = 5, BAR_W = 7  , BAR_E = 9, BAR_M1 = 10, BAR_M2 = 11, BAR_M3 = 12 };
constexpr int B_W = 0, B_S = 8, B_W2 = 16, B_KV = 24, B_WV = 40, B_WO = 48;
constexpr int G2_OFF = 0x130000, TS_OFF = 0x11000;

#define FEN() asm volatile("pmevent 0;" ::: "memory")
#define SCHED(x, c) asm volatile("{.reg .pred p; setp.eq.u32 p, %0, %1; @p exit;}" ::"r"(x), "r"(0x7fff0001u + 2 * (c)) : "memory")
DEVINL uint32_t g1page(uint32_t L) { L = ((L & 7) | ((L & 24) << 2)) << 1; return (L | (__popc(L & 0xb2) & 1)) << 12; }
DEVINL void spin_until(uint32_t t) {
  asm volatile("{.reg .pred p; .reg .b32 c; .reg .b64 w;\nS0: mov.u64 w, %%clock64; cvt.u32.u64 c, w; sub.u32 c, %0, c; setp.lt.u32 p, c, 16384; @p bra.uni S0;}" ::"r"(t) : "memory");
}
DEVINL uint32_t wait_until(uint32_t t, uint32_t z) { uint32_t r;
  asm volatile("{.reg .pred p; .reg .b32 c,x,y; .reg .b64 w;\nT0: .branchtargets L0, L1, L2, L3, L4, L5, L6, L7, L8, L9, L10;\n mov.u32 x, %2;\n"
               "mov.u64 w, %%clock64; cvt.u32.u64 c, w; sub.u32 c, %1, c; setp.ge.u32 p, c, 16384; @p bra.uni L0;\n"
               "S0: mov.u64 w, %%clock64; cvt.u32.u64 c, w; sub.u32 c, %1, c; setp.gt.s32 p, c, 40; @p bra.uni S0;\n"
               "mad.lo.s32 c, c, 37, 1200; shr.s32 c, c, 8; max.s32 c, c, 0;\nbrx.idx.uni c, T0;\n"
               "L10: mul.lo.u32 x, x, x; L9: mul.lo.u32 x, x, x; L8: mul.lo.u32 x, x, x; L7: mul.lo.u32 x, x, x; L6: mul.lo.u32 x, x, x; L5: mul.lo.u32 x, x, x; L4: mul.lo.u32 x, x, x; L3: mul.lo.u32 x, x, x; L2: mul.lo.u32 x, x, x; L1: mul.lo.u32 x, x, x; L0: mov.u32 %0, x;}" : "=r"(r) : "r"(t), "r"(z) : "memory"); return r;
}
DEVINL void gtime(uint32_t& G16, uint32_t& C) {
  asm volatile("{.reg .b64 w; .reg .b32 g,g0,a;\n mov.u64 w, %%clock64; cvt.u32.u64 %1, w; mov.u64 w, %%globaltimer; cvt.u32.u64 g0, w; mul.lo.u32 a, g0, -11;\n"
               "mov.u64 w, %%globaltimer; cvt.u32.u64 g, w; add.u32 a, a, g; mov.u64 w, %%globaltimer; cvt.u32.u64 g, w; add.u32 a, a, g; mov.u64 w, %%globaltimer; cvt.u32.u64 g, w; add.u32 a, a, g; mov.u64 w, %%globaltimer; cvt.u32.u64 g, w; add.u32 a, a, g; mov.u64 w, %%globaltimer; cvt.u32.u64 g, w; add.u32 a, a, g; mov.u64 w, %%globaltimer; cvt.u32.u64 g, w; add.u32 a, a, g; mov.u64 w, %%globaltimer; cvt.u32.u64 g, w; add.u32 a, a, g; mov.u64 w, %%globaltimer; cvt.u32.u64 g, w; add.u32 a, a, g; mov.u64 w, %%globaltimer; cvt.u32.u64 g, w; add.u32 a, a, g; mov.u64 w, %%globaltimer; cvt.u32.u64 g, w; add.u32 a, a, g; mov.u64 w, %%globaltimer; cvt.u32.u64 g, w; add.u32 a, a, g; \n mul.lo.u32 a, a, 341; shr.u32 a, a, 8; mad.lo.u32 %0, g0, 16, a;}" : "=r"(G16), "=r"(C)::"memory");
}
DEVINL uint32_t pack_tag(float lo, float hi, uint32_t tg) {
  const uint32_t w = pack_bf16(lo, __uint_as_float(tg | 0x3F800000u)), a = __float_as_uint(hi) + (tg ^ 0x10000u); uint32_t r;
  asm("lop3.b32 %0, %1, %2, 0xFFFE0000, 0xE4;" : "=r"(r) : "r"(a), "r"(w)); return r;
}
DEVINL float ex2v(float x) { float y; asm volatile("ex2.approx.ftz.f32 %0, %1;" : "=f"(y) : "f"(x)); return y; }
DEVINL void load_kv(uint32_t sb, int h, int j, int s) {
  asm volatile("{.reg .pred p; elect.sync _|p, 0xffffffff;\n fence.proxy.async.global;\n @p mbarrier.arrive.expect_tx.shared::cta.b64 _, [%2], 12288;\n"
               " @p cp.async.bulk.shared::cluster.global.mbarrier::complete_tx::bytes [%0], [%1], 12288, [%2];}"
               ::"r"(sb + C_KV + (s & 1) * 12288), "l"(g_kv + (size_t)(s * 32 + h) * 16384 + j * 4096), "r"(sb + S_BAR + B_KV + (s & 1) * 8) : "memory");
}

template <int KH>
DEVINL void chain_mma(uint32_t sb0, const ArgsA& args) {
  const int lane = threadIdx.x & 31, mg = (threadIdx.x >> 5) & 3, mi = lane >> 3, r = lane & 7;
  const uint32_t aW = opaque(sb0 + (uint32_t)(((mi >> 1) * 8 + r) * 128 + (((mg + 4 * (mi & 1)) ^ r) << 4)));
  const uint32_t aL = opaque(sb0 + lane * 16);
  const uint32_t aLm = opaque(sb0 + mg * 512 + lane * 16);
#define sb (launder(aL) & ~511u)
  constexpr int OV = C_WV + KH * 40960, OM = C_M + KH * 5120, NF = KH ? 16 : 24;
  auto owo = [](int f) { return C_WO + (KH + 2 * (f >> 3)) * 16384 + (f & 7) * 2048; };
  auto held = [](int k) { return (HELD >> k) & 1; };
  auto rank = [](int k) { return __popc(HELD & ((1 << k) - 1)); };
  uint32_t wq[20][4], wk[20][4];
  mbar_wait(sb + S_BAR + B_W, 0);
#pragma unroll
  for (int k = 0; k < 12; k++) { ldsm4t(wq[k], aW + OV + k * 2048); ldsm4t(wk[k], aW + C_WO + KH * 40960 + k * 2048); }
  bar_arrive(BAR_H, 288);
  mbar_wait(sb + S_BAR + B_W2, 0);
#pragma unroll
  for (int k = 12; k < 20; k++) { ldsm4t(wq[k], aW + OV + k * 2048); ldsm4t(wk[k], aW + C_WO + KH * 40960 + k * 2048); }
  bar_sync(BAR_E, 384);
  mbar_wait(sb + S_BAR + B_WV, 0);
  uint32_t sx = args.layer << 16;
#pragma unroll 1
  while (true) {
    uint32_t v[20][4], b[10][4];
    {
      const uint32_t o = launder(aLm) - sb, on = (sx >> 16) != (uint32_t)args.layer;
      const char* p = args.comm + lds32(sb + C_T + KH * 1024 + 4 + (o >> 1));
      const uint32_t am = sb + OM + (o & 0x400) + ((o & 0x3f0) >> 1);
      constexpr int NB = KH ? VPRE1 : VPRE0;
      const uint32_t zero = (uint32_t)(uintptr_t)p & 1, tt = lds32(sb + C_R + 48) + args.tb[0]; uint32_t av = aW;
#pragma unroll
      for (int k = 0; k < 20; k++) if (held(k) && rank(k) < NB) { ldsm4t(v[k], av + OV + k * 2048); if (rank(k) % VPW == VPW - 1 && rank(k) < NB - 1) av = aW + (v[k][0] & zero); }
      p += wait_until(tt, zero);
      uint4 a = ldg_rlx128(p);
      __syncwarp();
#pragma unroll
      for (int k = 0; k < 20; k++) if (held(k) && rank(k) >= NB) { ldsm4t(v[k], av + OV + k * 2048); if ((rank(k) - NB) % VPW == VPW - 1) av = aW + (v[k][0] & zero); }
      SCHED(am ^ on, 29);
      if (__builtin_expect(__any_sync(~0u, on && (((a.x ^ sx) | (a.z ^ sx)) & 0x10000u)), 0)) {
        int lim = 0;
        do a = ldg_rlx128(p); while (__any_sync(~0u, (((a.x ^ sx) | (a.z ^ sx)) & 0x10000u) && ++lim < POLL_LIMIT));
      }
      if (on) { sts64(am, a.x, a.z); sts64(am + 512, a.y, a.w); }
      bar_sync(BAR_W + KH, 128);
      ldsm4t(b[0], aL + OM); ldsm4t(b[1], aL + OM + 512);
    }
    float cq[4], ck[4], cv[4];
    static_for<0, 20>([&](auto I) {
      constexpr int k = I.value, p = k >> 1;
      const uint32_t b0 = b[p][(k & 1) * 2], b1 = b[p][(k & 1) * 2 + 1];
      if (k == 0) { mma16816z(cv, v[0], b0, b1); mma16816z(cq, wq[k], b0, b1); mma16816z(ck, wk[k], b0, b1); }
      else { if (k < 20 - VP) mma16816(cv, v[k], b0, b1); mma16816(cq, wq[k], b0, b1); mma16816(ck, wk[k], b0, b1); }
      if (k == KB1) bar_sync(BAR_M1, 288);
      if (k == KB1 + 4) bar_sync(BAR_M2, 288);
      if (k == KB1 + 8) bar_sync(BAR_M3, 352);
      { constexpr int q = (k + 8 - KB1) >> 1; if constexpr (((k - KB1) & 1) == 0 && q >= 2 && q < 10) ldsm4t(b[q], aL + OM + q * 512); }
      if constexpr (k + 3 < 20 - VP && !((HELD >> (k + 3)) & 1)) ldsm4t(v[k + 3], aW + OV + (k + 3) * 2048);
      if (k >= 20 - VP && k < 20 - VP + PRE && !held(k)) ldsm4t(v[k], aW + OV + k * 2048);
      if (P1F && (k & 1) && k >= P1F && k < 19) FEN();
    });
    stsm4(aLm + C_QK + KH * 2048, pack_bf16(cq[0], cq[1]), pack_bf16(cq[2], cq[3]), pack_bf16(ck[0], ck[1]), pack_bf16(ck[2], ck[3]));
    bar_arrive(BAR_QK, 384);
    FEN();
    const uint32_t l8 = (launder(aL) & 511) >> 1, px = lds32(sb + C_R + 80);
#pragma unroll
    for (int k = 20 - VP + PRE; k < 20; k++) if (!held(k)) ldsm4t(v[k], aW + OV + k * 2048);
#pragma unroll
    for (int k = 20 - VP; k < 20; k++) {
      const int p = k >> 1, q = k - 20 + VP; const uint32_t b0 = b[p][(k & 1) * 2], b1 = b[p][(k & 1) * 2 + 1];
      if (q % 3 == 0) mma16816(cv, v[k], b0, b1); else if (q == 1) mma16816z(cq, v[k], b0, b1); else if (q == 2) mma16816z(ck, v[k], b0, b1);
      else if (q % 3 == 1) mma16816(cq, v[k], b0, b1); else mma16816(ck, v[k], b0, b1);
    }
    if (VP >= 3) {
#pragma unroll
      for (int i = 0; i < 4; i++) cv[i] += cq[i] + ck[i];
    }
    { const uint32_t vx = pack_bf16(cv[0], cv[1]), vy = pack_bf16(cv[2], cv[3]);
      const uint32_t av = aLm - l8 + C_VP + KH * 256;
      stasync64(av + 2048 + px, vx, vy, sb + S_BAR + B_S + px);
      sts64(av, vx, vy);
      __syncwarp();
      if (l8 == 0) mbar_arrive(sb + S_BAR + B_S); }
    sx += 0x10000;
    if ((sx >> 16) == args.layer + 64u) break;
    uint32_t w[NF][4];
    {
      const uint32_t zero = px & 1; uint32_t a = aW;
      const bool tsw = KH == 1 && __any_sync(~0u, launder(aLm) == aL); uint2 ts = make_uint2(0, 0); uint4 cal = make_uint4(0, 0, 0, 0);
      if ((sx >> 16) == args.layer + 1u) mbar_wait(sb + S_BAR + B_WO, 0);
#pragma unroll
      for (int f = 0; f < 8; f++) { ldsm4t(w[f], a + owo(f));
        if (KH == 1 && f == TSF && tsw) { ts = ldg_rlx64(args.comm + TS_OFF + l8); cal = lds128(sb + C_R + 64); }
        uint32_t d = w[f][0] & zero;
#pragma unroll
        for (int q = 0; q < TRD; q++) d = __popc(d);
        a = aW + d; }
      if (KH == 1 && tsw) {
        const uint32_t d0 = ts.x - cal.x, d1 = ts.y - cal.x;
        const int dt = (int)__reduce_max_sync(~0u, max(d0 < 32768u ? d0 : 0u, d1 < 32768u ? d1 : 0u));
        sts32(sb + C_R + 48, cal.y + min((dt * cal.z) >> 16, 8192u));
      }
    }
    const uint32_t go = lds32(sb + C_T + KH * 1024 + ((launder(aLm) - sb) >> 1));
    SCHED(go, 30);
    bar_sync(BAR_O, 384);
    uint32_t ob[16];
#pragma unroll
    for (int p = 0; p < 4; p++) ldsm4t(ob + 4 * p, aL + C_O + p * 512);
    __syncwarp();
    float r0, r1; uint32_t y0, y1;
    { const uint2 rr = lds64(sb + C_R + 128 + ((launder(aL) >> 1) & 24)); r0 = rcp(__uint_as_float(rr.x)); r1 = rcp(__uint_as_float(rr.y)); }
    constexpr int RA = KH ? 0 : R0;
    static_for<0, NF>([&](auto I) {
      constexpr int f = I.value, k = f & 7; const uint32_t* A = w[f];
      if (k == 0) mma16816z(cq, A, ob[0], ob[1]); else if (k == 1) mma16816z(ck, A, ob[2], ob[3]);
      else if (k & 1) mma16816(ck, A, ob[2 * k], ob[2 * k + 1]); else mma16816(cq, A, ob[2 * k], ob[2 * k + 1]);
      if (f == 5 && RA) {
#pragma unroll
        for (int q = 0; q < RA; q++) ldsm4t(w[8 + q], aW + owo(8 + q));
        FEN();
      }
      if constexpr (f >= 8 && f + WD < NF) ldsm4t(w[f + WD], aW + owo(f + WD));
      if constexpr (XD != 0) { if (f == 15) spin_until(clk() + XD); }
      if (k == 7) { y0 = pack_tag((cq[0] + ck[0]) * r0, (cq[1] + ck[1]) * r1, sx & 0x10000u); y1 = pack_bf16((cq[2] + ck[2]) * r0, (cq[3] + ck[3]) * r1);
        stg_rlx64(args.comm + go + (f < 8 ? 0 : f < 16 ? 0x30000 : 0x100000), y0, y1); }
      if (f == 7) {
        if constexpr ((KH ? W1D : W0D) != 0) spin_until(clk() + (KH ? W1D : W0D)); else FEN();
#pragma unroll
        for (int q = RA; q < WD; q++) ldsm4t(w[8 + q], aW + owo(8 + q));
      }
      if (f >= 8 && k == 3) SCHED(y0 & y1 & go, 40 + f);
      else if (f >= 7 && (f & 1)) FEN();
    });
  }
}

#undef sb
DEVINL void chain_helper(uint32_t sb, uint32_t px, int h, int j, const ArgsA& args, const CUtensorMap* tq, const CUtensorMap* tk, const CUtensorMap* tv, const CUtensorMap* to) {
  const int c = 2 * h + j;
  const uint32_t bW = sb + S_BAR + B_W, bS = sb + S_BAR + B_S, bKV = sb + S_BAR + B_KV;
  const uint32_t lane0 = opaque(threadIdx.x & 31);
  const uint32_t warp = __reduce_max_sync(~0u, (threadIdx.x >> 5) & 3);
  { const int tid = threadIdx.x - 256;
    if (tid == 0) { mbar_arrive_tx(bW, 98304); mbar_arrive_tx(bW + B_W2, 65536); mbar_arrive_tx(bW + B_WV, 81920); mbar_arrive_tx(bW + B_WO, 81920);
#pragma unroll 1
      for (int q = 0; q < 10; q++) { const int i = (q & 1) * 5 + (q >> 1); const uint32_t bar = q < 6 ? bW : bW + B_W2;
        tma_2d(sb + C_WV + i * 8192, tq, h * 128 + j * 64, i * 64, bar); tma_2d(sb + C_WO + i * 8192, tk, h * 128 + j * 64, i * 64, bar); } }
    uint32_t G0, C0; gtime(G0, C0);
    if (warp == 0) sts64(sb + C_R + 96, G0, C0);
    { const uint32_t g = lane0 >> 2, t = lane0 & 3;
      sts128(sb + C_T + 2048 + tid * 16, make_uint4(g1page(c >> 1) + (c & 1) * 2048 + (warp == 0 ? 0 : warp == 1 ? 0x30000 : 0x100000) + ((g >> 2) * 4 + t) * 64 + (g & 3) * 16,
                                                    g1page(((t >> 1) + (g >> 2) * 2) * 4 + warp) + G2_OFF + c * 64 + (g & 3) * 16 + (t & 1) * 8,
                                                    g1page((h & 3) * 4 + 1 + (warp >> 1)) + G2_OFF + (warp & 1) * 1024 + lane0 * 16, (g & 1) ? 0x3F800000u : 0x00003F80u)); }
    sts32(sb + C_R + 80, px); sts32(sb + C_R + 48, C0 - 65536);
#pragma unroll
    for (int kh = 0; kh < 2; kh++)
      sts64(sb + C_T + kh * 1024 + tid * 8, g1page(j * 16 + kh * 8 + (tid >> 4)) + (tid & 8) * 256 + h * 64 + (tid & 7) * 8, g1page((h & 3) * 4) + G2_OFF + kh * 2048 + tid * 16);
#pragma unroll
    for (int i = 0; i < 5; i++) { const int q = tid + i * 128, n = q & 7, d0 = (q >> 3) * 8; const uint4 v = *(const uint4*)(args.mem0 + n * 640 + d0); const uint32_t w[4] = {v.x, v.y, v.z, v.w};
#pragma unroll
      for (int e = 0; e < 8; e++) asm volatile("st.shared.u16 [%0], %1;" ::"r"(sb + C_M + (d0 + e) * 16 + n * 2), "h"((unsigned short)(w[e >> 1] >> ((e & 1) * 16))) : "memory"); }
    auto round2 = [&](int q0, int q1) {
#pragma unroll 1
      for (int q = q0; q < q1; q++) { const int i = (q & 1) * 5 + (q >> 1); tma_2d(sb + C_WV + i * 8192, tv, h * 128 + j * 64, i * 64, bW + B_WV); }
#pragma unroll 1
      for (int q = q0; q < q1; q++) { const int i = (q & 1) * 5 + (q >> 1); tma_2d(sb + C_WO + i * 8192, to, j * 320 + (i >> 1) * 64, h * 128 + ((i & 1) ^ j) * 64, bW + B_WO); } };
    if (warp == 0) { bar_sync(BAR_H, 288); if (tid == 0) round2(0, 6); __syncwarp(); }
    bar_sync(BAR_E, 384);
    if (tid == 0) round2(6, 10);
    if (warp == 3) {
      if (tid == 96) LOG(c, 250);
      flag_wait_warp(args.flags + F_KV + h, 2);
      load_kv(sb, h, j, 0); load_kv(sb, h, j, 1); if (tid == 96) LOG(c, 251);
    }
  }
  auto calib = [&]() { uint32_t G, C; gtime(G, C);
    const uint2 o = lds64(sb + C_R + 96); const float rt = (float)(C - o.y) * rcp((float)(G - o.x));
    sts128(sb + C_R + 32, make_uint4(G, C, __float2uint_rn(rt * 65536.f) & 0xffffu, __float_as_uint(rcp(rt)))); __syncwarp(); };
  auto do_export = [&](int s, uint32_t lane, bool arrive) {
    uint32_t k0[2][4], k1[2][4]; uint2 a[4], b[4];
    const uint32_t ak = sb + C_QK + 256 + (lane >> 4) * 512 + (lane & 15) * 16, av = sb + C_VP + (lane >> 3) * 512 + (lane & 7) * 8;
#pragma unroll
    for (int i = 0; i < 2; i++) { ldsm4t(k0[i], ak + i * 1024); ldsm4t(k1[i], ak + i * 1024 + 2048); }
#pragma unroll
    for (int i = 0; i < 4; i++) { a[i] = lds64(av + i * 64); b[i] = lds64(av + i * 64 + 256); }
    char* dst = g_kvm + ((s * 32 + h) * 4096 + j * 1024 + lane * 16);
    const uint32_t tg = (args.layer ^ 1) << 16;
    auto put = [&](char* q, uint32_t x, uint32_t y, uint32_t z, uint32_t w) { stg_rlx128(q, (x & ~0x10000u) | tg, y, (z & ~0x10000u) | tg, w); };
#pragma unroll
    for (int i = 0; i < 2; i++) put(dst + i * 512, hadd2bf(k0[i][0], k1[i][0]), hadd2bf(k0[i][1], k1[i][1]), hadd2bf(k0[i][2], k1[i][2]), hadd2bf(k0[i][3], k1[i][3]));
    put(dst + 2048, hadd2bf(a[0].x, b[0].x), hadd2bf(a[1].x, b[1].x), hadd2bf(a[2].x, b[2].x), hadd2bf(a[3].x, b[3].x));
    put(dst + 2560, hadd2bf(a[0].y, b[0].y), hadd2bf(a[1].y, b[1].y), hadd2bf(a[2].y, b[2].y), hadd2bf(a[3].y, b[3].y));
    if (arrive) bar_arrive(BAR_M3, 352);
    stg_rlx32(args.flags + F_KM + h * 32 + j, s + 1);
  };
  if (warp == 0) { calib(); bar_arrive(BAR_M1, 288); } else if (warp == 1) bar_arrive(BAR_M2, 288); else bar_arrive(BAR_M3, 352);
  bool kv_all = false;
  uint2 kb[4];
  auto prep = [&](int s, uint32_t lane) {
    if (s < 63) mbar_wait(bKV + (s & 1) * 8, (s >> 1) & 1);
    const uint32_t aK = sb + C_KV + (s & 1) * 12288 + j * 8192 + warp * 1024 + lane * 16;
#pragma unroll
    for (int i = 0; i < 4; i++) kb[i] = lds64(aK + ((warp ^ i) >> 1) * 512 + ((warp ^ i) & 1) * 8);
    asm volatile("{.reg .pred p; setp.eq.u32 p, %2, 32; @p mbarrier.arrive.expect_tx.shared::cta.b64 _, [%0], %1;}" ::"r"(bS), "r"(s < 63 ? 3072 : 2048), "r"(warp * 32 + lane) : "memory");
  };
  prep(0, lane0);
#pragma unroll 1
  for (int s = 0;; s++) {
    const uint32_t ph = s & 1, kvb = sb + C_KV + ph * 12288;
    const uint32_t lane = __shfl_sync(~0u, lane0, lane0);
    const uint32_t mi = lane >> 3, r = lane & 7, zero = lane >> 5;
    const uint32_t aQ = sb + C_QK + (mi & 1) * 2048 + ((mi >> 1) * 8 + r) * 16;
    const uint32_t aKm = sb + C_QK + 256 + warp * 512 + (lane >> 4) * 2048 + (lane & 15) * 16;
    const uint32_t aH = sb + C_S + warp * 256 + lane * 8, aR = aH + 1024 + px;
    SCHED(aQ ^ aR ^ aKm, 60);
    if (warp == 0) {
      const uint4 cal = lds128(sb + C_R + 32);
      bar_sync(BAR_M3, 352);
      sts32(sb + C_R + 52, 0);
      const uint32_t E = clk(), e16 = cal.x + (uint32_t)__float2int_rn((float)(int)(E - cal.y) * __uint_as_float(cal.w));
      stg_rlx32(args.comm + TS_OFF + c * 4, e16); sts128(sb + C_R + 64, make_uint4(e16, E, cal.z, 0));
    }
    if (s == 63) { bar_sync(BAR_QK, 384); mbar_wait(bS, 1); if (warp == 3) do_export(63, lane, false); break; }
    {
      uint32_t qa[4][4], km[4]; float s0[4], s1[4], s2[4];
      bar_sync(BAR_QK, 384);
      ldsm4t(qa[0], aQ + warp * 512); ldsm4t(km, aKm); ldsm4t(qa[1], aQ + (warp ^ 1) * 512); ldsm4t(qa[2], aQ + (warp ^ 2) * 512); ldsm4t(qa[3], aQ + (warp ^ 3) * 512);
      mma16816z(s0, qa[0], kb[0].x, kb[0].y); mma16816z(s2, qa[0], km[0], km[1]); mma16816z(s1, qa[1], kb[1].x, kb[1].y);
      FEN();
      mma16816(s2, qa[0], km[2], km[3]); mma16816(s0, qa[2], kb[2].x, kb[2].y); mma16816(s1, qa[3], kb[3].x, kb[3].y);
      const uint32_t w0 = pack_bf16((s0[0] + s0[2]) + (s1[0] + s1[2]), (s0[1] + s0[3]) + (s1[1] + s1[3]));
      const uint32_t w1 = pack_bf16(s2[0] + s2[2], s2[1] + s2[3]);
      stasync64(aR, w0, w1, bS + px);
      sts64(aH, w0, w1);
    }
    {
      uint32_t vx[4][4], sl[5];
      const uint32_t aVx = kvb + 4096 + (warp >> 1) * (j ? -4096 : 4096) + (warp & 1) * 1024 + lane * 16;
      const uint32_t a8 = sb + lane * 8, av = a8 + C_VP + warp * 1024;
      const uint32_t aO = sb + C_O + ((warp >> 1) * 64 + (warp & 1) * 16 + (mi & 1) * 32 + (mi >> 1) * 8 + r) * 16, aU = sb + C_R + (lane & 28);
      bar_sync(BAR_X, 128);
      { uint2 t[4];
#pragma unroll
        for (int u = 0; u < 4; u++) t[u] = lds64(a8 + C_S + u * 256);
#pragma unroll
        for (int i = 0; i < 4; i++) { const uint4 q = lds128(aVx + (i & 1) * 2048 + (i >> 1) * 512); vx[i][0] = q.x ^ zero; vx[i][1] = q.z ^ zero; vx[i][2] = q.y ^ zero; vx[i][3] = q.w ^ zero; }
#pragma unroll
        for (int u = 0; u < 4; u++) sl[u] = t[u].x;
        sl[4] = pack_bf16((bf_lo(t[0].y) + bf_lo(t[1].y)) + (bf_lo(t[2].y) + bf_lo(t[3].y)), (bf_hi(t[0].y) + bf_hi(t[1].y)) + (bf_hi(t[2].y) + bf_hi(t[3].y))); }
      mbar_wait(bS, ph);
      uint32_t vm[2][4];
      { uint2 t[4];
#pragma unroll
        for (int u = 0; u < 4; u++) t[u] = lds64(a8 + C_S + 1024 + u * 256);
#pragma unroll
        for (int u = 0; u < 4; u++) sl[u] = hadd2bf(sl[u], t[u].x);
        sl[4] = hadd2bf(hadd2bf(hadd2bf(sl[4], t[0].y), t[1].y), hadd2bf(t[2].y, t[3].y)); }
      uint32_t m2 = hmax2bf(hmax2bf(hmax2bf(sl[0], sl[1]), hmax2bf(sl[2], sl[3])), sl[4]);
      const uint32_t x1 = __shfl_xor_sync(~0u, m2, 1), x2 = __shfl_xor_sync(~0u, m2, 2), x3 = __shfl_xor_sync(~0u, m2, 3);
#pragma unroll
      for (int i = 0; i < 4; i++) { const uint2 q = lds64(av + i * 256); vm[i >> 1][(i & 1) * 2] = q.x; vm[i >> 1][(i & 1) * 2 + 1] = q.y; }
      float sv[10];
#pragma unroll
      for (int u = 0; u < 5; u++) { sv[2 * u] = bf_lo(sl[u]) * SM_SCALE; sv[2 * u + 1] = bf_hi(sl[u]) * SM_SCALE; }
      FEN();
      m2 = hmax2bf(hmax2bf(m2, x1), hmax2bf(x2, x3));
      const float mx = fmaxf(bf_lo(m2), bf_hi(m2));
      float o0[4], o1[4];
#pragma unroll
      for (int i = 0; i < 10; i++) sv[i] = fmaf(mx, -SM_SCALE, sv[i]);
      sv[8] = ex2v(sv[8]); sv[9] = ex2v(sv[9]);
#pragma unroll
      for (int i = 0; i < 8; i++) sv[i] = ex2v(sv[i]);
      { const uint32_t p = pack_bf16(sv[8], sv[9]); mma16816z(o0, vm[0], p, p); mma16816z(o1, vm[1], p, p); }
      { const uint32_t p0 = pack_bf16(sv[0], sv[1]), p1 = pack_bf16(sv[2], sv[3]); mma16816(o0, vx[0], p0, p1); mma16816(o1, vx[2], p0, p1); }
      { const uint32_t p0 = pack_bf16(sv[4], sv[5]), p1 = pack_bf16(sv[6], sv[7]); mma16816(o0, vx[1], p0, p1); mma16816(o1, vx[3], p0, p1); }
      float su = (((sv[8] + sv[9]) + ((sv[0] + sv[1]) + (sv[2] + sv[3]))) + (sv[4] + sv[5])) + (sv[6] + sv[7]);
      { const float a1 = __shfl_xor_sync(~0u, su, 1), a2 = __shfl_xor_sync(~0u, su, 2), a3 = __shfl_xor_sync(~0u, su, 3); su = (su + a1) + (a2 + a3); }
      sts32(aU + 128, __float_as_uint(su));
      stsm4(aO, pack_bf16(o0[0], o0[1]), pack_bf16(o0[2], o0[3]), pack_bf16(o1[0], o1[1]), pack_bf16(o1[2], o1[3]));
      bar_sync(BAR_O, 384);
    }
    const uint32_t t0 = lds32(sb + C_R + 48);
    const uint4 xo = lds128(sb + C_T + 2048 + warp * 512 + lane * 16);
    const uint32_t tag = (s + args.layer + 1) & 1, tm = 0u - tag;
    if (warp == 3) {
      if (lane == 0) { LOGS(c, s); LOGV(c, 192 + (s >> 1), clk()); }
      spin_until(t0 + args.tc[0]);
      do_export(s, lane, true);
      if (lane == 0) LOG(c, 64 + s);
    }
    if (warp == 2) calib();
    if (warp < 2 || (warp == 2 && !(c & 16))) {
      const char* p = args.comm + xo.x; char* g2w = args.comm + xo.y;
      const uint32_t s0 = (lane & 8) ? 0u : xo.w, s1 = (lane & 8) ? xo.w : 0u;
      int lim = 0; bool bad;
      p += wait_until(t0 + args.ta[warp == 0 ? 0 : warp == 2 ? 3 : 1 + ((c >> 4) & 1)], lane >> 5);
      do {
        uint4 a[4]; float z0[4], z1[4], y[4];
#pragma unroll
        for (int i = 0; i < 4; i++) a[i] = ldg_rlx128(p + i * 512);
        ++lim;
        { const uint32_t A[4] = {a[0].x, a[0].y, a[0].z, a[0].w}; mma16816z(z0, A, s0, s1); }
        { const uint32_t A[4] = {a[1].x, a[1].y, a[1].z, a[1].w}; mma16816z(z1, A, s0, s1); }
        { const uint32_t A[4] = {a[2].x, a[2].y, a[2].z, a[2].w}; mma16816(z0, A, s0, s1); }
        { const uint32_t A[4] = {a[3].x, a[3].y, a[3].z, a[3].w}; mma16816(z1, A, s0, s1); }
        const uint32_t m0 = launder((a[0].x ^ tm) | (a[0].z ^ tm)), m1 = launder((a[1].x ^ tm) | (a[1].z ^ tm)), m2 = launder((a[2].x ^ tm) | (a[2].z ^ tm)), m3 = launder((a[3].x ^ tm) | (a[3].z ^ tm));
        bad = __any_sync(~0u, ((launder(m0 | m1 | m2) | m3) & 0x10000u) && lim < POLL_LIMIT);
#pragma unroll
        for (int i = 0; i < 4; i++) { y[i] = z0[i] + z1[i]; y[i] += __shfl_xor_sync(~0u, y[i], 16); }
        const uint32_t w0 = pack_tag(y[0], y[1], tag << 16), w1 = pack_bf16(y[2], y[3]);
        if (!bad) stg_rlx64(g2w, w0, w1);
      } while (bad);
      if (lane == 0 && warp == 0) LOGV(c, 128 + s, lim);
      if (lane == 0) { EV(warp, clk() - t0); EV(3 + warp, lim); }
    }
    prep(s + 1, lane);
    if (warp == 3) {
      const bool chk = !ph && !kv_all;
      const uint32_t* f = args.flags + F_KV + (lane < 2 ? 30 + lane : min((s + 2) >> 1, 31)) * 32 + h;
      if (chk) {
        uint32_t rdy; int n = 0;
        do rdy = ldg_rlx32(f); while (__any_sync(~0u, lane >= 2 && rdy < 2 && ++n < POLL_LIMIT));
        kv_all = __all_sync(~0u, rdy >= 2);
      }
      spin_until(t0 + args.tc[1]);
      if (chk) asm volatile("fence.acquire.gpu;" ::: "memory");
      if (s < 61) load_kv(sb, h, j, s + 2);
    }
    if (warp < 3) {
      constexpr uint32_t hg = 2048, hs = 5120;
      const char* p = args.comm + xo.z;
      const uint32_t aMw = sb + C_M + 2048 + warp * 1024 + lane * 8;
      int lim = 0; bool bad;
      p += wait_until(t0 + args.tb[warp + 1], lane >> 5);
      do { uint4 a[4]; uint32_t m = 0; ++lim;
#pragma unroll
        for (int i = 0; i < 4; i++) a[i] = ldg_rlx128(p + (i & 1) * 512 + (i >> 1) * hg);
#pragma unroll
        for (int i = 0; i < 4; i++) { const uint32_t q = aMw + (i & 1) * 256 + (i >> 1) * hs; sts64(q, a[i].x, a[i].z); sts64(q + 512, a[i].y, a[i].w); m |= (a[i].x ^ tm) | (a[i].z ^ tm); }
        bad = __any_sync(~0u, (m & 0x10000u) && lim < POLL_LIMIT);
      } while (bad);
      bar_arrive(BAR_M1 + warp, warp == 2 ? 352 : 288);
      if (lane == 0) { EV(6 + warp, clk() - t0); EV(9 + warp, lim); }
    }
  }
}

#define PDLAT 2
#define NPROBE 3
#define OPACE 400
constexpr int G_ST = 163840;
constexpr int B_FULL = 64, B_EMPTY = 96, B_WD = 136, B_ROLE = 144, B_PROG = 148, B_WF = 160  ;
enum { BAR_T = 1  , BAR_G = 3  , BAR_V = 5   };
DEVINL uint64_t mkdesc(uint32_t a, uint32_t lbo, uint32_t sbo, uint32_t sw) { return (uint64_t)((a & 0x3FFFF) >> 4) | ((uint64_t)(lbo >> 4) << 16) | ((uint64_t)(sbo >> 4) << 32) | ((uint64_t)sw << 62); }
DEVINL void wgmma_n128(float* d, uint64_t a, uint64_t b, int acc) {
  asm volatile("{.reg .pred p; setp.ne.b32 p, %66, 0; wgmma.mma_async.sync.aligned.m64n128k16.f32.bf16.bf16 {%0,%1,%2,%3,%4,%5,%6,%7,%8,%9,%10,%11,%12,%13,%14,%15,%16,%17,%18,%19,%20,%21,%22,%23,%24,%25,%26,%27,%28,%29,%30,%31,%32,%33,%34,%35,%36,%37,%38,%39,%40,%41,%42,%43,%44,%45,%46,%47,%48,%49,%50,%51,%52,%53,%54,%55,%56,%57,%58,%59,%60,%61,%62,%63}, %64, %65, p, 1, 1, 0, 1;}"
               : "+f"(d[0]),"+f"(d[1]),"+f"(d[2]),"+f"(d[3]),"+f"(d[4]),"+f"(d[5]),"+f"(d[6]),"+f"(d[7]),"+f"(d[8]),"+f"(d[9]),"+f"(d[10]),"+f"(d[11]),"+f"(d[12]),"+f"(d[13]),"+f"(d[14]),"+f"(d[15]),"+f"(d[16]),"+f"(d[17]),"+f"(d[18]),"+f"(d[19]),"+f"(d[20]),"+f"(d[21]),"+f"(d[22]),"+f"(d[23]),"+f"(d[24]),"+f"(d[25]),"+f"(d[26]),"+f"(d[27]),"+f"(d[28]),"+f"(d[29]),"+f"(d[30]),"+f"(d[31]),"+f"(d[32]),"+f"(d[33]),"+f"(d[34]),"+f"(d[35]),"+f"(d[36]),"+f"(d[37]),"+f"(d[38]),"+f"(d[39]),"+f"(d[40]),"+f"(d[41]),"+f"(d[42]),"+f"(d[43]),"+f"(d[44]),"+f"(d[45]),"+f"(d[46]),"+f"(d[47]),"+f"(d[48]),"+f"(d[49]),"+f"(d[50]),"+f"(d[51]),"+f"(d[52]),"+f"(d[53]),"+f"(d[54]),"+f"(d[55]),"+f"(d[56]),"+f"(d[57]),"+f"(d[58]),"+f"(d[59]),"+f"(d[60]),"+f"(d[61]),"+f"(d[62]),"+f"(d[63]) : "l"(a), "l"(b), "r"(acc));
}
DEVINL void wgmma_n80(float* d, uint64_t a, uint64_t b, int acc) {
  asm volatile("{.reg .pred p; setp.ne.b32 p, %42, 0; wgmma.mma_async.sync.aligned.m64n80k16.f32.bf16.bf16 {%0,%1,%2,%3,%4,%5,%6,%7,%8,%9,%10,%11,%12,%13,%14,%15,%16,%17,%18,%19,%20,%21,%22,%23,%24,%25,%26,%27,%28,%29,%30,%31,%32,%33,%34,%35,%36,%37,%38,%39}, %40, %41, p, 1, 1, 0, 1;}"
               : "+f"(d[0]),"+f"(d[1]),"+f"(d[2]),"+f"(d[3]),"+f"(d[4]),"+f"(d[5]),"+f"(d[6]),"+f"(d[7]),"+f"(d[8]),"+f"(d[9]),"+f"(d[10]),"+f"(d[11]),"+f"(d[12]),"+f"(d[13]),"+f"(d[14]),"+f"(d[15]),"+f"(d[16]),"+f"(d[17]),"+f"(d[18]),"+f"(d[19]),"+f"(d[20]),"+f"(d[21]),"+f"(d[22]),"+f"(d[23]),"+f"(d[24]),"+f"(d[25]),"+f"(d[26]),"+f"(d[27]),"+f"(d[28]),"+f"(d[29]),"+f"(d[30]),"+f"(d[31]),"+f"(d[32]),"+f"(d[33]),"+f"(d[34]),"+f"(d[35]),"+f"(d[36]),"+f"(d[37]),"+f"(d[38]),"+f"(d[39]) : "l"(a), "l"(b), "r"(acc));
}

template <int N, int NST, bool HAND>
DEVINL void gemm_tile(float* acc, uint32_t sb, uint32_t px, int wg, uint32_t u0, int rot, bool lead, int wph) {
  const uint64_t db = N == 128 ? mkdesc(sb, 81920, 1024, 1) : mkdesc(sb, 32768, 256, 3);
#pragma unroll
  for (int i = 0; i < N / 2; i++) acc[i] = 0.f;
  bar_sync(BAR_T + wg, 256);
#pragma unroll 1
  for (int st = 0; st < NST; st++) {
    const uint32_t u = u0 + st, slot = u & 3, ks = (st + rot >= NST ? st + rot - NST : st + rot) * 8;
    if (wph >= 0) mbar_wait(sb + S_BAR + B_WF + (N == 128 ? st * 8 : 0), wph);
    mbar_wait(sb + S_BAR + B_FULL + slot * 8, (u >> 2) & 1);
    const uint64_t da = mkdesc(sb + G_ST + slot * 16384, 16, 1024, 1);
    asm volatile("wgmma.fence.sync.aligned;" ::: "memory");
#pragma unroll
    for (int k = 0; k < 8; k++) {
      const uint64_t a = da + (k >> 2) * 512 + (k & 3) * 2;
      if (N == 128) wgmma_n128(acc, a, db + (ks + k) * 128, 1); else wgmma_n80(acc, a, db + (ks + k) * 32, 1);
    }
    asm volatile("wgmma.commit_group.sync.aligned;" ::: "memory");
    if (HAND && st == NST - 1) bar_arrive(BAR_T + (wg ^ 1), 256);
    if (st > 0) {
      asm volatile("wgmma.wait_group.sync.aligned 1;" ::: "memory");
      if (lead) { const uint32_t e = sb + S_BAR + B_EMPTY + ((u - 1) & 3) * 8; mbar_arrive(e); mbar_arrive_remote(e + px); }
    }
  }
  asm volatile("wgmma.wait_group.sync.aligned 0;" ::: "memory");
  if (lead) { const uint32_t e = sb + S_BAR + B_EMPTY + ((u0 + NST - 1) & 3) * 8; mbar_arrive(e); mbar_arrive_remote(e + px); }
}
DEVINL void wg_publish(int wg) { bar_sync(BAR_G + wg, 160); }
DEVINL uint32_t km_known(uint32_t sb) { uint32_t v; asm volatile("ld.volatile.shared.u32 %0, [%1];" : "=r"(v) : "r"(sb + S_BAR + B_PROG) : "memory"); return __reduce_min_sync(~0u, v); }
DEVINL void km_load(uint4* f, const char* p) {
#pragma unroll
  for (int G = 0; G < 4; G++) f[G] = ldg_rlx128(p + G * 512);
}
DEVINL void km_check(uint4* f, const char* p, uint32_t tg) {
  int n = 0;
  while (__any_sync(~0u, (((f[0].x ^ tg) | (f[0].z ^ tg) | (f[1].x ^ tg) | (f[1].z ^ tg) | (f[2].x ^ tg) | (f[2].z ^ tg) | (f[3].x ^ tg) | (f[3].z ^ tg)) & 0x10000u) && ++n < POLL_LIMIT)) km_load(f, p);
}
DEVINL void km_watcher(uint32_t sb, const uint32_t* p) {
  uint32_t v = 0;
#pragma unroll 1
  for (int n = 0; n < 16 * POLL_LIMIT && v < 64; n++) {
    const uint2 q = ldg_rlx64(p);
    if (min(q.x, q.y) != v) { v = min(q.x, q.y); asm volatile("st.volatile.shared.u32 [%0], %1;" ::"r"(sb + S_BAR + B_PROG), "r"(v) : "memory"); }
    __nanosleep(v < 61 ? 300 : 20);
  }
}

template <int HF>
DEVINL void attend(const float* acc, uint4 (*kf)[4], uint4* kmf, uint4* op, const char* kvp, const char* mp, bf16* orow, int lane, int wg, uint32_t sb, int tile, bool& pend, uint32_t tg) {
  constexpr int NT = HF ? 4 : 2;
  const int g = lane >> 2, t = lane & 3;
  km_check(kmf, mp + lane * 16, tg);
  float sc[NT + 1][4];
#pragma unroll
  for (int k = 0; k < 8; k++) {
    uint32_t qa[4];
#pragma unroll
    for (int i = 0; i < 4; i++) { const float* a = acc + 32 * (k >> 2) + 4 * (k & 3) + 16 * (i >> 1) + 2 * (i & 1); qa[i] = pack_bf16(a[0], a[1]); }
#pragma unroll
    for (int kt = 0; kt <= NT; kt++) {
      const uint4 b = kt < NT ? kf[kt][k >> 1] : kmf[k >> 1];
      if (k == 0) mma16816z(sc[kt], qa, b.x, b.y); else if (k & 1) mma16816(sc[kt], qa, b.z, b.w); else mma16816(sc[kt], qa, b.x, b.y);
    }
  }
  FEN();
  bar_arrive(BAR_T + (wg ^ 1), 256);
  if (pend) {
#pragma unroll
    for (int q = 0; q < 4; q++) { *(uint4*)(orow - 128 * 4096 + q * 32) = op[2 * q]; *(uint4*)(orow - 120 * 4096 + q * 32) = op[2 * q + 1]; }
    wg_publish(wg);
  }
  {
    uint32_t go; asm volatile("{.reg .pred p,q; setp.ne.u32 q, %1, 0; bar.red.and.pred p, %2, 128, q; selp.u32 %0, 1, 0, p;}" : "=r"(go) : "r"((uint32_t)(tile < 30 && km_known(sb) > tile * 2 + 5)), "r"(BAR_V + wg) : "memory");
    pend = __reduce_max_sync(~0u, go); }
  uint4 vf[HF + 1][8], vm[4];
  const char* vp = kvp + 4096 + (g >> 1) * 512 + ((g & 1) * 4 + t) * 16;
  km_load(vm, mp + 2048 + lane * 16);
#pragma unroll
  for (int i = 0; i < 8; i++) vf[0][i] = ldg_ca128(vp + (i >> 2) * 4096 + (i & 3) * 128);
  if (tile < 30) {
#pragma unroll
    for (int i = 0; i < 8; i++) kf[i >> 2][i & 3] = ldg_ca128(kvp + 4 * 32 * 16384 + ((i >> 1) & 1) * 12288 + (i >> 2) * 1024 + (i & 1) * 512 + lane * 16);
  }
  if (pend) km_load(kmf, mp + 4 * 32 * 4096 + lane * 16);
  if (HF) {
#pragma unroll
    for (int i = 0; i < 8; i++) vf[HF][i] = ldg_cg128(vp + 2048 + (i >> 2) * 4096 + (i & 3) * 128);
    if (tile < 30) {
#pragma unroll
      for (int i = 8; i < 16; i++) kf[i >> 2][i & 3] = ldg_cg128(kvp + 4 * 32 * 16384 + ((i >> 1) & 1) * 12288 + (i >> 2) * 1024 + (i & 1) * 512 + lane * 16);
    }
  }
  const float NINF = __int_as_float(0xff800000);
  if (2 * t > g) { sc[NT - 2][0] = NINF; sc[NT - 1][2] = NINF; }
  if (2 * t + 1 > g) { sc[NT - 2][1] = NINF; sc[NT - 1][3] = NINF; }
  sc[NT - 1][0] = NINF; sc[NT - 1][1] = NINF;
  float m0 = fmaxf(sc[NT][0], sc[NT][1]), m1 = fmaxf(sc[NT][2], sc[NT][3]);
#pragma unroll
  for (int kt = 0; kt < NT; kt++) { m0 = fmaxf(m0, fmaxf(sc[kt][0], sc[kt][1])); m1 = fmaxf(m1, fmaxf(sc[kt][2], sc[kt][3])); }
  m0 = fmaxf(fmaxf(m0, __shfl_xor_sync(~0u, m0, 1)), fmaxf(__shfl_xor_sync(~0u, m0, 2), __shfl_xor_sync(~0u, m0, 3)));
  m1 = fmaxf(fmaxf(m1, __shfl_xor_sync(~0u, m1, 1)), fmaxf(__shfl_xor_sync(~0u, m1, 2), __shfl_xor_sync(~0u, m1, 3)));
  m0 *= -SM_SCALE; m1 *= -SM_SCALE;
  float s0 = 0.f, s1 = 0.f; uint32_t p[NT + 1][2];
#pragma unroll
  for (int kt = 0; kt <= NT; kt++) {
    const float a = ex2(fmaf(sc[kt][0], SM_SCALE, m0)), b = ex2(fmaf(sc[kt][1], SM_SCALE, m0)), c = ex2(fmaf(sc[kt][2], SM_SCALE, m1)), d = ex2(fmaf(sc[kt][3], SM_SCALE, m1));
    s0 += a + b; s1 += c + d; p[kt][0] = pack_bf16(a, b); p[kt][1] = pack_bf16(c, d);
  }
  s0 = (s0 + __shfl_xor_sync(~0u, s0, 1)) + (__shfl_xor_sync(~0u, s0, 2) + __shfl_xor_sync(~0u, s0, 3));
  s1 = (s1 + __shfl_xor_sync(~0u, s1, 1)) + (__shfl_xor_sync(~0u, s1, 2) + __shfl_xor_sync(~0u, s1, 3));
  s0 = rcp(s0); s1 = rcp(s1);
  km_check(vm, mp + 2048 + lane * 16, tg);
#pragma unroll
  for (int grp = 0; grp < 4; grp++) {
    float o[4][4];
#pragma unroll
    for (int L = 0; L < 4; L++) {
      mma1688z(o[L], p[NT][0], p[NT][1], L == 0 ? vm[grp].x : L == 1 ? vm[grp].y : L == 2 ? vm[grp].z : vm[grp].w);
#pragma unroll
      for (int kh = 0; kh <= HF; kh++) {
        const uint4 w = vf[kh][(grp >> 1) * 4 + L]; const uint32_t A[4] = {p[2 * kh][0], p[2 * kh][1], p[2 * kh + 1][0], p[2 * kh + 1][1]};
        if (grp & 1) mma16816(o[L], A, w.z, w.w); else mma16816(o[L], A, w.x, w.y);
      }
    }
    op[2 * grp] = make_uint4(pack_bf16(o[0][0] * s0, o[0][1] * s0), pack_bf16(o[1][0] * s0, o[1][1] * s0), pack_bf16(o[2][0] * s0, o[2][1] * s0), pack_bf16(o[3][0] * s0, o[3][1] * s0));
    op[2 * grp + 1] = make_uint4(pack_bf16(o[0][2] * s1, o[0][3] * s1), pack_bf16(o[1][2] * s1, o[1][3] * s1), pack_bf16(o[2][2] * s1, o[2][3] * s1), pack_bf16(o[3][2] * s1, o[3][3] * s1));
  }
}

DEVINL void gemm_consumer(uint32_t sb, uint32_t px, int wg, int pr, int rank, const ArgsA& args) {
  const int lane = opaque(threadIdx.x & 31), w = __reduce_max_sync(~0u, (threadIdx.x >> 5) & 3);
  const bool lead = lane == 0 && w == 0;
  const int rot5 = pr % 5;
  if (wg == 1) bar_arrive(BAR_T, 256);
  if (threadIdx.x == 0) LOG(64 + pr * 2 + rank, 250);
#pragma unroll 1
  for (int tile = wg; tile < 32; tile += 2) {
    float acc[64];
    gemm_tile<128, 5, true>(acc, sb, px, wg, tile * 5, rot5, lead, tile < 2 ? 0 : -1);
    if (tile >= 30 && lead) mbar_arrive(sb + S_BAR + B_WD);
    char* dst = g_kv + (size_t)((tile * 2 + (w >> 1)) * 32 + pr) * 16384 + (w & 1) * 2048 + lane * 16;
    if (rank == 0) {
#pragma unroll
      for (int G = 0; G < 4; G++)
#pragma unroll
        for (int hh = 0; hh < 2; hh++) {
          const float* a = acc + 32 * (G >> 1) + 8 * (G & 1) + 2 * hh;
          *(uint4*)(dst + (G >> 1) * 12288 + hh * 1024 + (G & 1) * 512) = make_uint4(pack_bf16(a[0], a[1]), pack_bf16(a[16], a[17]), pack_bf16(a[4], a[5]), pack_bf16(a[20], a[21]));
        }
    } else {
#pragma unroll
      for (int i = 0; i < 8; i++) {
        const float* a = acc + (i >> 2) * 32 + (i & 3) * 4;
        *(uint4*)(dst + 4096 + (i >> 2) * 4096 + (i & 3) * 512) = make_uint4(movm(pack_bf16(a[0], a[1])), movm(pack_bf16(a[2], a[3])), movm(pack_bf16(a[16], a[17])), movm(pack_bf16(a[18], a[19])));
      }
    }
    wg_publish(wg);
    if ((threadIdx.x & 127) == 0) LOG(64 + pr * 2 + rank, tile);
  }
  if (threadIdx.x == 0) LOG(64 + pr * 2 + rank, 251);
  if (pr < 16) {
    const int h = 2 * pr + rank;
    flag_wait_warp(args.flags + F_KV + (16 + (lane & 1)) * 32 + h, 2);
    bool pend = false; uint4 op[8], kf[4][4], kmf[4];
#pragma unroll
    for (int i = 0; i < 16; i++) kf[i >> 2][i & 3] = ldg_cg128(g_kv + (size_t)((wg * 2 + (w >> 1)) * 32 + h) * 16384 + ((i >> 1) & 1) * 12288 + (i >> 2) * 1024 + (i & 1) * 512 + lane * 16);
#pragma unroll
    for (int i = 0; i < 8; i++) op[i] = kmf[i & 3] = make_uint4(0, 0, 0, 0);
#pragma unroll 1
    for (int tile = wg; tile < 32; tile += 2) {
      const uint32_t seg = tile * 2 + (w >> 1);
      const char* kvp = g_kv + (size_t)(seg * 32 + h) * 16384;
      const char* mp = g_kvm + (size_t)(seg * 32 + h) * 4096;
      bf16* orow = g_o + (size_t)(tile * 64 + w * 16 + (lane >> 2)) * 4096 + h * 128 + (lane & 3) * 8;
      if ((tile >> 1) == 6) flag_wait_warp(args.flags + F_KV + (30 + (lane & 1)) * 32 + h, 2);
      float acc[64];
      gemm_tile<128, 5, false>(acc, sb, px, wg, 160 + tile * 5, rot5, lead, tile < 2 ? 1 : -1);
      if ((threadIdx.x & 127) == 96) LOG(64 + pr * 2 + rank, 64 + tile);
      if (!pend) {
        int n = 0;
        while (km_known(sb) <= seg && ++n < 16 * POLL_LIMIT) {}
        km_load(kmf, mp + lane * 16);
      }
      if ((threadIdx.x & 127) == 96) LOG(64 + pr * 2 + rank, 96 + tile);
      if (w & 1) attend<1>(acc, kf, kmf, op, kvp, mp, orow, lane, wg, sb, tile, pend, (args.layer ^ 1) << 16); else attend<0>(acc, kf, kmf, op, kvp, mp, orow, lane, wg, sb, tile, pend, (args.layer ^ 1) << 16);
      if (!pend) {
#pragma unroll
        for (int q = 0; q < 4; q++) { *(uint4*)(orow + q * 32) = op[2 * q]; *(uint4*)(orow + 8 * 4096 + q * 32) = op[2 * q + 1]; }
        wg_publish(wg);
      }
      if ((threadIdx.x & 127) == 0) LOG(64 + pr * 2 + rank, 32 + tile);
    }
  } else {
    const int kq = (pr - 16) >> 2, cg = 2 * (pr & 3) + rank;
#pragma unroll 1
    for (int tile = wg; tile < 32; tile += 2) {
      float acc[40];
      gemm_tile<80, 8, true>(acc, sb, px, wg, 160 + tile * 8, (pr & 3) * 2, lead, tile < 2 ? 1 : -1);
      const bool odd = lane & 1;
      bf16* dst = g_part + (size_t)(kq * 2048 + tile * 64 + w * 16 + (lane >> 2)) * 640 + cg * 80 + (lane & 1) * 8 + (lane & 2) * 2;
#pragma unroll
      for (int q = 0; q < 5; q++)
#pragma unroll
        for (int hh = 0; hh < 2; hh++) {
          const uint32_t A = pack_bf16(acc[8 * q + 2 * hh], acc[8 * q + 2 * hh + 1]), B = pack_bf16(acc[8 * q + 4 + 2 * hh], acc[8 * q + 5 + 2 * hh]);
          const uint32_t x = __shfl_xor_sync(~0u, odd ? A : B, 1);
          *(uint2*)(dst + hh * 8 * 640 + q * 16) = odd ? make_uint2(x, B) : make_uint2(A, x);
        }
      wg_publish(wg);
      if ((threadIdx.x & 127) == 0) LOG(64 + pr * 2 + rank, 32 + tile);
    }
  }
  if (wg == 0) bar_sync(BAR_T, 256);
}

DEVINL void gemm_producer(uint32_t sb, int pr, int rank, const ArgsA& args, const CUtensorMap* tq, const CUtensorMap* tk, const CUtensorMap* tv,
                          const CUtensorMap* to32, const CUtensorMap* tx, const CUtensorMap* tao) {
  const uint32_t bWF = sb + S_BAR + B_WF;
  auto load_w = [&](const CUtensorMap* tm, int col, int st) {
    const int r = ((st + pr) % 5) * 2; mbar_arrive_tx(bWF + st * 8, 32768);
#pragma unroll 1
    for (int i = 0; i < 4; i++) tma_2d(sb + (i & 1) * 81920 + (r + (i >> 1)) * 8192, tm, col + (i & 1) * 64, (r + (i >> 1)) * 64, bWF + st * 8); };
  uint32_t u = 0;
  auto push = [&](const CUtensorMap* tm, int c0, int c1) {
    const uint32_t slot = u & 3, full = sb + S_BAR + B_FULL + slot * 8;
    mbar_wait(sb + S_BAR + B_EMPTY + slot * 8, ((u >> 2) & 1) ^ 1);
    mbar_arrive_tx(full, 16384);
    tma_2d_mc(sb + G_ST + slot * 16384 + rank * 8192, tm, c0 + rank * 64, c1, full);
    u++; };
#pragma unroll 1
  for (int st = 0; st < 5; st++) load_w(rank ? tv : tk, pr * 128, st);
  if (args.layer == 0) { flag_wait(args.flags + F_X, 128); fence_proxy_async(); } else pdl_wait();
#pragma unroll 1
  for (int tile = 0; tile < 32; tile++) {
    l2_prefetch((const char*)g_xn + ((tile + 2) & 31) * 81920 + (pr * 2 + rank) * 1280, 1280);
    if (tile >= 20 && tile < 30) l2_prefetch((rank ? args.wo : args.wq) + (pr * 10 + tile - 20) * 16384, 16384);
#pragma unroll 1
    for (int st = 0; st < 5; st++) push(tx, ((st + pr) % 5) * 128, tile * 64);
  }
  pdl_launch();
  if (pr < 16) {
    load_w(tq, (2 * pr + rank) * 128, 0);
#pragma unroll 1
    for (int tile = 0; tile < 32; tile++) {
      if (tile < 30) {
        l2_prefetch((const char*)g_xn + (tile + 2) * 81920 + (pr * 2 + rank) * 2560, 2560);
        const int q = (tile * 2 + 4) * 32 + 2 * pr + rank;
        l2_prefetch(g_kv + (size_t)q * 16384, 16384); l2_prefetch(g_kv + (size_t)(q + 32) * 16384, 16384);
        if (lds32(sb + S_BAR + B_PROG) > tile * 2 + 5) { l2_prefetch(g_kvm + (size_t)q * 4096, 4096); l2_prefetch(g_kvm + (size_t)(q + 32) * 4096, 4096); }
      }
#pragma unroll 1
      for (int st = 0; st < 5; st++) { push(tx, ((st + pr) % 5) * 128, tile * 64); if (tile == 0 && st < 4) load_w(tq, (2 * pr + rank) * 128, st + 1); }
    }
  } else {
    const int kq = (pr - 16) >> 2, cg = 2 * (pr & 3) + rank;
    mbar_wait(sb + S_BAR + B_WD, 0);
    mbar_arrive_tx(bWF, 163840);
#pragma unroll 1
    for (int i = 0; i < 20; i++) { tma_2d(sb + (i % 5) * 32768 + (i / 5) * 8192, to32, cg * 80 + (i % 5) * 16, kq * 1024 + (i / 5) * 256, bWF); __nanosleep(OPACE); }
#pragma unroll 1
    for (int tile = 0; tile < 32; tile++) {
      flag_wait(args.flags + F_O + tile * 4 + kq, 8);
      fence_proxy_async();
#pragma unroll 1
      for (int st = 0; st < 8; st++) push(tao, kq * 1024 + ((st + (pr & 3) * 2) & 7) * 128, tile * 64);
    }
  }
#pragma unroll 1
  for (int i = 0; i < 4; i++, u++) mbar_wait(sb + S_BAR + B_EMPTY + (u & 3) * 8, ((u >> 2) & 1) ^ 1);
}

DEVINL void gemm_publisher(int wg, int pr, int rank, const ArgsA& args) {
#pragma unroll 1
  for (int i = 0; i < 32; i++) {
    const int tile = (i & 15) * 2 + wg;
    bar_sync(BAR_G + wg, 160);
    if ((threadIdx.x & 31) == 0) {
      flag_add(args.flags + (i < 16 ? F_KV + tile * 32 + pr : pr < 16 ? F_O + tile * 4 + (pr >> 2) : F_P + tile * 32));
    }
    __syncwarp();
  }
}

DEVINL void filter_prep(uint32_t* sm, int part, const ArgsA& args) {
  const int tid = threadIdx.x, lane = tid & 31, w = tid >> 5;
  const unsigned short* wr = (const unsigned short*)args.wr; const unsigned short* wi = (const unsigned short*)args.wi;
#pragma unroll 1
  for (int it = part; it < 32; it += 4) {
#pragma unroll 1
    for (int rr = 0; rr < 8; rr += 2) {
      uint32_t a[2][11], b[2][11];
#pragma unroll
      for (int r = 0; r < 2; r++) {
        const int pos = it * 64 + w * 8 + rr + r, th = (pos >> 2) & 127, v = (pos >> 9) * 4 + (pos & 3);
        const int o = ((th >> 3) + 16 * ((th & 7) + (v & 8)) + 256 * (v & 7)) * 321 + lane;
#pragma unroll
        for (int c = 0; c < 11; c++) if (c < 10 || lane == 0) { a[r][c] = wr[o + c * 32]; b[r][c] = wi[o + c * 32]; }
      }
#pragma unroll
      for (int r = 0; r < 2; r++)
#pragma unroll
        for (int c = 0; c < 11; c++) if (c < 10 || lane == 0) sm[(c * 32 + lane) * 65 + w * 8 + rr + r] = a[r][c] | (b[r][c] << 16);
    }
    bar_sync(1, 256);
#pragma unroll 2
    for (int i = tid; i < 64 * 321; i += 256) g_wt[(i >> 6) * 2048 + it * 64 + (i & 63)] = sm[(i >> 6) * 65 + (i & 63)];
    bar_sync(1, 256);
  }
}

__global__ void __cluster_dims__(2, 1, 1) __launch_bounds__(384, 1)
layer_a_kernel(const __grid_constant__ CUtensorMap tq, const __grid_constant__ CUtensorMap tk, const __grid_constant__ CUtensorMap tv,
               const __grid_constant__ CUtensorMap to, const __grid_constant__ CUtensorMap to32, const __grid_constant__ CUtensorMap tx,
               const __grid_constant__ CUtensorMap tao, const __grid_constant__ ArgsA args) {
  extern __shared__ __align__(1024) char smraw[];
  const uint32_t sb = (smem_u32(smraw) + 1023) & ~1023u;
  uint32_t rank; asm volatile("mov.u32 %0, %%cluster_ctarank;" : "=r"(rank));
  rank = __reduce_max_sync(~0u, rank);
  const uint32_t px = __reduce_max_sync(~0u, mapa(sb, rank ^ 1) - sb);
  if (PDLAT == 0) pdl_launch();
  if (args.layer == 0) LOGK(0, 0);
  uint32_t smid; asm volatile("mov.u32 %0, %%smid;" : "=r"(smid));
  if (threadIdx.x >= 256) {
    const uint32_t b = sb + S_BAR;
    if (threadIdx.x == 320) {
      mbar_init(b + B_W, 1); mbar_init(b + B_W2, 1); mbar_init(b + B_WV, 1); mbar_init(b + B_WO, 1); mbar_init(b + B_S, 9); mbar_init(b + B_KV, 1); mbar_init(b + B_KV + 8, 1);
      for (int i = 0; i < 4; i++) { mbar_init(b + B_FULL + i * 8, 1); mbar_init(b + B_EMPTY + i * 8, 2); }
      for (int i = 0; i < 5; i++) mbar_init(b + B_WF + i * 8, 1);
      mbar_init(b + B_WD, 2); sts32(b + B_PROG, 0);
      asm volatile("fence.mbarrier_init.release.cluster;" ::: "memory");
    }
    if (rank == 0 && threadIdx.x < 320) {
      if (args.layer == 0) {
        uint32_t* p = (uint32_t*)(args.comm + 0x20000 + (threadIdx.x < 288 ? 0x1000 : 0) + (blockIdx.x >> 1) * 32);
        if ((threadIdx.x & 31) < 8) p[threadIdx.x & 31] = 0;
        __syncwarp();
        if ((threadIdx.x & 31) == 0) {
          uint32_t v, best = ~0u;
#pragma unroll 1
          for (int i = 0; i < NPROBE; i++) { const uint32_t t0 = clk(); asm volatile("atom.relaxed.gpu.global.add.u32 %0, [%1], 1;" : "=r"(v) : "l"(p) : "memory"); asm volatile("st.volatile.shared.u32 [%0], %1;" ::"r"(b + 208), "r"(v) : "memory"); best = min(best, clk() - t0); }
          sts32(b + 200 + ((threadIdx.x >> 5) & 1) * 4, best);
        }
        bar_sync(1, 64);
      }
      if (threadIdx.x == 256) {
        int d;
        if (args.layer == 0) { d = (int)(lds32(b + 200) - lds32(b + 204)); g_side[smid & 254] = d; g_side[(smid & 254) + 1] = d; } else d = g_side[smid & 255];
        uint32_t* cnt = args.flags + F_ROLE; uint32_t role;
        if (d < 0) { role = atomicAdd(cnt, 1); if (role >= 32) role = 32 + atomicAdd(cnt + 1, 1); }
        else { role = 32 + atomicAdd(cnt + 1, 1); if (role >= 66) role = atomicAdd(cnt, 1); }
        sts32(b + B_ROLE, role);
      }
    }
  } else if (args.layer == 0 && blockIdx.x < 128) {
    const size_t off = (size_t)(blockIdx.x * 16 + (threadIdx.x >> 4)) * 640 + (threadIdx.x & 15) * 8;
    float f[40];
#pragma unroll
    for (int i = 0; i < 5; i++) unpack8(*(const uint4*)(args.x + off + i * 128), f + 8 * i);
    ln_row(f);
#pragma unroll
    for (int i = 0; i < 5; i++) *(uint4*)(g_xn + off + i * 128) = pack8(f + 8 * i);
  }
  __syncthreads();
  asm volatile("barrier.cluster.arrive.release.aligned;" ::: "memory");
  if (threadIdx.x == 0 && args.layer == 0 && blockIdx.x < 128) flag_add(args.flags + F_X);
  __syncwarp();
  asm volatile("barrier.cluster.wait.acquire.aligned;" ::: "memory");
  uint32_t role; asm volatile("ld.shared::cluster.u32 %0, [%1];" : "=r"(role) : "r"(sb + S_BAR + B_ROLE + (rank ? px : 0)) : "memory");
  role = __reduce_max_sync(~0u, role);
  if (PDLAT == 1 || (PDLAT == 2 && role != 32)) pdl_launch();
  if (role >= 64) cluster_sync();
  const int wg = __reduce_max_sync(~0u, threadIdx.x >> 7);
  auto U = [](uint32_t x) { return __reduce_max_sync(~0u, opaque(x)); };
  if (wg < 2) {
    asm volatile("setmaxnreg.inc.sync.aligned.u32 224;");
    if (role >= 32) {
      if (role >= 64) { if (args.layer == 0) { filter_prep((uint32_t*)smraw, (role - 64) * 2 + rank, args); if (threadIdx.x == 0) LOG(role * 2 + rank, 0); } }
      else gemm_consumer(U(sb), U(px), U(wg), U(role - 32), U(rank), args);
    } else { if (wg == 0) chain_mma<0>(sb, args); else chain_mma<1>(sb, args); }
  } else {
    asm volatile("setmaxnreg.dec.sync.aligned.u32 56;");
    if (role >= 32) {
      if (role < 64) {
        if (threadIdx.x == 256) gemm_producer(sb, role - 32, rank, args, &tq, &tk, &tv, &to32, &tx, &tao);
        else if (threadIdx.x >= 288 && threadIdx.x < 352) gemm_publisher((threadIdx.x >> 5) - 9, role - 32, rank, args);
        else if (threadIdx.x == 352 && role < 48) km_watcher(sb, args.flags + F_KM + (2 * (role - 32) + rank) * 32);
      }
    } else chain_helper(U(sb), U(px), U(role), U(rank), args, &tq, &tk, &tv, &to);
  }
}

DEVINL float2 cadd(float2 a, float2 b) { return make_float2(a.x + b.x, a.y + b.y); }
DEVINL float2 csub(float2 a, float2 b) { return make_float2(a.x - b.x, a.y - b.y); }
DEVINL float2 cmul(float2 a, float2 b) { return make_float2(fmaf(a.x, b.x, -a.y * b.y), fmaf(a.x, b.y, a.y * b.x)); }
DEVINL float2 cmulc(float2 a, float2 b) { return make_float2(fmaf(a.x, b.x, a.y * b.y), fmaf(a.y, b.x, -a.x * b.y)); }
template <int INV> DEVINL float2 ctw(float2 a, float2 w) { return INV ? cmulc(a, w) : cmul(a, w); }
template <int INV> DEVINL float2 rot(float2 a) { return INV ? make_float2(-a.y, a.x) : make_float2(a.y, -a.x); }
template <int INV> DEVINL void fft4(float2& a, float2& b, float2& c, float2& d) {
  const float2 s0 = cadd(a, c), d0 = csub(a, c), s1 = cadd(b, d), d1 = rot<INV>(csub(b, d));
  a = cadd(s0, s1); b = cadd(d0, d1); c = csub(s0, s1); d = csub(d0, d1);
}
template <int INV> DEVINL float2 w8(float2 a) { const float h = 0.70710678118654752f; const float2 r = rot<INV>(a); return make_float2((a.x + r.x) * h, (a.y + r.y) * h); }
template <int INV> DEVINL void fft8(float2* x) {
  fft4<INV>(x[0], x[2], x[4], x[6]); fft4<INV>(x[1], x[3], x[5], x[7]);
  const float2 e0 = x[0], e1 = x[2], e2 = x[4], e3 = x[6], o0 = x[1], o1 = w8<INV>(x[3]), o2 = rot<INV>(x[5]), o3 = rot<INV>(w8<INV>(x[7]));
  x[0] = cadd(e0, o0); x[1] = cadd(e1, o1); x[2] = cadd(e2, o2); x[3] = cadd(e3, o3);
  x[4] = csub(e0, o0); x[5] = csub(e1, o1); x[6] = csub(e2, o2); x[7] = csub(e3, o3);
}
template <int INV> DEVINL void fft16(float2* x) {
  const float c = 0.92387953251128674f, s = 0.38268343236508977f;
  const float2 w1 = make_float2(c, -s), w3 = make_float2(s, -c);
#pragma unroll
  for (int i = 0; i < 4; i++) fft4<INV>(x[i], x[i + 4], x[i + 8], x[i + 12]);
  x[5] = ctw<INV>(x[5], w1); x[9] = w8<INV>(x[9]); x[13] = ctw<INV>(x[13], w3);
  x[6] = w8<INV>(x[6]); x[10] = rot<INV>(x[10]); x[14] = rot<INV>(w8<INV>(x[14]));
  x[7] = ctw<INV>(x[7], w3); x[11] = rot<INV>(w8<INV>(x[11])); x[15] = ctw<INV>(x[15], make_float2(-c, s));
#pragma unroll
  for (int k = 0; k < 4; k++) fft4<INV>(x[4 * k], x[4 * k + 1], x[4 * k + 2], x[4 * k + 3]);
#pragma unroll
  for (int k = 0; k < 4; k++)
#pragma unroll
    for (int m = k + 1; m < 4; m++) { const float2 t = x[4 * k + m]; x[4 * k + m] = x[4 * m + k]; x[4 * m + k] = t; }
}
template <int INV> DEVINL void fft5(float2& x0, float2& x1, float2& x2, float2& x3, float2& x4) {
  const float c1 = 0.30901699437494742f, c2 = -0.80901699437494742f, s1 = 0.95105651629515357f, s2 = 0.58778525229247313f;
  const float2 a1 = cadd(x1, x4), a2 = cadd(x2, x3), b1 = rot<INV>(csub(x1, x4)), b2 = rot<INV>(csub(x2, x3));
  const float2 p1 = make_float2(fmaf(c1, a1.x, fmaf(c2, a2.x, x0.x)), fmaf(c1, a1.y, fmaf(c2, a2.y, x0.y)));
  const float2 p2 = make_float2(fmaf(c2, a1.x, fmaf(c1, a2.x, x0.x)), fmaf(c2, a1.y, fmaf(c1, a2.y, x0.y)));
  const float2 q1 = make_float2(fmaf(s1, b1.x, s2 * b2.x), fmaf(s1, b1.y, s2 * b2.y));
  const float2 q2 = make_float2(fmaf(s2, b1.x, -s1 * b2.x), fmaf(s2, b1.y, -s1 * b2.y));
  x0 = cadd(x0, cadd(a1, a2)); x1 = cadd(p1, q1); x4 = csub(p1, q1); x2 = cadd(p2, q2); x3 = csub(p2, q2);
}
template <int INV> DEVINL void fft20(const float2* in, float2* out) {
  float2 t[4][5];
#pragma unroll
  for (int a = 0; a < 4; a++) {
#pragma unroll
    for (int b = 0; b < 5; b++) t[a][b] = in[(5 * a + 4 * b) % 20];
    fft5<INV>(t[a][0], t[a][1], t[a][2], t[a][3], t[a][4]);
  }
#pragma unroll
  for (int d = 0; d < 5; d++) {
    fft4<INV>(t[0][d], t[1][d], t[2][d], t[3][d]);
#pragma unroll
    for (int c = 0; c < 4; c++) out[(5 * c + 16 * d) % 20] = t[c][d];
  }
}
constexpr int ZP = 336;
struct RowSmem { float2 T[320 * 17]; uint32_t Z[16 * ZP]; float2 tw[320]; float2 tp[160]; };
DEVINL float2 cis(int k, int n) {
  float sn, cs; __sincosf((float)(2 * k > n ? k - n : k) * (-6.283185307179586f / (float)n), &sn, &cs); return make_float2(cs, sn);
}
DEVINL void row_tables(RowSmem& sm) {
  const int t = threadIdx.x;
  sm.tw[t] = cis((t >> 4) * (t & 15), 320);
  if (t < 160) sm.tp[t] = cis(t, 640);
}

#define CUNR 1
#define CDRY 0
#define RDRY 1

__global__ void __launch_bounds__(320, 1) rows_fwd_kernel(const bf16* __restrict__ xin, const uint32_t* flags) {
  extern __shared__ __align__(1024) char smraw[]; RowSmem& sm = *(RowSmem*)smraw;
  const int tid = threadIdx.x, s0 = blockIdx.x * 16, wp = __reduce_max_sync(~0u, tid >> 5);
  const uint32_t* flag = flags + F_P + (blockIdx.x >> 2) * 32;
  LOGK(1 + 3 * (xin == g_x), 0);
  if (tid == 0) l2_prefetch(xin + s0 * 640, 20480);
  row_tables(sm);
#pragma unroll 1
  for (int live = !RDRY || wp != 1 || __any_sync(~0u, ldg_rlx32(flag) >= 32); live < 2; live++) {
    if (live) {
      if (wp == 0) { uint32_t v; int n = 0;
        while (true) { asm volatile("ld.acquire.gpu.global.u32 %0, [%1];" : "=r"(v) : "l"(flag) : "memory"); if (__all_sync(~0u, v >= 32 || ++n >= 8 * POLL_LIMIT)) break; __nanosleep(v ? 20 : 200); } }
      __syncthreads();
      pdl_launch();
      LOGK(1 + 3 * (xin == g_x), 1);
    }
    if (wp < 8) {
      const int row = tid >> 4, j = tid & 15; const size_t off = (size_t)(s0 + row) * 640 + j * 8;
      float f[40]; uint4 in[5][5];
#pragma unroll
      for (int i = 0; i < 5; i++) {
#pragma unroll
        for (int q = 0; q < 4; q++) in[i][q] = ldg128_if(g_part + q * 2048 * 640 + off + i * 128, live);
        in[i][4] = ldg128_if(xin + off + i * 128, live);
      }
#pragma unroll
      for (int i = 0; i < 5; i++) {
        float a[8], b[8], c[8], d[8];
        unpack8(in[i][0], a); unpack8(in[i][1], b); unpack8(in[i][2], c); unpack8(in[i][3], d);
#pragma unroll
        for (int e = 0; e < 8; e++) a[e] = (a[e] + b[e]) + (c[e] + d[e]);
        const uint4 o = pack8(a), x = in[i][4];
        const uint4 r = make_uint4(hadd2bf(o.x, x.x), hadd2bf(o.y, x.y), hadd2bf(o.z, x.z), hadd2bf(o.w, x.w));
        stg128_if(g_x + off + i * 128, r, live); unpack8(r, f + 8 * i);
      }
      ln_row(f);
#pragma unroll
      for (int i = 0; i < 5; i++) *(uint4*)(sm.Z + row * ZP + i * 64 + j * 4) = pack8(f + 8 * i);
      __syncwarp();
      float2 z[20], y[20];
#pragma unroll
      for (int n1 = 0; n1 < 20; n1++) { const uint32_t w = sm.Z[row * ZP + n1 * 16 + j]; z[n1] = make_float2(bf_lo(w), bf_hi(w)); }
      fft20<0>(z, y);
#pragma unroll
      for (int k1 = 0; k1 < 20; k1++) sm.T[(k1 * 16 + j) * 17 + row] = k1 ? cmul(y[k1], sm.tw[k1 * 16 + j]) : y[0];
    }
    if (live) __syncthreads();
    const int up = (tid >> 4) & 1, row = tid & 15, k1 = wp ? (up ? 20 - wp : wp) : up * 10;
    float2 x[16];
#pragma unroll
    for (int n2 = 0; n2 < 16; n2++) x[n2] = sm.T[(k1 * 16 + n2) * 17 + row];
    fft16<0>(x);
    uint32_t* ya = g_y + s0 + row + k1 * 2048; uint32_t* yb = g_y + s0 + row + (320 - k1) * 2048;
    stg32_if(g_y + s0 + row + 160 * 2048, pack_f16(2.f * x[8].x, -2.f * x[8].y), live && k1 == 0);
    const int src = (tid & 31) ^ (wp ? 16 : 0);
#pragma unroll
    for (int k2 = 0; k2 < 8; k2++) {
      const float2 c = k1 ? x[15 - k2] : x[(16 - k2) & 15], b = make_float2(__shfl_sync(~0u, c.x, src), __shfl_sync(~0u, c.y, src)), a = x[k2];
      const float2 E = make_float2(a.x + b.x, a.y - b.y), O = cmul(make_float2(a.y + b.y, b.x - a.x), sm.tp[k1 + 20 * k2]);
      stg32_if(ya + k2 * 20 * 2048, pack_f16(E.x + O.x, E.y + O.y), live); stg32_if(yb - k2 * 20 * 2048, pack_f16(E.x - O.x, O.y - E.y), live);
    }
  }
  LOGK(1 + 3 * (xin == g_x), 2);
  if (blockIdx.x == gridDim.x - 1) pdl_wait();
}

__global__ void __launch_bounds__(384) cols_kernel(int layer) {
  extern __shared__ __align__(1024) char smraw[];
  const int sub = threadIdx.x >> 7, tid = threadIdx.x & 127, col = blockIdx.x * 3 + sub, k1 = tid >> 3, j0 = tid & 7;
  float2* sm = (float2*)smraw + sub * (16 * 152);
  float2* tw = (float2*)smraw + 3 * 16 * 152;
  LOGK(2 + 3 * layer, 0);
  pdl_launch();
  uint32_t* y = g_y + col * 2048 + tid;
  if (tid < 2) l2_prefetch((tid ? g_wt : g_y) + col * 2048, 8192);
#pragma unroll 1
  for (int i = threadIdx.x; i < 2176; i += 384) {
    const int a = i < 2048 ? i >> 7 : (i - 2048) >> 3, b = i < 2048 ? i & 127 : i & 7;
    tw[i < 2048 ? a * 136 + b : 2176 + a * 9 + b] = cis(i < 2048 ? a * b : a * b * 16, 2048);
  }
  float2* reg = sm + k1 * 152;
  uint4 wf[4];
#pragma unroll
  for (int q = 0; q < 4; q++) {
    const int live = q >= 0, it = live ? q : q == -3 ? 0 : q == -2 ? 1 : 3;
    float2 x[16];
    if (it == 0) {
      if (live) { __syncthreads(); pdl_wait(); LOGK(2 + 3 * layer, 1); }
#pragma unroll
      for (int i = 0; i < 16; i++) { const uint32_t w = ldg32_if(y + i * 128, live); x[i] = __half22float2(*(const __half2*)&w); }
#pragma unroll
      for (int i = 0; i < 4; i++) wf[i] = ldg128_if(g_wt + col * 2048 + i * 512 + tid * 4, live);
    } else {
      const float2* in = it == 3 ? sm + tid : reg + j0; const int is = it == 1 ? 8 : it == 2 ? 9 : 152;
#pragma unroll
      for (int i = 0; i < 16; i++) x[i] = in[i * is];
    }
    fft16<0>(x);
    if (it == 3) {
      const float sc = 1.f / 4096.f;
#pragma unroll
      for (int i = 0; i < 16; i++) stg32_if(y + i * 128, pack_bf16(x[i].y * sc, x[i].x * sc), live);
    } else {
      const float2* t = it == 0 ? tw + tid : it == 1 ? tw + 2176 + j0 : tw + k1 * 136 + j0; const int ts = it == 0 ? 136 : it == 1 ? 9 : 8;
      float2* o = it == 0 ? sm + tid : reg + j0; const int os = it == 0 ? 152 : it == 1 ? 9 : 8;
      __syncwarp();
#pragma unroll
      for (int k = 0; k < 16; k++) o[k * os] = (CUNR && k == 0 && it < 2) ? x[0] : cmul(x[k], t[k * ts]);
      if (it == 1) {
        __syncwarp();
        float2* r9 = reg + j0 * 9;
#pragma unroll
        for (int i = 0; i < 16; i++) x[i] = r9[(i & 8) * 9 + (i & 7)];
#pragma unroll
        for (int h = 0; h < 2; h++) {
          fft8<0>(x); fft8<0>(x + 8);
          if (h == 0) {
#pragma unroll
            for (int i = 0; i < 16; i++) {
              const uint32_t w = (i & 3) == 0 ? wf[i >> 2].x : (i & 3) == 1 ? wf[i >> 2].y : (i & 3) == 2 ? wf[i >> 2].z : wf[i >> 2].w;
              const float2 v = cmul(x[i], make_float2(bf_lo(w), bf_hi(w))); x[i] = make_float2(v.y, v.x);
            }
          }
        }
        const float2* t9 = tw + 2176 + j0 * 9;
#pragma unroll
        for (int i = 0; i < 16; i++) r9[(i & 8) * 9 + (i & 7)] = (i & 7) ? cmul(x[i], t9[(i & 8) * 9 + (i & 7)]) : x[i];
        __syncwarp();
      } else if (live) bar_sync(sub + 1, 128);
    }
  }
  LOGK(2 + 3 * layer, 2);
}

__global__ void __launch_bounds__(320) rows_inv_kernel(bf16* __restrict__ xout, int do_ln) {
  extern __shared__ __align__(1024) char smraw[]; RowSmem& sm = *(RowSmem*)smraw;
  const int tid = threadIdx.x, s0 = blockIdx.x * 16, wp = __reduce_max_sync(~0u, tid >> 5);
  LOGK(3 + 3 * !do_ln, 0);
  if (tid == 0) l2_prefetch(g_x + s0 * 640, 20480);
  row_tables(sm);
  const size_t off = (size_t)(s0 + ((tid >> 4) & 15)) * 640 + (tid & 15) * 8;
#pragma unroll 1
  for (int live = !RDRY || wp != 1; live < 2; live++) {
    if (live) {
      __syncthreads();
      pdl_wait();
      pdl_launch();
      LOGK(3 + 3 * !do_ln, 1);
    }
    uint4 xr[5];
    {
      const int up = (tid >> 4) & 1, row = tid & 15, k1 = wp ? (up ? 20 - wp : wp) : up * 10;
      const uint32_t* ya = g_y + s0 + row + k1 * 2048; const uint32_t* yb = g_y + s0 + row + (320 - k1) * 2048;
      uint32_t wa[8], wb[8];
#pragma unroll
      for (int k2 = 0; k2 < 8; k2++) { wa[k2] = ldg32_if(ya + k2 * 20 * 2048, live); wb[k2] = ldg32_if(yb - k2 * 20 * 2048, live); }
      const uint32_t wm = ldg32_if(g_y + s0 + row + 160 * 2048, live && k1 == 0);
#pragma unroll
      for (int i = 0; i < 5; i++) xr[i] = ldg128_if(g_x + off + i * 128, live && wp < 8);
      stg32_if(g_flags + blockIdx.x * 320 + tid, 0, live && !do_ln && blockIdx.x * 320 + tid < 2 * F_LAYER);
      if (k1 == 0) { wa[0] &= 0xffffu; wb[0] &= 0xffffu; }
      float2 x[16], r[8];
#pragma unroll
      for (int k2 = 0; k2 < 8; k2++) {
        const float2 a = make_float2(bf_lo(wa[k2]), bf_hi(wa[k2])), b = make_float2(bf_lo(wb[k2]), bf_hi(wb[k2]));
        const float2 E = make_float2(a.x + b.x, a.y - b.y), O = cmulc(make_float2(a.x - b.x, a.y + b.y), sm.tp[k1 + 20 * k2]);
        x[k2] = make_float2(E.x - O.y, E.y + O.x); r[k2] = make_float2(E.x + O.y, O.x - E.y);
      }
      if (k1 == 0) r[0] = make_float2(2.f * bf_lo(wm), -2.f * bf_hi(wm));
      const int src = (tid & 31) ^ (wp ? 16 : 0);
#pragma unroll
      for (int i = 8; i < 16; i++) { const float2 c = k1 ? r[15 - i] : r[(16 - i) & 7]; x[i] = make_float2(__shfl_sync(~0u, c.x, src), __shfl_sync(~0u, c.y, src)); }
      fft16<1>(x);
#pragma unroll
      for (int n2 = 0; n2 < 16; n2++) sm.T[(k1 * 16 + n2) * 17 + row] = x[n2];
    }
    if (live) __syncthreads();
    if (wp < 8) {
      const int row = tid >> 4, n2 = tid & 15;
      float2 z[20], y[20];
#pragma unroll
      for (int k1 = 0; k1 < 20; k1++) { const float2 t = sm.T[(k1 * 16 + n2) * 17 + row]; z[k1] = k1 ? cmulc(t, sm.tw[k1 * 16 + n2]) : t; }
      fft20<1>(z, y);
      const float sc = 1.f / 640.f;
#pragma unroll
      for (int n1 = 0; n1 < 20; n1++) sm.Z[row * ZP + n1 * 16 + n2] = pack_bf16(y[n1].x * sc, y[n1].y * sc);
      __syncwarp();
      float f[40];
#pragma unroll
      for (int i = 0; i < 5; i++) {
        const uint4 o = *(const uint4*)(sm.Z + row * ZP + i * 64 + n2 * 4), x = xr[i];
        const uint4 r = make_uint4(hadd2bf(o.x, x.x), hadd2bf(o.y, x.y), hadd2bf(o.z, x.z), hadd2bf(o.w, x.w));
        stg128_if(xout + off + i * 128, r, live); unpack8(r, f + 8 * i);
      }
      if (do_ln) {
        ln_row(f);
#pragma unroll
        for (int i = 0; i < 5; i++) stg128_if(g_xn + off + i * 128, pack8(f + 8 * i), live);
      }
    }
  }
  LOGK(3 + 3 * !do_ln, 2);
}

typedef CUresult (*EncFn)(CUtensorMap*, CUtensorMapDataType, cuuint32_t, void*, const cuuint64_t*, const cuuint64_t*, const cuuint32_t*, const cuuint32_t*,
                          CUtensorMapInterleave, CUtensorMapSwizzle, CUtensorMapL2promotion, CUtensorMapFloatOOBfill);
static void make_map(EncFn fn, CUtensorMap* m, const void* p, uint64_t cols, uint64_t rows, uint32_t bc, uint32_t br, CUtensorMapSwizzle sw) {
  cuuint64_t gd[2] = {cols, rows}, gs[1] = {cols * 2}; cuuint32_t bd[2] = {bc, br}, es[2] = {1, 1};
  fn(m, CU_TENSOR_MAP_DATA_TYPE_BFLOAT16, 2, (void*)p, gd, gs, bd, es, CU_TENSOR_MAP_INTERLEAVE_NONE, sw, CU_TENSOR_MAP_L2_PROMOTION_L2_128B, CU_TENSOR_MAP_FLOAT_OOB_FILL_NONE);
}
template <class... P, class... A>
static void launch(void (*k)(P...), int grid, int block, int smem, bool pdl, A... a) {
  cudaLaunchConfig_t cfg = {}; cfg.gridDim = dim3(grid); cfg.blockDim = dim3(block); cfg.dynamicSmemBytes = smem; cfg.stream = cudaStreamPerThread;
  cudaLaunchAttribute at[1]; at[0].id = cudaLaunchAttributeProgrammaticStreamSerialization; at[0].val.programmaticStreamSerializationAllowed = 1;
  cfg.attrs = at; cfg.numAttrs = pdl ? 1 : 0;
  cudaLaunchKernelEx(&cfg, k, a...);
}
static const int tune_t[10] = {1580, 1800, 1930, 2080, 2380, 2480, 2710, 2860, 2598, 2700}; constexpr int dev_stop = 100, dev_pdl = 1;

extern "C" void kernel_launch(void* const* d_in, const int* in_sizes, int n_in, void* d_out, int out_size) {
  const bf16 *x = (const bf16*)d_in[0], *mem0 = (const bf16*)d_in[1], *Wq = (const bf16*)d_in[2], *Wk = (const bf16*)d_in[3], *Wv = (const bf16*)d_in[4], *Wo = (const bf16*)d_in[5];
  const bf16 *wr = (const bf16*)d_in[8], *wi = (const bf16*)d_in[9];
  constexpr int SM_A = S_END + 1024, SM_R = sizeof(RowSmem), SM_C = 76 * 1024, SM_I = 116 * 1024;
  void *p_xn, *p_o, *p_x, *p_comm, *p_flags, *fn; cudaDriverEntryPointQueryResult qr;
  cudaGetSymbolAddress(&p_xn, g_xn); cudaGetSymbolAddress(&p_o, g_o); cudaGetSymbolAddress(&p_x, g_x); cudaGetSymbolAddress(&p_comm, g_comm); cudaGetSymbolAddress(&p_flags, g_flags);
  cudaGetDriverEntryPoint("cuTensorMapEncodeTiled", &fn, cudaEnableDefault, &qr);
  cudaFuncSetAttribute(layer_a_kernel, cudaFuncAttributeMaxDynamicSharedMemorySize, SM_A);
  cudaFuncSetAttribute(rows_fwd_kernel, cudaFuncAttributeMaxDynamicSharedMemorySize, SM_R);
  cudaFuncSetAttribute(rows_inv_kernel, cudaFuncAttributeMaxDynamicSharedMemorySize, SM_I);
  cudaFuncSetAttribute(cols_kernel, cudaFuncAttributeMaxDynamicSharedMemorySize, SM_C);
  cudaFuncSetAttribute(rows_fwd_kernel, cudaFuncAttributePreferredSharedMemoryCarveout, 100);
  cudaFuncSetAttribute(cols_kernel, cudaFuncAttributePreferredSharedMemoryCarveout, 100);
  cudaFuncSetAttribute(rows_inv_kernel, cudaFuncAttributePreferredSharedMemoryCarveout, 100);
  CUtensorMap tq, tk, tv, to, to32, tx, tao; EncFn enc = (EncFn)fn;
  make_map(enc, &tq, Wq, 4096, 640, 64, 64, CU_TENSOR_MAP_SWIZZLE_128B); make_map(enc, &tk, Wk, 4096, 640, 64, 64, CU_TENSOR_MAP_SWIZZLE_128B);
  make_map(enc, &tv, Wv, 4096, 640, 64, 64, CU_TENSOR_MAP_SWIZZLE_128B); make_map(enc, &to, Wo, 640, 4096, 64, 64, CU_TENSOR_MAP_SWIZZLE_128B);
  make_map(enc, &to32, Wo, 640, 4096, 16, 256, CU_TENSOR_MAP_SWIZZLE_32B);
  make_map(enc, &tx, p_xn, 640, 2048, 64, 64, CU_TENSOR_MAP_SWIZZLE_128B); make_map(enc, &tao, p_o, 4096, 2048, 64, 64, CU_TENSOR_MAP_SWIZZLE_128B);
  char* comm = (char*)(((uintptr_t)p_comm + (2 << 20) - 1) & ~(uintptr_t)((2 << 20) - 1));
  const bool pdl = dev_pdl;
#define L0PDL 0
  for (int l = 0; l < 2; l++) {
    ArgsA a{x, mem0, comm, (uint32_t*)p_flags + l * F_LAYER, wr, wi, (const char*)Wq, (const char*)Wo, l, {tune_t[0], tune_t[1], tune_t[2], tune_t[3]}, {tune_t[4], tune_t[5], tune_t[6], tune_t[7]}, {tune_t[8], tune_t[9]}};
    if (dev_stop > 4 * l + 0) launch(layer_a_kernel, 132, 384, SM_A, pdl && (l || L0PDL), tq, tk, tv, to, to32, tx, tao, a);
    if (dev_stop > 4 * l + 1) launch(rows_fwd_kernel, 128, 320, SM_R, pdl, l ? (const bf16*)p_x : x, (const uint32_t*)a.flags);
    if (dev_stop > 4 * l + 2) launch(cols_kernel, 107, 384, SM_C, pdl, l);
    if (dev_stop > 4 * l + 3) launch(rows_inv_kernel, 128, 320, SM_I, pdl, l ? (bf16*)d_out : (bf16*)p_x, l == 0);
  }
}
```

```cpp
#include <cuda_runtime.h>
#include <cuda_bf16.h>
#include <cuda_fp16.h>
#include <cuda.h>
#include <stdint.h>

typedef __nv_bfloat16 bf16;
#define DEVINL __device__ __forceinline__

__device__ __align__(1024) bf16 g_xn[2048 * 640];
__device__ __align__(1024) bf16 g_x[2048 * 640];
__device__ __align__(1024) char g_kv[64 * 32 * 16384];
__device__ __align__(1024) char g_kvm[64 * 32 * 4096];
__device__ __align__(1024) bf16 g_o[2048 * 4096];
__device__ __align__(1024) bf16 g_part[4 * 2048 * 640];
__device__ __align__(1024) uint32_t g_y[321 * 2048];
__device__ __align__(1024) uint32_t g_wt[321 * 2048];
__device__ __align__(4096) char g_comm[4 << 20];
constexpr int F_KV = 0, F_KM = 1024, F_O = F_KM + 1024, F_P = F_O + 128, F_ROLE = F_P + 32 * 32, F_X = F_ROLE + 64, F_LAYER = F_X + 32;
__device__ __align__(1024) uint32_t g_flags[2 * F_LAYER];
__device__ int g_side[256];

template <int V> struct IC { static constexpr int value = V; };
template <int B, int E, class F> DEVINL void static_for(F&& f) { if constexpr (B < E) { f(IC<B>{}); static_for<B + 1, E>(f); } }

#define POLL_LIMIT (1 << 17)
DEVINL uint32_t smem_u32(const void* p) { return (uint32_t)__cvta_generic_to_shared(p); }
DEVINL uint32_t mapa(uint32_t a, uint32_t r) { uint32_t o; asm volatile("mapa.shared::cluster.u32 %0, %1, %2;" : "=r"(o) : "r"(a), "r"(r)); return o; }
DEVINL uint32_t clk() { uint32_t v; asm volatile("{.reg .b64 w; mov.u64 w, %%clock64; cvt.u32.u64 %0, w;}" : "=r"(v)::"memory"); return v; }
DEVINL void mbar_init(uint32_t bar, uint32_t cnt) { asm volatile("mbarrier.init.shared::cta.b64 [%0], %1;" ::"r"(bar), "r"(cnt) : "memory"); }
DEVINL void mbar_arrive(uint32_t bar) { asm volatile("mbarrier.arrive.shared::cta.b64 _, [%0];" ::"r"(bar) : "memory"); }
DEVINL void mbar_arrive_remote(uint32_t bar) { asm volatile("mbarrier.arrive.shared::cluster.b64 _, [%0];" ::"r"(bar) : "memory"); }
DEVINL void mbar_arrive_tx(uint32_t bar, uint32_t tx) { asm volatile("mbarrier.arrive.expect_tx.shared::cta.b64 _, [%0], %1;" ::"r"(bar), "r"(tx) : "memory"); }
DEVINL void mbar_wait(uint32_t bar, uint32_t ph) {
  asm volatile("{.reg .pred p; .reg .b32 c,q; shl.b32 c, %1, 20;\n"
               "W0: bfe.u32 q, c, 20, 1; mbarrier.try_wait.parity.shared::cta.b64 p, [%0], q; add.u32 c,c,1; @!p bra.uni W0;}" ::"r"(bar), "r"(ph) : "memory");
}
DEVINL void bar_sync(int id, int n) { asm volatile("bar.sync %0, %1;" ::"r"(id), "r"(n) : "memory"); }
DEVINL void bar_arrive(int id, int n) { asm volatile("bar.arrive %0, %1;" ::"r"(id), "r"(n) : "memory"); }
DEVINL void cluster_sync() { asm volatile("barrier.cluster.arrive.release.aligned; barrier.cluster.wait.acquire.aligned;" ::: "memory"); }
DEVINL void tma_2d(uint32_t dst, const CUtensorMap* tm, int c0, int c1, uint32_t bar) {
  asm volatile("cp.async.bulk.tensor.2d.shared::cluster.global.mbarrier::complete_tx::bytes [%0], [%1, {%2, %3}], [%4];" ::"r"(dst), "l"(tm), "r"(c0), "r"(c1), "r"(bar) : "memory");
}
DEVINL void tma_2d_mc(uint32_t dst, const CUtensorMap* tm, int c0, int c1, uint32_t bar) {
  asm volatile("cp.async.bulk.tensor.2d.shared::cluster.global.mbarrier::complete_tx::bytes.multicast::cluster [%0], [%1, {%2, %3}], [%4], %5;" ::"r"(dst), "l"(tm), "r"(c0), "r"(c1), "r"(bar), "h"((uint16_t)3) : "memory");
}
DEVINL void bulk_g2s(uint32_t dst, const void* src, uint32_t bytes, uint32_t bar) {
  asm volatile("cp.async.bulk.shared::cluster.global.mbarrier::complete_tx::bytes [%0], [%1], %2, [%3];" ::"r"(dst), "l"(src), "r"(bytes), "r"(bar) : "memory");
}
DEVINL void l2_prefetch(const void* p, uint32_t bytes) { asm volatile("cp.async.bulk.prefetch.L2.global [%0], %1;" ::"l"(p), "r"(bytes) : "memory"); }
DEVINL void fence_proxy_async() { asm volatile("fence.proxy.async.global;" ::: "memory"); }
DEVINL void ldsm4t(uint32_t* r, uint32_t a) { asm volatile("ldmatrix.sync.aligned.m8n8.x4.trans.shared.b16 {%0,%1,%2,%3}, [%4];" : "=r"(r[0]), "=r"(r[1]), "=r"(r[2]), "=r"(r[3]) : "r"(a) : "memory"); }
DEVINL void stsm4(uint32_t a, uint32_t r0, uint32_t r1, uint32_t r2, uint32_t r3) { asm volatile("stmatrix.sync.aligned.m8n8.x4.shared.b16 [%0], {%1,%2,%3,%4};" ::"r"(a), "r"(r0), "r"(r1), "r"(r2), "r"(r3) : "memory"); }
DEVINL void mma16816(float* d, const uint32_t* a, uint32_t b0, uint32_t b1) {
  asm volatile("mma.sync.aligned.m16n8k16.row.col.f32.bf16.bf16.f32 {%0,%1,%2,%3}, {%4,%5,%6,%7}, {%8,%9}, {%0,%1,%2,%3};"
               : "+f"(d[0]), "+f"(d[1]), "+f"(d[2]), "+f"(d[3]) : "r"(a[0]), "r"(a[1]), "r"(a[2]), "r"(a[3]), "r"(b0), "r"(b1));
}
DEVINL void mma16816z(float* d, const uint32_t* a, uint32_t b0, uint32_t b1) {
  asm volatile("mma.sync.aligned.m16n8k16.row.col.f32.bf16.bf16.f32 {%0,%1,%2,%3}, {%4,%5,%6,%7}, {%8,%9}, {%10,%10,%10,%10};"
               : "=f"(d[0]), "=f"(d[1]), "=f"(d[2]), "=f"(d[3]) : "r"(a[0]), "r"(a[1]), "r"(a[2]), "r"(a[3]), "r"(b0), "r"(b1), "f"(0.f));
}
DEVINL void mma1688z(float* d, uint32_t a0, uint32_t a1, uint32_t b0) {
  asm volatile("mma.sync.aligned.m16n8k8.row.col.f32.bf16.bf16.f32 {%0,%1,%2,%3}, {%4,%5}, {%6}, {%7,%7,%7,%7};"
               : "=f"(d[0]), "=f"(d[1]), "=f"(d[2]), "=f"(d[3]) : "r"(a0), "r"(a1), "r"(b0), "f"(0.f));
}
DEVINL uint32_t movm(uint32_t a) { uint32_t r; asm volatile("movmatrix.sync.aligned.m8n8.trans.b16 %0, %1;" : "=r"(r) : "r"(a)); return r; }
DEVINL uint32_t pack_bf16(float lo, float hi) { uint32_t r; asm("cvt.rn.bf16x2.f32 %0, %1, %2;" : "=r"(r) : "f"(hi), "f"(lo)); return r; }
DEVINL uint32_t pack_f16(float lo, float hi) { uint32_t r; asm("cvt.rn.f16x2.f32 %0, %1, %2;" : "=r"(r) : "f"(hi), "f"(lo)); return r; }
DEVINL float bf_lo(uint32_t w) { return __uint_as_float(w << 16); }
DEVINL float bf_hi(uint32_t w) { return __uint_as_float(w & 0xffff0000u); }
DEVINL uint32_t hadd2bf(uint32_t a, uint32_t b) { uint32_t r; asm("add.rn.bf16x2 %0, %1, %2;" : "=r"(r) : "r"(a), "r"(b)); return r; }
DEVINL uint32_t hmax2bf(uint32_t a, uint32_t b) { uint32_t r; asm("max.bf16x2 %0, %1, %2;" : "=r"(r) : "r"(a), "r"(b)); return r; }
DEVINL uint32_t lds32(uint32_t a) { uint32_t v; asm volatile("ld.shared.u32 %0, [%1];" : "=r"(v) : "r"(a) : "memory"); return v; }
DEVINL uint2 lds64(uint32_t a) { uint2 v; asm volatile("ld.shared.v2.u32 {%0,%1}, [%2];" : "=r"(v.x), "=r"(v.y) : "r"(a) : "memory"); return v; }
DEVINL uint4 lds128(uint32_t a) { uint4 v; asm volatile("ld.shared.v4.u32 {%0,%1,%2,%3}, [%4];" : "=r"(v.x), "=r"(v.y), "=r"(v.z), "=r"(v.w) : "r"(a) : "memory"); return v; }
DEVINL void sts32(uint32_t a, uint32_t v) { asm volatile("st.shared.u32 [%0], %1;" ::"r"(a), "r"(v) : "memory"); }
DEVINL void sts64(uint32_t a, uint32_t x, uint32_t y) { asm volatile("st.shared.v2.u32 [%0], {%1,%2};" ::"r"(a), "r"(x), "r"(y) : "memory"); }
DEVINL void sts128(uint32_t a, uint4 v) { asm volatile("st.shared.v4.u32 [%0], {%1,%2,%3,%4};" ::"r"(a), "r"(v.x), "r"(v.y), "r"(v.z), "r"(v.w) : "memory"); }
DEVINL void stasync64(uint32_t a, uint32_t x, uint32_t y, uint32_t bar) { asm volatile("st.async.weak.shared::cluster.mbarrier::complete_tx::bytes.v2.b32 [%0], {%1,%2}, [%3];" ::"r"(a), "r"(x), "r"(y), "r"(bar) : "memory"); }
DEVINL uint4 ldg_rlx128(const void* p) { uint4 v; asm volatile("{.reg .b64 a,b; ld.relaxed.gpu.global.v2.b64 {a,b}, [%4]; mov.b64 {%0,%1}, a; mov.b64 {%2,%3}, b;}" : "=r"(v.x), "=r"(v.y), "=r"(v.z), "=r"(v.w) : "l"(p) : "memory"); return v; }
DEVINL uint2 ldg_rlx64(const void* p) { uint2 v; asm volatile("ld.relaxed.gpu.global.v2.u32 {%0,%1}, [%2];" : "=r"(v.x), "=r"(v.y) : "l"(p) : "memory"); return v; }
DEVINL void stg_rlx64(void* p, uint32_t x, uint32_t y) { asm volatile("{.reg .b64 a; mov.b64 a, {%1,%2}; st.relaxed.gpu.global.b64 [%0], a;}" ::"l"(p), "r"(x), "r"(y) : "memory"); }
DEVINL void stg_rlx128(void* p, uint32_t x, uint32_t y, uint32_t z, uint32_t w) { asm volatile("{.reg .b64 a,b; mov.b64 a, {%1,%2}; mov.b64 b, {%3,%4}; st.relaxed.gpu.global.v2.b64 [%0], {a,b};}" ::"l"(p), "r"(x), "r"(y), "r"(z), "r"(w) : "memory"); }
DEVINL void stg_rlx32(void* p, uint32_t x) { asm volatile("st.relaxed.gpu.global.u32 [%0], %1;" ::"l"(p), "r"(x) : "memory"); }
DEVINL uint4 ldg_cg128(const void* p) { uint4 v; asm volatile("ld.global.cg.v4.u32 {%0,%1,%2,%3}, [%4];" : "=r"(v.x), "=r"(v.y), "=r"(v.z), "=r"(v.w) : "l"(p) : "memory"); return v; }
DEVINL uint32_t ldg_cg32(const void* p) { uint32_t v; asm volatile("ld.global.cg.u32 %0, [%1];" : "=r"(v) : "l"(p) : "memory"); return v; }
DEVINL uint32_t ldg32_if(const void* p, int on) { uint32_t v; asm volatile("{.reg .pred q; setp.ne.s32 q, %2, 0; mov.u32 %0, 0; @q ld.global.cg.u32 %0, [%1];}" : "=r"(v) : "l"(p), "r"(on) : "memory"); return v; }
DEVINL uint4 ldg128_if(const void* p, int on) { uint4 v; asm volatile("{.reg .pred q; setp.ne.s32 q, %5, 0; mov.u32 %0, 0; mov.u32 %1, 0; mov.u32 %2, 0; mov.u32 %3, 0; @q ld.global.cg.v4.u32 {%0,%1,%2,%3}, [%4];}" : "=r"(v.x), "=r"(v.y), "=r"(v.z), "=r"(v.w) : "l"(p), "r"(on) : "memory"); return v; }
DEVINL void stg32_if(void* p, uint32_t v, int on) { asm volatile("{.reg .pred q; setp.ne.s32 q, %2, 0; @q st.global.u32 [%0], %1;}" ::"l"(p), "r"(v), "r"(on) : "memory"); }
DEVINL void stg128_if(void* p, uint4 v, int on) { asm volatile("{.reg .pred q; setp.ne.s32 q, %5, 0; @q st.global.v4.u32 [%0], {%1,%2,%3,%4};}" ::"l"(p), "r"(v.x), "r"(v.y), "r"(v.z), "r"(v.w), "r"(on) : "memory"); }
DEVINL uint4 ldg_ca128(const void* p) { uint4 v; asm volatile("ld.global.ca.v4.u32 {%0,%1,%2,%3}, [%4];" : "=r"(v.x), "=r"(v.y), "=r"(v.z), "=r"(v.w) : "l"(p) : "memory"); return v; }
DEVINL uint32_t ldg_ca32(const void* p) { uint32_t v; asm volatile("ld.global.ca.u32 %0, [%1];" : "=r"(v) : "l"(p) : "memory"); return v; }
DEVINL void flag_wait(const uint32_t* p, uint32_t want) {
  uint32_t v;
#pragma unroll 1
  for (int n = 0; n < POLL_LIMIT; n++) { asm volatile("ld.acquire.gpu.global.u32 %0, [%1];" : "=r"(v) : "l"(p) : "memory"); if (v >= want) break; __nanosleep(40); }
}
DEVINL void flag_wait_warp(const uint32_t* p, uint32_t want) {
  uint32_t v; int n = 0;
  do { asm volatile("ld.acquire.gpu.global.u32 %0, [%1];" : "=r"(v) : "l"(p) : "memory"); } while (__any_sync(~0u, v < want && ++n < POLL_LIMIT));
}
DEVINL void flag_add(uint32_t* p) { asm volatile("red.release.gpu.global.add.u32 [%0], 1;" ::"l"(p) : "memory"); }
DEVINL void flag_set(uint32_t* p, uint32_t v) { asm volatile("fence.acq_rel.gpu; st.relaxed.gpu.global.u32 [%0], %1;" ::"l"(p), "r"(v) : "memory"); }
DEVINL uint32_t ldg_rlx32(const void* p) { uint32_t v; asm volatile("ld.relaxed.gpu.global.u32 %0, [%1];" : "=r"(v) : "l"(p) : "memory"); return v; }
DEVINL float ex2(float x) { float y; asm("ex2.approx.ftz.f32 %0, %1;" : "=f"(y) : "f"(x)); return y; }
DEVINL float rcp(float x) { float y; asm("rcp.approx.ftz.f32 %0, %1;" : "=f"(y) : "f"(x)); return y; }
DEVINL uint32_t opaque(uint32_t x) { return __shfl_sync(~0u, x, threadIdx.x & 31); }
DEVINL uint32_t launder(uint32_t x) { asm volatile("" : "+r"(x)); return x; }
DEVINL void pdl_wait() { asm volatile("griddepcontrol.wait;" ::: "memory"); }
DEVINL void pdl_launch() { asm volatile("griddepcontrol.launch_dependents;" ::: "memory"); }
#define LOGS(cta, i)
#define LOGK(k, i)
#define LOG(cta, i)
#define LOGV(cta, i, v)
#define EV(i, v)
constexpr float SM_SCALE = 0.08838834764831845f * 1.4426950408889634f;

DEVINL void unpack8(uint4 v, float* f) { f[0] = bf_lo(v.x); f[1] = bf_hi(v.x); f[2] = bf_lo(v.y); f[3] = bf_hi(v.y); f[4] = bf_lo(v.z); f[5] = bf_hi(v.z); f[6] = bf_lo(v.w); f[7] = bf_hi(v.w); }
DEVINL uint4 pack8(const float* f) { return make_uint4(pack_bf16(f[0], f[1]), pack_bf16(f[2], f[3]), pack_bf16(f[4], f[5]), pack_bf16(f[6], f[7])); }
DEVINL void ln_row(float* f) {
  float s = 0.f;
#pragma unroll
  for (int i = 0; i < 40; i++) s += f[i];
#pragma unroll
  for (int o = 1; o < 16; o <<= 1) s += __shfl_xor_sync(~0u, s, o);
  const float mean = s * (1.f / 640.f); float q = 0.f;
#pragma unroll
  for (int i = 0; i < 40; i++) { f[i] -= mean; q = fmaf(f[i], f[i], q); }
#pragma unroll
  for (int o = 1; o < 16; o <<= 1) q += __shfl_xor_sync(~0u, q, o);
  const float rs = rsqrtf(q * (1.f / 640.f) + 1e-5f);
#pragma unroll
  for (int i = 0; i < 40; i++) f[i] *= rs;
}

struct ArgsA {
  const bf16* x; const bf16* mem0; char* comm; uint32_t* flags; const bf16* wr; const bf16* wi; const char* wq; const char* wo;
  int layer; int ta[4], tb[4], tc[2];
};

#define VP 4
#define HELD 0x2557
#define PRE 4
#define VPRE0 2
#define VPRE1 4
#define R0 2
#define TRK 30
#define TEXP 200
#define TRD 0
#define TKV 300
#define KB1 5
#define W2D 0
#define WD 4
#define VPW 2
#define P1F 1
#define W0D 0
#define XD 0
#define TSF 1
#define XP 0
#define PW 1
#define VXE 0
#define LA 0
#define KB2 9
#define KB3 13
#define TSE 7
#define PRP 0
#define W1D 60
constexpr int C_WV = 0;
constexpr int C_WO = 81920;
constexpr int C_KV = 163840;
constexpr int C_M  = C_KV + 24576;
constexpr int C_QK = C_M + 10240;
constexpr int C_VP = C_QK + 4096;
constexpr int C_S  = C_VP + 4096;
constexpr int C_O  = C_S + 2048;
constexpr int C_R  = C_O + 2048;
constexpr int C_T  = C_R + 256;
constexpr int S_BAR = 229376;
constexpr int S_END = S_BAR + 256;
enum { BAR_QK = 2, BAR_O = 3, BAR_H = 4, BAR_X = 5, BAR_W = 7  , BAR_E = 9, BAR_M1 = 10  , BAR_M3 = 12, BAR_M2 = 13   };
constexpr int B_W = 0, B_S = 8, B_W2 = 16, B_KV = 24, B_WV = 40, B_WO = 48;
constexpr int G2_OFF = 0x130000, TS_OFF = 0x11000;

#define FEN() asm volatile("pmevent 0;" ::: "memory")
#define SCHED(x, c) asm volatile("{.reg .pred p; setp.eq.u32 p, %0, %1; @p exit;}" ::"r"(x), "r"(0x7fff0001u + 2 * (c)) : "memory")
DEVINL uint32_t g1page(uint32_t L) { L = ((L & 7) | ((L & 24) << 2)) << 1; return (L | (__popc(L & 0xb2) & 1)) << 12; }
DEVINL void spin_until(uint32_t t) {
  asm volatile("{.reg .pred p; .reg .b32 c; .reg .b64 w;\nS0: mov.u64 w, %%clock64; cvt.u32.u64 c, w; sub.u32 c, %0, c; setp.lt.u32 p, c, 16384; @p bra.uni S0;}" ::"r"(t) : "memory");
}
DEVINL uint32_t wait_until(uint32_t t, uint32_t z) { uint32_t r;
  asm volatile("{.reg .pred p; .reg .b32 c,x,y; .reg .b64 w;\nT0: .branchtargets L0, L1, L2, L3, L4, L5, L6, L7, L8, L9, L10;\n mov.u32 x, %2;\n"
               "mov.u64 w, %%clock64; cvt.u32.u64 c, w; sub.u32 c, %1, c; setp.ge.u32 p, c, 16384; @p bra.uni L0;\n"
               "S0: mov.u64 w, %%clock64; cvt.u32.u64 c, w; sub.u32 c, %1, c; setp.gt.s32 p, c, 40; @p bra.uni S0;\n"
               "mad.lo.s32 c, c, 37, 1200; shr.s32 c, c, 8; max.s32 c, c, 0;\nbrx.idx.uni c, T0;\n"
               "L10: mul.lo.u32 x, x, x; L9: mul.lo.u32 x, x, x; L8: mul.lo.u32 x, x, x; L7: mul.lo.u32 x, x, x; L6: mul.lo.u32 x, x, x; L5: mul.lo.u32 x, x, x; L4: mul.lo.u32 x, x, x; L3: mul.lo.u32 x, x, x; L2: mul.lo.u32 x, x, x; L1: mul.lo.u32 x, x, x; L0: mov.u32 %0, x;}" : "=r"(r) : "r"(t), "r"(z) : "memory"); return r;
}
DEVINL void gtime(uint32_t& G16, uint32_t& C) {
  asm volatile("{.reg .b64 w; .reg .b32 g,g0,a;\n mov.u64 w, %%clock64; cvt.u32.u64 %1, w; mov.u64 w, %%globaltimer; cvt.u32.u64 g0, w; mul.lo.u32 a, g0, -11;\n"
               "mov.u64 w, %%globaltimer; cvt.u32.u64 g, w; add.u32 a, a, g; mov.u64 w, %%globaltimer; cvt.u32.u64 g, w; add.u32 a, a, g; mov.u64 w, %%globaltimer; cvt.u32.u64 g, w; add.u32 a, a, g; mov.u64 w, %%globaltimer; cvt.u32.u64 g, w; add.u32 a, a, g; mov.u64 w, %%globaltimer; cvt.u32.u64 g, w; add.u32 a, a, g; mov.u64 w, %%globaltimer; cvt.u32.u64 g, w; add.u32 a, a, g; mov.u64 w, %%globaltimer; cvt.u32.u64 g, w; add.u32 a, a, g; mov.u64 w, %%globaltimer; cvt.u32.u64 g, w; add.u32 a, a, g; mov.u64 w, %%globaltimer; cvt.u32.u64 g, w; add.u32 a, a, g; mov.u64 w, %%globaltimer; cvt.u32.u64 g, w; add.u32 a, a, g; mov.u64 w, %%globaltimer; cvt.u32.u64 g, w; add.u32 a, a, g; \n mul.lo.u32 a, a, 341; shr.u32 a, a, 8; mad.lo.u32 %0, g0, 16, a;}" : "=r"(G16), "=r"(C)::"memory");
}
DEVINL uint32_t pack_tag(float lo, float hi, uint32_t tg) {
  const uint32_t w = pack_bf16(lo, __uint_as_float(tg | 0x3F800000u)), a = __float_as_uint(hi) + (tg ^ 0x10000u); uint32_t r;
  asm("lop3.b32 %0, %1, %2, 0xFFFE0000, 0xE4;" : "=r"(r) : "r"(a), "r"(w)); return r;
}
DEVINL float ex2v(float x) { float y; asm volatile("ex2.approx.ftz.f32 %0, %1;" : "=f"(y) : "f"(x)); return y; }
DEVINL void load_kv(uint32_t sb, int h, int j, int s) {
  asm volatile("{.reg .pred p; elect.sync _|p, 0xffffffff;\n fence.proxy.async.global;\n @p mbarrier.arrive.expect_tx.shared::cta.b64 _, [%2], 12288;\n"
               " @p cp.async.bulk.shared::cluster.global.mbarrier::complete_tx::bytes [%0], [%1], 12288, [%2];}"
               ::"r"(sb + C_KV + (s & 1) * 12288), "l"(g_kv + (size_t)(s * 32 + h) * 16384 + j * 4096), "r"(sb + S_BAR + B_KV + (s & 1) * 8) : "memory");
}

template <int KH>
DEVINL void chain_mma(uint32_t sb0, const ArgsA& args) {
  const int lane = threadIdx.x & 31, mg = (threadIdx.x >> 5) & 3, mi = lane >> 3, r = lane & 7;
  const uint32_t aW = opaque(sb0 + (uint32_t)(((mi >> 1) * 8 + r) * 128 + (((mg + 4 * (mi & 1)) ^ r) << 4)));
  const uint32_t aL = opaque(sb0 + lane * 16);
  const uint32_t aLm = opaque(sb0 + mg * 512 + lane * 16);
#define sb (launder(aL) & ~511u)
  constexpr int OV = C_WV + KH * 40960, OM = C_M + KH * 5120, NF = KH ? 16 : 24;
  auto owo = [](int f) { return C_WO + (KH + 2 * (f >> 3)) * 16384 + (f & 7) * 2048; };
  auto held = [](int k) { return (HELD >> k) & 1; };
  auto rank = [](int k) { return __popc(HELD & ((1 << k) - 1)); };
  uint32_t wq[20][4], wk[20][4];
  mbar_wait(sb + S_BAR + B_W, 0);
#pragma unroll
  for (int k = 0; k < 12; k++) { ldsm4t(wq[k], aW + OV + k * 2048); ldsm4t(wk[k], aW + C_WO + KH * 40960 + k * 2048); }
  bar_arrive(BAR_H, 288);
  mbar_wait(sb + S_BAR + B_W2, 0);
#pragma unroll
  for (int k = 12; k < 20; k++) { ldsm4t(wq[k], aW + OV + k * 2048); ldsm4t(wk[k], aW + C_WO + KH * 40960 + k * 2048); }
  bar_sync(BAR_E, 384);
  mbar_wait(sb + S_BAR + B_WV, 0);
  uint32_t sx = args.layer << 16;
#pragma unroll 1
  while (true) {
    uint32_t v[20][4], b[10][4];
    {
      const uint32_t o = launder(aLm) - sb, on = (sx >> 16) != (uint32_t)args.layer;
      const char* p = args.comm + lds32(sb + C_T + KH * 1024 + 4 + (o >> 1));
      constexpr int NB = KH ? VPRE1 : VPRE0;
      const uint32_t zero = (uint32_t)(uintptr_t)p & 1, tt = lds32(sb + C_R + 48) + args.tb[0]; uint32_t av = aW;
#pragma unroll
      for (int k = 0; k < 20; k++) if (held(k) && rank(k) < NB) { ldsm4t(v[k], av + OV + k * 2048); if (rank(k) % VPW == VPW - 1 && rank(k) < NB - 1) av = aW + (v[k][0] & zero); }
      p += wait_until(tt, zero);
      uint4 a = ldg_rlx128(p);
      __syncwarp();
#pragma unroll
      for (int k = 0; k < 20; k++) if (held(k) && rank(k) >= NB) { ldsm4t(v[k], av + OV + k * 2048); if ((rank(k) - NB) % VPW == VPW - 1) av = aW + (v[k][0] & zero); }
      SCHED(o ^ on, 29);
      if (on) sts128(aLm + OM, a);
      if (__builtin_expect(__any_sync(~0u, on && (((a.x ^ sx) | (a.z ^ sx)) & 0x10000u)), 0)) {
        int lim = 0;
        do a = ldg_rlx128(p); while (__any_sync(~0u, (((a.x ^ sx) | (a.z ^ sx)) & 0x10000u) && ++lim < POLL_LIMIT));
        sts128(aLm + OM, a);
      }
      bar_sync(BAR_W + KH, 128);
      ldsm4t(b[0], aL + OM); ldsm4t(b[1], aL + OM + 512);
    }
    float cq[4], ck[4], cv[4];
    static_for<0, 20>([&](auto I) {
      constexpr int k = I.value, p = k >> 1;
      const uint32_t b0 = b[p][(k & 1) * 2], b1 = b[p][(k & 1) * 2 + 1];
      if (k == 0) { mma16816z(cv, v[0], b0, b1); mma16816z(cq, wq[k], b0, b1); mma16816z(ck, wk[k], b0, b1); }
      else { if (k < 20 - VP) mma16816(cv, v[k], b0, b1); mma16816(cq, wq[k], b0, b1); mma16816(ck, wk[k], b0, b1); }
      if (k == KB1) bar_sync(BAR_M1 + KH, 160);
      if (k == KB2) bar_sync(BAR_M2 + KH, 160);
      if (k == KB3) bar_sync(BAR_M3, 320);
      static_for<2, 10>([&](auto J) {
        constexpr int q = J.value, st = q < 4 ? 0 : q < 6 ? KB1 : q < 8 ? KB2 : KB3;
        if constexpr (k == (2 * q - 3 > st ? 2 * q - 3 : st)) ldsm4t(b[q], aL + OM + q * 512); });
      if constexpr (k + 3 < 20 - VP && !((HELD >> (k + 3)) & 1)) ldsm4t(v[k + 3], aW + OV + (k + 3) * 2048);
      if (k >= 20 - VP && k < 20 - VP + PRE && !held(k)) ldsm4t(v[k], aW + OV + k * 2048);
      if (P1F && (k & 1) && k >= P1F && k < 19) FEN();
    });
    stsm4(aLm + C_QK + KH * 2048, pack_bf16(cq[0], cq[1]), pack_bf16(cq[2], cq[3]), pack_bf16(ck[0], ck[1]), pack_bf16(ck[2], ck[3]));
    bar_arrive(BAR_QK, 384);
    FEN();
    const uint32_t l8 = (launder(aL) & 511) >> 1, px = lds32(sb + C_R + 80);
#pragma unroll
    for (int k = 20 - VP + PRE; k < 20; k++) if (!held(k)) ldsm4t(v[k], aW + OV + k * 2048);
#pragma unroll
    for (int k = 20 - VP; k < 20; k++) {
      const int p = k >> 1, q = k - 20 + VP; const uint32_t b0 = b[p][(k & 1) * 2], b1 = b[p][(k & 1) * 2 + 1];
      if (q % 3 == 0) mma16816(cv, v[k], b0, b1); else if (q == 1) mma16816z(cq, v[k], b0, b1); else if (q == 2) mma16816z(ck, v[k], b0, b1);
      else if (q % 3 == 1) mma16816(cq, v[k], b0, b1); else mma16816(ck, v[k], b0, b1);
    }
    if (VP >= 3) {
#pragma unroll
      for (int i = 0; i < 4; i++) cv[i] += cq[i] + ck[i];
    }
    { const uint32_t vx = pack_bf16(cv[0], cv[1]), vy = pack_bf16(cv[2], cv[3]);
      const uint32_t av = aLm - l8 + C_VP + KH * 256;
      stasync64(av + 2048 + px, vx, vy, sb + S_BAR + B_S + px);
      sts64(av, vx, vy);
      __syncwarp();
      if (l8 == 0) mbar_arrive(sb + S_BAR + B_S); }
    sx += 0x10000;
    if ((sx >> 16) == args.layer + 64u) break;
    uint32_t w[NF][4];
    {
      const uint32_t zero = px & 1; uint32_t a = aW;
      const bool tsw = KH == 1 && __any_sync(~0u, launder(aLm) == aL); uint2 ts = make_uint2(0, 0); uint4 cal = make_uint4(0, 0, 0, 0);
      if ((sx >> 16) == args.layer + 1u) mbar_wait(sb + S_BAR + B_WO, 0);
#pragma unroll
      for (int f = 0; f < 8 + XP; f++) { ldsm4t(w[f], a + owo(f));
        if (KH == 1 && f == TSF && tsw) { ts = ldg_rlx64(args.comm + TS_OFF + l8); cal = lds128(sb + C_R + 64); }
      if (KH == 1 && f == TSE && tsw) {
        const uint32_t d0 = ts.x - cal.x, d1 = ts.y - cal.x;
        const int dt = (int)__reduce_max_sync(~0u, max(d0 < 32768u ? d0 : 0u, d1 < 32768u ? d1 : 0u));
        sts32(sb + C_R + 48, cal.y + min((dt * cal.z) >> 16, 8192u));
      }
        uint32_t d = w[f][0] & zero;
#pragma unroll
        for (int q = 0; q < TRD; q++) d = __popc(d);
        if (f % PW == PW - 1) a = aW + d; }
    }
    const uint32_t go = lds32(sb + C_T + KH * 1024 + ((launder(aLm) - sb) >> 1));
    SCHED(go, 30);
    bar_sync(BAR_O, 384);
    uint32_t ob[16];
#pragma unroll
    for (int p = 0; p < 4; p++) ldsm4t(ob + 4 * p, aL + C_O + p * 512);
    __syncwarp();
    float r0, r1; uint32_t y0, y1;
    { const uint2 rr = lds64(sb + C_R + 128 + ((launder(aL) >> 1) & 24)); r0 = rcp(__uint_as_float(rr.x)); r1 = rcp(__uint_as_float(rr.y)); }
    constexpr int RA = KH ? 0 : R0;
    static_for<0, NF>([&](auto I) {
      constexpr int f = I.value, k = f & 7; const uint32_t* A = w[f];
      if (k == 0) mma16816z(cq, A, ob[0], ob[1]); else if (k == 1) mma16816z(ck, A, ob[2], ob[3]);
      else if (k & 1) mma16816(ck, A, ob[2 * k], ob[2 * k + 1]); else mma16816(cq, A, ob[2 * k], ob[2 * k + 1]);
      if (f == 5 && RA) {
#pragma unroll
        for (int q = XP; q < XP + RA; q++) ldsm4t(w[8 + q], aW + owo(8 + q));
        FEN();
      }
      if constexpr (f >= 8 && (f & 1) && f + WD < NF && (LA || k + WD < 8)) {
        const uint32_t a = aW + (A[0] & go & 1); ldsm4t(w[f + WD - 1], a + owo(f + WD - 1)); ldsm4t(w[f + WD], a + owo(f + WD)); }
      if constexpr (XD != 0) { if (f == 15) spin_until(clk() + XD); }
      if (k == 7) { y0 = pack_tag((cq[0] + ck[0]) * r0, (cq[1] + ck[1]) * r1, sx & 0x10000u); y1 = pack_bf16((cq[2] + ck[2]) * r0, (cq[3] + ck[3]) * r1);
        stg_rlx64(args.comm + go + (f < 8 ? 0 : f < 16 ? 0x30000 : 0x100000), y0, y1); }
      if (f == 7) {
        if constexpr ((KH ? W1D : W0D) != 0) spin_until(clk() + (KH ? W1D : W0D)); else FEN();
#pragma unroll
        for (int q = XP + RA; q < WD; q++) ldsm4t(w[8 + q], aW + owo(8 + q));
      }
      if constexpr (!LA && f == 15 && NF > 16) { FEN();
#pragma unroll
        for (int q = 0; q < WD; q++) ldsm4t(w[16 + q], aW + owo(16 + q)); }
      if (f >= 8 && k == 3) SCHED(y0 & y1 & go, 40 + f);
      else if (f >= 7 && (f & 1)) FEN();
    });
  }
}

#undef sb
DEVINL void chain_helper(uint32_t sb, uint32_t px, int h, int j, const ArgsA& args, const CUtensorMap* tq, const CUtensorMap* tk, const CUtensorMap* tv, const CUtensorMap* to) {
  const int c = 2 * h + j;
  const uint32_t bW = sb + S_BAR + B_W, bS = sb + S_BAR + B_S, bKV = sb + S_BAR + B_KV;
  const uint32_t lane0 = opaque(threadIdx.x & 31);
  const uint32_t warp = __reduce_max_sync(~0u, (threadIdx.x >> 5) & 3);
  { const int tid = threadIdx.x - 256;
    if (tid == 0) { mbar_arrive_tx(bW, 98304); mbar_arrive_tx(bW + B_W2, 65536); mbar_arrive_tx(bW + B_WV, 81920); mbar_arrive_tx(bW + B_WO, 81920);
#pragma unroll 1
      for (int q = 0; q < 10; q++) { const int i = (q & 1) * 5 + (q >> 1); const uint32_t bar = q < 6 ? bW : bW + B_W2;
        tma_2d(sb + C_WV + i * 8192, tq, h * 128 + j * 64, i * 64, bar); tma_2d(sb + C_WO + i * 8192, tk, h * 128 + j * 64, i * 64, bar); } }
    uint32_t G0, C0; gtime(G0, C0);
    if (warp == 0) sts64(sb + C_R + 96, G0, C0);
    { const uint32_t g = lane0 >> 2, t = lane0 & 3;
      sts128(sb + C_T + 2048 + tid * 16, make_uint4(g1page(c >> 1) + (c & 1) * 2048 + (warp == 0 ? 0 : warp == 1 ? 0x30000 : 0x100000) + ((g >> 2) * 4 + t) * 64 + (g & 3) * 16,
                                                    g1page(((t >> 1) + (g >> 2) * 2) * 4 + warp) + G2_OFF + (c >> 4) * 1024 + (t & 1) * 512 + (c & 15) * 32 + (g & 3) * 8,
                                                    g1page((h & 3) * 4 + (warp == 2 ? 2 : 1)) + G2_OFF + (warp == 1 ? 1024 : warp == 3 ? 2048 : 0) + lane0 * 16, (g & 1) ? 0x3F800000u : 0x00003F80u)); }
    sts32(sb + C_R + 80, px); sts32(sb + C_R + 48, C0 - 65536);
#pragma unroll
    for (int kh = 0; kh < 2; kh++)
      sts64(sb + C_T + kh * 1024 + tid * 8, g1page(j * 16 + kh * 8 + (tid >> 4)) + (tid & 8) * 256 + h * 64 + (tid & 7) * 8, g1page((h & 3) * 4) + G2_OFF + kh * 2048 + tid * 16);
#pragma unroll
    for (int i = 0; i < 5; i++) { const int q = tid + i * 128, n = q & 7, d0 = (q >> 3) * 8; const uint4 v = *(const uint4*)(args.mem0 + n * 640 + d0); const uint32_t w[4] = {v.x, v.y, v.z, v.w};
#pragma unroll
      for (int e = 0; e < 8; e++) asm volatile("st.shared.u16 [%0], %1;" ::"r"(sb + C_M + (d0 + e) * 16 + n * 2), "h"((unsigned short)(w[e >> 1] >> ((e & 1) * 16))) : "memory"); }
    auto round2 = [&](int q0, int q1) {
#pragma unroll 1
      for (int q = q0; q < q1; q++) { const int i = (q & 1) * 5 + (q >> 1); tma_2d(sb + C_WV + i * 8192, tv, h * 128 + j * 64, i * 64, bW + B_WV); }
#pragma unroll 1
      for (int q = q0; q < q1; q++) { const int i = (q & 1) * 5 + (q >> 1); tma_2d(sb + C_WO + i * 8192, to, j * 320 + (i >> 1) * 64, h * 128 + ((i & 1) ^ j) * 64, bW + B_WO); } };
    if (warp == 0) { bar_sync(BAR_H, 288); if (tid == 0) round2(0, 6); __syncwarp(); }
    bar_sync(BAR_E, 384);
    if (tid == 0) round2(6, 10);
    if (warp == 3) {
      if (tid == 96) LOG(c, 250);
      flag_wait_warp(args.flags + F_KV + h, 2);
      load_kv(sb, h, j, 0); load_kv(sb, h, j, 1); if (tid == 96) LOG(c, 251);
    }
  }
  auto calib = [&]() { uint32_t G, C; gtime(G, C);
    const uint2 o = lds64(sb + C_R + 96); const float rt = (float)(C - o.y) * rcp((float)(G - o.x));
    sts128(sb + C_R + 32, make_uint4(G, C, __float2uint_rn(rt * 65536.f) & 0xffffu, __float_as_uint(rcp(rt)))); __syncwarp(); };
  auto do_export = [&](int s, uint32_t lane) {
    uint32_t k0[2][4], k1[2][4]; uint2 a[4], b[4];
    const uint32_t ak = sb + C_QK + 256 + (lane >> 4) * 512 + (lane & 15) * 16, av = sb + C_VP + (lane >> 3) * 512 + (lane & 7) * 8;
#pragma unroll
    for (int i = 0; i < 2; i++) { ldsm4t(k0[i], ak + i * 1024); ldsm4t(k1[i], ak + i * 1024 + 2048); }
#pragma unroll
    for (int i = 0; i < 4; i++) { a[i] = lds64(av + i * 64); b[i] = lds64(av + i * 64 + 256); }
    char* dst = g_kvm + ((s * 32 + h) * 4096 + j * 1024 + lane * 16);
    const uint32_t tg = (args.layer ^ 1) << 16;
    auto put = [&](char* q, uint32_t x, uint32_t y, uint32_t z, uint32_t w) { stg_rlx128(q, (x & ~0x10000u) | tg, y, (z & ~0x10000u) | tg, w); };
#pragma unroll
    for (int i = 0; i < 2; i++) put(dst + i * 512, hadd2bf(k0[i][0], k1[i][0]), hadd2bf(k0[i][1], k1[i][1]), hadd2bf(k0[i][2], k1[i][2]), hadd2bf(k0[i][3], k1[i][3]));
    put(dst + 2048, hadd2bf(a[0].x, b[0].x), hadd2bf(a[1].x, b[1].x), hadd2bf(a[2].x, b[2].x), hadd2bf(a[3].x, b[3].x));
    put(dst + 2560, hadd2bf(a[0].y, b[0].y), hadd2bf(a[1].y, b[1].y), hadd2bf(a[2].y, b[2].y), hadd2bf(a[3].y, b[3].y));
    stg_rlx32(args.flags + F_KM + h * 32 + j, s + 1);
  };
  auto staged = [&]() { if (warp == 2) bar_arrive(BAR_M3, 320); else if (warp == 1) { bar_arrive(BAR_M2, 160); bar_arrive(BAR_M2 + 1, 160); } else bar_arrive(BAR_M1 + (warp >> 1), 160); };
  if (warp == 0) calib();
  staged();
  bool kv_all = false;
  uint32_t vx[4][4];
  auto load_vx = [&](int s, uint32_t lane) {
    const uint32_t aVx = sb + C_KV + (s & 1) * 12288 + 4096 + (warp >> 1) * (j ? -4096 : 4096) + (warp & 1) * 1024 + lane * 16, zero = lane >> 5;
#pragma unroll
    for (int i = 0; i < 4; i++) { const uint4 q = lds128(aVx + (i & 1) * 2048 + (i >> 1) * 512); vx[i][0] = q.x ^ zero; vx[i][1] = q.z ^ zero; vx[i][2] = q.y ^ zero; vx[i][3] = q.w ^ zero; }
  };
  uint2 kb[4];
  auto prep = [&](int s, uint32_t lane) {
    if (s < 63) mbar_wait(bKV + (s & 1) * 8, (s >> 1) & 1);
    const uint32_t aK = sb + C_KV + (s & 1) * 12288 + j * 8192 + warp * 1024 + lane * 16;
#pragma unroll
    for (int i = 0; i < 4; i++) kb[i] = lds64(aK + ((warp ^ i) >> 1) * 512 + ((warp ^ i) & 1) * 8);
    if (VXE) load_vx(s, lane);
    asm volatile("{.reg .pred p; setp.eq.u32 p, %2, 32; @p mbarrier.arrive.expect_tx.shared::cta.b64 _, [%0], %1;}" ::"r"(bS), "r"(s < 63 ? 3072 : 2048), "r"(warp * 32 + lane) : "memory");
  };
  prep(0, lane0);
#pragma unroll 1
  for (int s = 0;; s++) {
    const uint32_t ph = s & 1;
    const uint32_t lane = __shfl_sync(~0u, lane0, lane0);
    const uint32_t mi = lane >> 3, r = lane & 7;
    const uint32_t aQ = sb + C_QK + (mi & 1) * 2048 + ((mi >> 1) * 8 + r) * 16;
    const uint32_t aKm = sb + C_QK + 256 + warp * 512 + (lane >> 4) * 2048 + (lane & 15) * 16;
    const uint32_t aH = sb + C_S + warp * 256 + lane * 8, aR = aH + 1024 + px;
    SCHED(aQ ^ aR ^ aKm, 60);
    if (warp == 0) {
      const uint4 cal = lds128(sb + C_R + 32);
      bar_sync(BAR_M3, 320);
      sts32(sb + C_R + 52, 0);
      const uint32_t E = clk(), e16 = cal.x + (uint32_t)__float2int_rn((float)(int)(E - cal.y) * __uint_as_float(cal.w));
      stg_rlx32(args.comm + TS_OFF + c * 4, e16); sts128(sb + C_R + 64, make_uint4(e16, E, cal.z, 0));
    }
    if (s == 63) { bar_sync(BAR_QK, 384); mbar_wait(bS, 1); if (warp == 3) do_export(63, lane); break; }
    {
      uint32_t qa[4][4], km[4]; float s0[4], s1[4], s2[4];
      bar_sync(BAR_QK, 384);
      ldsm4t(qa[0], aQ + warp * 512); ldsm4t(km, aKm); ldsm4t(qa[1], aQ + (warp ^ 1) * 512); ldsm4t(qa[2], aQ + (warp ^ 2) * 512); ldsm4t(qa[3], aQ + (warp ^ 3) * 512);
      mma16816z(s0, qa[0], kb[0].x, kb[0].y); mma16816z(s2, qa[0], km[0], km[1]); mma16816z(s1, qa[1], kb[1].x, kb[1].y);
      FEN();
      mma16816(s2, qa[0], km[2], km[3]); mma16816(s0, qa[2], kb[2].x, kb[2].y); mma16816(s1, qa[3], kb[3].x, kb[3].y);
      const uint32_t w0 = pack_bf16((s0[0] + s0[2]) + (s1[0] + s1[2]), (s0[1] + s0[3]) + (s1[1] + s1[3]));
      const uint32_t w1 = pack_bf16(s2[0] + s2[2], s2[1] + s2[3]);
      stasync64(aR, w0, w1, bS + px);
      sts64(aH, w0, w1);
    }
    {
      uint32_t sl[5];
      const uint32_t a8 = sb + lane * 8, av = a8 + C_VP + warp * 1024;
      const uint32_t aO = sb + C_O + ((warp >> 1) * 64 + (warp & 1) * 16 + (mi & 1) * 32 + (mi >> 1) * 8 + r) * 16, aU = sb + C_R + (lane & 28);
      bar_sync(BAR_X, 128);
      { uint2 t[4];
#pragma unroll
        for (int u = 0; u < 4; u++) t[u] = lds64(a8 + C_S + u * 256);
        if (!VXE) load_vx(s, lane);
#pragma unroll
        for (int u = 0; u < 4; u++) sl[u] = t[u].x;
        sl[4] = pack_bf16((bf_lo(t[0].y) + bf_lo(t[1].y)) + (bf_lo(t[2].y) + bf_lo(t[3].y)), (bf_hi(t[0].y) + bf_hi(t[1].y)) + (bf_hi(t[2].y) + bf_hi(t[3].y))); }
      mbar_wait(bS, ph);
      uint32_t vm[2][4];
      { uint2 t[4];
#pragma unroll
        for (int u = 0; u < 4; u++) t[u] = lds64(a8 + C_S + 1024 + u * 256);
#pragma unroll
        for (int u = 0; u < 4; u++) sl[u] = hadd2bf(sl[u], t[u].x);
        sl[4] = hadd2bf(hadd2bf(hadd2bf(sl[4], t[0].y), t[1].y), hadd2bf(t[2].y, t[3].y)); }
      uint32_t m2 = hmax2bf(hmax2bf(hmax2bf(sl[0], sl[1]), hmax2bf(sl[2], sl[3])), sl[4]);
      const uint32_t x1 = __shfl_xor_sync(~0u, m2, 1), x2 = __shfl_xor_sync(~0u, m2, 2), x3 = __shfl_xor_sync(~0u, m2, 3);
#pragma unroll
      for (int i = 0; i < 4; i++) { const uint2 q = lds64(av + i * 256); vm[i >> 1][(i & 1) * 2] = q.x; vm[i >> 1][(i & 1) * 2 + 1] = q.y; }
      float sv[10];
#pragma unroll
      for (int u = 0; u < 5; u++) { sv[2 * u] = bf_lo(sl[u]) * SM_SCALE; sv[2 * u + 1] = bf_hi(sl[u]) * SM_SCALE; }
      FEN();
      m2 = hmax2bf(hmax2bf(m2, x1), hmax2bf(x2, x3));
      const float mx = fmaxf(bf_lo(m2), bf_hi(m2));
      float o0[4], o1[4];
#pragma unroll
      for (int i = 0; i < 10; i++) sv[i] = fmaf(mx, -SM_SCALE, sv[i]);
      sv[8] = ex2v(sv[8]); sv[9] = ex2v(sv[9]);
#pragma unroll
      for (int i = 0; i < 8; i++) sv[i] = ex2v(sv[i]);
      { const uint32_t p = pack_bf16(sv[8], sv[9]); mma16816z(o0, vm[0], p, p); mma16816z(o1, vm[1], p, p); }
      { const uint32_t p0 = pack_bf16(sv[0], sv[1]), p1 = pack_bf16(sv[2], sv[3]); mma16816(o0, vx[0], p0, p1); mma16816(o1, vx[2], p0, p1); }
      { const uint32_t p0 = pack_bf16(sv[4], sv[5]), p1 = pack_bf16(sv[6], sv[7]); mma16816(o0, vx[1], p0, p1); mma16816(o1, vx[3], p0, p1); }
      float su = (((sv[8] + sv[9]) + ((sv[0] + sv[1]) + (sv[2] + sv[3]))) + (sv[4] + sv[5])) + (sv[6] + sv[7]);
      { const float a1 = __shfl_xor_sync(~0u, su, 1), a2 = __shfl_xor_sync(~0u, su, 2), a3 = __shfl_xor_sync(~0u, su, 3); su = (su + a1) + (a2 + a3); }
      sts32(aU + 128, __float_as_uint(su));
      stsm4(aO, pack_bf16(o0[0], o0[1]), pack_bf16(o0[2], o0[3]), pack_bf16(o1[0], o1[1]), pack_bf16(o1[2], o1[3]));
      bar_sync(BAR_O, 384);
    }
    const uint32_t t0 = lds32(sb + C_R + 48);
    const uint4 xo = lds128(sb + C_T + 2048 + warp * 512 + lane * 16);
    const uint32_t tag = (s + args.layer + 1) & 1, tm = 0u - tag;
    if (warp == 3) {
      if (lane == 0) { LOGS(c, s); LOGV(c, 192 + (s >> 1), clk()); }
      spin_until(t0 + args.tc[0]);
      do_export(s, lane);
      if (lane == 0) LOG(c, 64 + s);
    }
    if (warp == 2) calib();
    if (warp < 2 || (warp == 2 && !(c & 16))) {
      const char* p = args.comm + xo.x; char* g2w = args.comm + xo.y;
      const uint32_t s0 = (lane & 8) ? 0u : xo.w, s1 = (lane & 8) ? xo.w : 0u;
      int lim = 0; bool bad;
      p += wait_until(t0 + args.ta[warp == 0 ? 0 : warp == 2 ? 3 : 1 + ((c >> 4) & 1)], lane >> 5);
      do {
        uint4 a[4]; float z0[4], z1[4], y[4];
#pragma unroll
        for (int i = 0; i < 4; i++) a[i] = ldg_rlx128(p + i * 512);
        ++lim;
        { const uint32_t A[4] = {a[0].x, a[0].y, a[0].z, a[0].w}; mma16816z(z0, A, s0, s1); }
        { const uint32_t A[4] = {a[1].x, a[1].y, a[1].z, a[1].w}; mma16816z(z1, A, s0, s1); }
        { const uint32_t A[4] = {a[2].x, a[2].y, a[2].z, a[2].w}; mma16816(z0, A, s0, s1); }
        { const uint32_t A[4] = {a[3].x, a[3].y, a[3].z, a[3].w}; mma16816(z1, A, s0, s1); }
        const uint32_t m0 = launder((a[0].x ^ tm) | (a[0].z ^ tm)), m1 = launder((a[1].x ^ tm) | (a[1].z ^ tm)), m2 = launder((a[2].x ^ tm) | (a[2].z ^ tm)), m3 = launder((a[3].x ^ tm) | (a[3].z ^ tm));
        bad = __any_sync(~0u, ((launder(m0 | m1 | m2) | m3) & 0x10000u) && lim < POLL_LIMIT);
#pragma unroll
        for (int i = 0; i < 4; i++) y[i] = z0[i] + z1[i];
        const bool odd = lane & 1; const float k0 = odd ? y[2] : y[0], k1 = odd ? y[3] : y[1], e0 = odd ? y[0] : y[2], e1 = odd ? y[1] : y[3];
        const float o0 = __shfl_xor_sync(~0u, e0, 1) + __shfl_xor_sync(~0u, e0, 17), o1 = __shfl_xor_sync(~0u, e1, 1) + __shfl_xor_sync(~0u, e1, 17);
        const float q0 = k0 + __shfl_xor_sync(~0u, k0, 16), q1 = k1 + __shfl_xor_sync(~0u, k1, 16);
        const uint32_t w0 = pack_tag(odd ? o0 : q0, odd ? o1 : q1, tag << 16), w1 = pack_bf16(odd ? q0 : o0, odd ? q1 : o1);
        if (!bad) stg_rlx64(g2w, w0, w1);
      } while (bad);
      if (lane == 0 && warp == 0) LOGV(c, 128 + s, lim);
      if (lane == 0) { EV(warp, clk() - t0); EV(3 + warp, lim); }
    }
    if (!PRP || warp != 1) prep(s + 1, lane); else kb[0] = kb[1] = kb[2] = kb[3] = make_uint2(0, 0);
    {
      const char* p = args.comm + xo.z;
      const uint32_t aMw = sb + C_M + 2048 + (warp == 3 ? 5120 : warp * 1024) + lane * 16;
      int lim = 0; bool bad;
      p += wait_until(t0 + args.tb[warp == 3 ? 1 : warp + 1], lane >> 5);
      if (warp == 0 || warp == 3) {
        do { const uint4 a = ldg_rlx128(p), b = ldg_rlx128(p + 512); ++lim;
          sts128(aMw, a); sts128(aMw + 512, b);
          bad = __any_sync(~0u, ((launder((a.x ^ tm) | (a.z ^ tm)) | launder((b.x ^ tm) | (b.z ^ tm))) & 0x10000u) && lim < POLL_LIMIT);
        } while (bad);
      } else {
        do { uint4 a[4]; uint32_t m[4]; ++lim;
#pragma unroll
          for (int i = 0; i < 4; i++) a[i] = ldg_rlx128(p + (i & 1) * 512 + (i >> 1) * 2048);
#pragma unroll
          for (int i = 0; i < 4; i++) { sts128(aMw + (i & 1) * 512 + (i >> 1) * 5120, a[i]); m[i] = launder((a[i].x ^ tm) | (a[i].z ^ tm)); }
          bad = __any_sync(~0u, ((launder(m[0] | m[1] | m[2]) | m[3]) & 0x10000u) && lim < POLL_LIMIT);
        } while (bad);
      }
      staged();
      if (lane == 0 && warp < 3) { EV(6 + warp, clk() - t0); EV(9 + warp, lim); }
    }
    if (PRP && warp == 1) prep(s + 1, lane);
    if (warp == 3) {
      const bool chk = !ph && !kv_all;
      const uint32_t* f = args.flags + F_KV + (lane < 2 ? 30 + lane : min((s + 2) >> 1, 31)) * 32 + h;
      if (chk) {
        uint32_t rdy; int n = 0;
        do rdy = ldg_rlx32(f); while (__any_sync(~0u, lane >= 2 && rdy < 2 && ++n < POLL_LIMIT));
        kv_all = __all_sync(~0u, rdy >= 2);
      }
      spin_until(t0 + args.tc[1]);
      if (chk) asm volatile("fence.acquire.gpu;" ::: "memory");
      if (s < 61) load_kv(sb, h, j, s + 2);
    }
  }
}

#define PDLAT 2
#define NPROBE 3
#define OPACE 400
constexpr int G_ST = 163840;
constexpr int B_FULL = 64, B_EMPTY = 96, B_WD = 136, B_ROLE = 144, B_PROG = 148, B_WF = 160  ;
enum { BAR_T = 1  , BAR_G = 3  , BAR_V = 5   };
DEVINL uint64_t mkdesc(uint32_t a, uint32_t lbo, uint32_t sbo, uint32_t sw) { return (uint64_t)((a & 0x3FFFF) >> 4) | ((uint64_t)(lbo >> 4) << 16) | ((uint64_t)(sbo >> 4) << 32) | ((uint64_t)sw << 62); }
DEVINL void wgmma_n128(float* d, uint64_t a, uint64_t b, int acc) {
  asm volatile("{.reg .pred p; setp.ne.b32 p, %66, 0; wgmma.mma_async.sync.aligned.m64n128k16.f32.bf16.bf16 {%0,%1,%2,%3,%4,%5,%6,%7,%8,%9,%10,%11,%12,%13,%14,%15,%16,%17,%18,%19,%20,%21,%22,%23,%24,%25,%26,%27,%28,%29,%30,%31,%32,%33,%34,%35,%36,%37,%38,%39,%40,%41,%42,%43,%44,%45,%46,%47,%48,%49,%50,%51,%52,%53,%54,%55,%56,%57,%58,%59,%60,%61,%62,%63}, %64, %65, p, 1, 1, 0, 1;}"
               : "+f"(d[0]),"+f"(d[1]),"+f"(d[2]),"+f"(d[3]),"+f"(d[4]),"+f"(d[5]),"+f"(d[6]),"+f"(d[7]),"+f"(d[8]),"+f"(d[9]),"+f"(d[10]),"+f"(d[11]),"+f"(d[12]),"+f"(d[13]),"+f"(d[14]),"+f"(d[15]),"+f"(d[16]),"+f"(d[17]),"+f"(d[18]),"+f"(d[19]),"+f"(d[20]),"+f"(d[21]),"+f"(d[22]),"+f"(d[23]),"+f"(d[24]),"+f"(d[25]),"+f"(d[26]),"+f"(d[27]),"+f"(d[28]),"+f"(d[29]),"+f"(d[30]),"+f"(d[31]),"+f"(d[32]),"+f"(d[33]),"+f"(d[34]),"+f"(d[35]),"+f"(d[36]),"+f"(d[37]),"+f"(d[38]),"+f"(d[39]),"+f"(d[40]),"+f"(d[41]),"+f"(d[42]),"+f"(d[43]),"+f"(d[44]),"+f"(d[45]),"+f"(d[46]),"+f"(d[47]),"+f"(d[48]),"+f"(d[49]),"+f"(d[50]),"+f"(d[51]),"+f"(d[52]),"+f"(d[53]),"+f"(d[54]),"+f"(d[55]),"+f"(d[56]),"+f"(d[57]),"+f"(d[58]),"+f"(d[59]),"+f"(d[60]),"+f"(d[61]),"+f"(d[62]),"+f"(d[63]) : "l"(a), "l"(b), "r"(acc));
}
DEVINL void wgmma_n80(float* d, uint64_t a, uint64_t b, int acc) {
  asm volatile("{.reg .pred p; setp.ne.b32 p, %42, 0; wgmma.mma_async.sync.aligned.m64n80k16.f32.bf16.bf16 {%0,%1,%2,%3,%4,%5,%6,%7,%8,%9,%10,%11,%12,%13,%14,%15,%16,%17,%18,%19,%20,%21,%22,%23,%24,%25,%26,%27,%28,%29,%30,%31,%32,%33,%34,%35,%36,%37,%38,%39}, %40, %41, p, 1, 1, 0, 1;}"
               : "+f"(d[0]),"+f"(d[1]),"+f"(d[2]),"+f"(d[3]),"+f"(d[4]),"+f"(d[5]),"+f"(d[6]),"+f"(d[7]),"+f"(d[8]),"+f"(d[9]),"+f"(d[10]),"+f"(d[11]),"+f"(d[12]),"+f"(d[13]),"+f"(d[14]),"+f"(d[15]),"+f"(d[16]),"+f"(d[17]),"+f"(d[18]),"+f"(d[19]),"+f"(d[20]),"+f"(d[21]),"+f"(d[22]),"+f"(d[23]),"+f"(d[24]),"+f"(d[25]),"+f"(d[26]),"+f"(d[27]),"+f"(d[28]),"+f"(d[29]),"+f"(d[30]),"+f"(d[31]),"+f"(d[32]),"+f"(d[33]),"+f"(d[34]),"+f"(d[35]),"+f"(d[36]),"+f"(d[37]),"+f"(d[38]),"+f"(d[39]) : "l"(a), "l"(b), "r"(acc));
}

template <int N, int NST, bool HAND>
DEVINL void gemm_tile(float* acc, uint32_t sb, uint32_t px, int wg, uint32_t u0, int rot, bool lead, int wph) {
  const uint64_t db = N == 128 ? mkdesc(sb, 81920, 1024, 1) : mkdesc(sb, 32768, 256, 3);
#pragma unroll
  for (int i = 0; i < N / 2; i++) acc[i] = 0.f;
  bar_sync(BAR_T + wg, 256);
#pragma unroll 1
  for (int st = 0; st < NST; st++) {
    const uint32_t u = u0 + st, slot = u & 3, ks = (st + rot >= NST ? st + rot - NST : st + rot) * 8;
    if (wph >= 0) mbar_wait(sb + S_BAR + B_WF + (N == 128 ? st * 8 : 0), wph);
    mbar_wait(sb + S_BAR + B_FULL + slot * 8, (u >> 2) & 1);
    const uint64_t da = mkdesc(sb + G_ST + slot * 16384, 16, 1024, 1);
    asm volatile("wgmma.fence.sync.aligned;" ::: "memory");
#pragma unroll
    for (int k = 0; k < 8; k++) {
      const uint64_t a = da + (k >> 2) * 512 + (k & 3) * 2;
      if (N == 128) wgmma_n128(acc, a, db + (ks + k) * 128, 1); else wgmma_n80(acc, a, db + (ks + k) * 32, 1);
    }
    asm volatile("wgmma.commit_group.sync.aligned;" ::: "memory");
    if (HAND && st == NST - 1) bar_arrive(BAR_T + (wg ^ 1), 256);
    if (st > 0) {
      asm volatile("wgmma.wait_group.sync.aligned 1;" ::: "memory");
      if (lead) { const uint32_t e = sb + S_BAR + B_EMPTY + ((u - 1) & 3) * 8; mbar_arrive(e); mbar_arrive_remote(e + px); }
    }
  }
  asm volatile("wgmma.wait_group.sync.aligned 0;" ::: "memory");
  if (lead) { const uint32_t e = sb + S_BAR + B_EMPTY + ((u0 + NST - 1) & 3) * 8; mbar_arrive(e); mbar_arrive_remote(e + px); }
}
DEVINL void wg_publish(int wg) { bar_sync(BAR_G + wg, 160); }
DEVINL uint32_t km_known(uint32_t sb) { uint32_t v; asm volatile("ld.volatile.shared.u32 %0, [%1];" : "=r"(v) : "r"(sb + S_BAR + B_PROG) : "memory"); return __reduce_min_sync(~0u, v); }
DEVINL void km_load(uint4* f, const char* p) {
#pragma unroll
  for (int G = 0; G < 4; G++) f[G] = ldg_rlx128(p + G * 512);
}
DEVINL void km_check(uint4* f, const char* p, uint32_t tg) {
  int n = 0;
  while (__any_sync(~0u, (((f[0].x ^ tg) | (f[0].z ^ tg) | (f[1].x ^ tg) | (f[1].z ^ tg) | (f[2].x ^ tg) | (f[2].z ^ tg) | (f[3].x ^ tg) | (f[3].z ^ tg)) & 0x10000u) && ++n < POLL_LIMIT)) km_load(f, p);
}
DEVINL void km_watcher(uint32_t sb, const uint32_t* p) {
  uint32_t v = 0;
#pragma unroll 1
  for (int n = 0; n < 16 * POLL_LIMIT && v < 64; n++) {
    const uint2 q = ldg_rlx64(p);
    if (min(q.x, q.y) != v) { v = min(q.x, q.y); asm volatile("st.volatile.shared.u32 [%0], %1;" ::"r"(sb + S_BAR + B_PROG), "r"(v) : "memory"); }
    __nanosleep(v < 61 ? 300 : 20);
  }
}

template <int HF>
DEVINL void attend(const float* acc, uint4 (*kf)[4], uint4* kmf, uint4* op, const char* kvp, const char* mp, bf16* orow, int lane, int wg, uint32_t sb, int tile, bool& pend, uint32_t tg) {
  constexpr int NT = HF ? 4 : 2;
  const int g = lane >> 2, t = lane & 3;
  km_check(kmf, mp + lane * 16, tg);
  float sc[NT + 1][4];
#pragma unroll
  for (int k = 0; k < 8; k++) {
    uint32_t qa[4];
#pragma unroll
    for (int i = 0; i < 4; i++) { const float* a = acc + 32 * (k >> 2) + 4 * (k & 3) + 16 * (i >> 1) + 2 * (i & 1); qa[i] = pack_bf16(a[0], a[1]); }
#pragma unroll
    for (int kt = 0; kt <= NT; kt++) {
      const uint4 b = kt < NT ? kf[kt][k >> 1] : kmf[k >> 1];
      if (k == 0) mma16816z(sc[kt], qa, b.x, b.y); else if (k & 1) mma16816(sc[kt], qa, b.z, b.w); else mma16816(sc[kt], qa, b.x, b.y);
    }
  }
  FEN();
  bar_arrive(BAR_T + (wg ^ 1), 256);
  if (pend) {
#pragma unroll
    for (int q = 0; q < 4; q++) { *(uint4*)(orow - 128 * 4096 + q * 32) = op[2 * q]; *(uint4*)(orow - 120 * 4096 + q * 32) = op[2 * q + 1]; }
    wg_publish(wg);
  }
  {
    uint32_t go; asm volatile("{.reg .pred p,q; setp.ne.u32 q, %1, 0; bar.red.and.pred p, %2, 128, q; selp.u32 %0, 1, 0, p;}" : "=r"(go) : "r"((uint32_t)(tile < 30 && km_known(sb) > tile * 2 + 5)), "r"(BAR_V + wg) : "memory");
    pend = __reduce_max_sync(~0u, go); }
  uint4 vf[HF + 1][8], vm[4];
  const char* vp = kvp + 4096 + (g >> 1) * 512 + ((g & 1) * 4 + t) * 16;
  km_load(vm, mp + 2048 + lane * 16);
#pragma unroll
  for (int i = 0; i < 8; i++) vf[0][i] = ldg_ca128(vp + (i >> 2) * 4096 + (i & 3) * 128);
  if (tile < 30) {
#pragma unroll
    for (int i = 0; i < 8; i++) kf[i >> 2][i & 3] = ldg_ca128(kvp + 4 * 32 * 16384 + ((i >> 1) & 1) * 12288 + (i >> 2) * 1024 + (i & 1) * 512 + lane * 16);
  }
  if (pend) km_load(kmf, mp + 4 * 32 * 4096 + lane * 16);
  if (HF) {
#pragma unroll
    for (int i = 0; i < 8; i++) vf[HF][i] = ldg_cg128(vp + 2048 + (i >> 2) * 4096 + (i & 3) * 128);
    if (tile < 30) {
#pragma unroll
      for (int i = 8; i < 16; i++) kf[i >> 2][i & 3] = ldg_cg128(kvp + 4 * 32 * 16384 + ((i >> 1) & 1) * 12288 + (i >> 2) * 1024 + (i & 1) * 512 + lane * 16);
    }
  }
  const float NINF = __int_as_float(0xff800000);
  if (2 * t > g) { sc[NT - 2][0] = NINF; sc[NT - 1][2] = NINF; }
  if (2 * t + 1 > g) { sc[NT - 2][1] = NINF; sc[NT - 1][3] = NINF; }
  sc[NT - 1][0] = NINF; sc[NT - 1][1] = NINF;
  float m0 = fmaxf(sc[NT][0], sc[NT][1]), m1 = fmaxf(sc[NT][2], sc[NT][3]);
#pragma unroll
  for (int kt = 0; kt < NT; kt++) { m0 = fmaxf(m0, fmaxf(sc[kt][0], sc[kt][1])); m1 = fmaxf(m1, fmaxf(sc[kt][2], sc[kt][3])); }
  m0 = fmaxf(fmaxf(m0, __shfl_xor_sync(~0u, m0, 1)), fmaxf(__shfl_xor_sync(~0u, m0, 2), __shfl_xor_sync(~0u, m0, 3)));
  m1 = fmaxf(fmaxf(m1, __shfl_xor_sync(~0u, m1, 1)), fmaxf(__shfl_xor_sync(~0u, m1, 2), __shfl_xor_sync(~0u, m1, 3)));
  m0 *= -SM_SCALE; m1 *= -SM_SCALE;
  float s0 = 0.f, s1 = 0.f; uint32_t p[NT + 1][2];
#pragma unroll
  for (int kt = 0; kt <= NT; kt++) {
    const float a = ex2(fmaf(sc[kt][0], SM_SCALE, m0)), b = ex2(fmaf(sc[kt][1], SM_SCALE, m0)), c = ex2(fmaf(sc[kt][2], SM_SCALE, m1)), d = ex2(fmaf(sc[kt][3], SM_SCALE, m1));
    s0 += a + b; s1 += c + d; p[kt][0] = pack_bf16(a, b); p[kt][1] = pack_bf16(c, d);
  }
  s0 = (s0 + __shfl_xor_sync(~0u, s0, 1)) + (__shfl_xor_sync(~0u, s0, 2) + __shfl_xor_sync(~0u, s0, 3));
  s1 = (s1 + __shfl_xor_sync(~0u, s1, 1)) + (__shfl_xor_sync(~0u, s1, 2) + __shfl_xor_sync(~0u, s1, 3));
  s0 = rcp(s0); s1 = rcp(s1);
  km_check(vm, mp + 2048 + lane * 16, tg);
#pragma unroll
  for (int grp = 0; grp < 4; grp++) {
    float o[4][4];
#pragma unroll
    for (int L = 0; L < 4; L++) {
      mma1688z(o[L], p[NT][0], p[NT][1], L == 0 ? vm[grp].x : L == 1 ? vm[grp].y : L == 2 ? vm[grp].z : vm[grp].w);
#pragma unroll
      for (int kh = 0; kh <= HF; kh++) {
        const uint4 w = vf[kh][(grp >> 1) * 4 + L]; const uint32_t A[4] = {p[2 * kh][0], p[2 * kh][1], p[2 * kh + 1][0], p[2 * kh + 1][1]};
        if (grp & 1) mma16816(o[L], A, w.z, w.w); else mma16816(o[L], A, w.x, w.y);
      }
    }
    op[2 * grp] = make_uint4(pack_bf16(o[0][0] * s0, o[0][1] * s0), pack_bf16(o[1][0] * s0, o[1][1] * s0), pack_bf16(o[2][0] * s0, o[2][1] * s0), pack_bf16(o[3][0] * s0, o[3][1] * s0));
    op[2 * grp + 1] = make_uint4(pack_bf16(o[0][2] * s1, o[0][3] * s1), pack_bf16(o[1][2] * s1, o[1][3] * s1), pack_bf16(o[2][2] * s1, o[2][3] * s1), pack_bf16(o[3][2] * s1, o[3][3] * s1));
  }
}

DEVINL void gemm_consumer(uint32_t sb, uint32_t px, int wg, int pr, int rank, const ArgsA& args) {
  const int lane = opaque(threadIdx.x & 31), w = __reduce_max_sync(~0u, (threadIdx.x >> 5) & 3);
  const bool lead = lane == 0 && w == 0;
  const int rot5 = pr % 5;
  if (wg == 1) bar_arrive(BAR_T, 256);
  if (threadIdx.x == 0) LOG(64 + pr * 2 + rank, 250);
#pragma unroll 1
  for (int tile = wg; tile < 32; tile += 2) {
    float acc[64];
    gemm_tile<128, 5, true>(acc, sb, px, wg, tile * 5, rot5, lead, tile < 2 ? 0 : -1);
    if (tile >= 30 && lead) mbar_arrive(sb + S_BAR + B_WD);
    char* dst = g_kv + (size_t)((tile * 2 + (w >> 1)) * 32 + pr) * 16384 + (w & 1) * 2048 + lane * 16;
    if (rank == 0) {
#pragma unroll
      for (int G = 0; G < 4; G++)
#pragma unroll
        for (int hh = 0; hh < 2; hh++) {
          const float* a = acc + 32 * (G >> 1) + 8 * (G & 1) + 2 * hh;
          *(uint4*)(dst + (G >> 1) * 12288 + hh * 1024 + (G & 1) * 512) = make_uint4(pack_bf16(a[0], a[1]), pack_bf16(a[16], a[17]), pack_bf16(a[4], a[5]), pack_bf16(a[20], a[21]));
        }
    } else {
#pragma unroll
      for (int i = 0; i < 8; i++) {
        const float* a = acc + (i >> 2) * 32 + (i & 3) * 4;
        *(uint4*)(dst + 4096 + (i >> 2) * 4096 + (i & 3) * 512) = make_uint4(movm(pack_bf16(a[0], a[1])), movm(pack_bf16(a[2], a[3])), movm(pack_bf16(a[16], a[17])), movm(pack_bf16(a[18], a[19])));
      }
    }
    wg_publish(wg);
    if ((threadIdx.x & 127) == 0) LOG(64 + pr * 2 + rank, tile);
  }
  if (threadIdx.x == 0) LOG(64 + pr * 2 + rank, 251);
  if (pr < 16) {
    const int h = 2 * pr + rank;
    flag_wait_warp(args.flags + F_KV + (16 + (lane & 1)) * 32 + h, 2);
    bool pend = false; uint4 op[8], kf[4][4], kmf[4];
#pragma unroll
    for (int i = 0; i < 16; i++) kf[i >> 2][i & 3] = ldg_cg128(g_kv + (size_t)((wg * 2 + (w >> 1)) * 32 + h) * 16384 + ((i >> 1) & 1) * 12288 + (i >> 2) * 1024 + (i & 1) * 512 + lane * 16);
#pragma unroll
    for (int i = 0; i < 8; i++) op[i] = kmf[i & 3] = make_uint4(0, 0, 0, 0);
#pragma unroll 1
    for (int tile = wg; tile < 32; tile += 2) {
      const uint32_t seg = tile * 2 + (w >> 1);
      const char* kvp = g_kv + (size_t)(seg * 32 + h) * 16384;
      const char* mp = g_kvm + (size_t)(seg * 32 + h) * 4096;
      bf16* orow = g_o + (size_t)(tile * 64 + w * 16 + (lane >> 2)) * 4096 + h * 128 + (lane & 3) * 8;
      if ((tile >> 1) == 6) flag_wait_warp(args.flags + F_KV + (30 + (lane & 1)) * 32 + h, 2);
      float acc[64];
      gemm_tile<128, 5, false>(acc, sb, px, wg, 160 + tile * 5, rot5, lead, tile < 2 ? 1 : -1);
      if ((threadIdx.x & 127) == 96) LOG(64 + pr * 2 + rank, 64 + tile);
      if (!pend) {
        int n = 0;
        while (km_known(sb) <= seg && ++n < 16 * POLL_LIMIT) {}
        km_load(kmf, mp + lane * 16);
      }
      if ((threadIdx.x & 127) == 96) LOG(64 + pr * 2 + rank, 96 + tile);
      if (w & 1) attend<1>(acc, kf, kmf, op, kvp, mp, orow, lane, wg, sb, tile, pend, (args.layer ^ 1) << 16); else attend<0>(acc, kf, kmf, op, kvp, mp, orow, lane, wg, sb, tile, pend, (args.layer ^ 1) << 16);
      if (!pend) {
#pragma unroll
        for (int q = 0; q < 4; q++) { *(uint4*)(orow + q * 32) = op[2 * q]; *(uint4*)(orow + 8 * 4096 + q * 32) = op[2 * q + 1]; }
        wg_publish(wg);
      }
      if ((threadIdx.x & 127) == 0) LOG(64 + pr * 2 + rank, 32 + tile);
    }
  } else {
    const int kq = (pr - 16) >> 2, cg = 2 * (pr & 3) + rank;
#pragma unroll 1
    for (int tile = wg; tile < 32; tile += 2) {
      float acc[40];
      gemm_tile<80, 8, true>(acc, sb, px, wg, 160 + tile * 8, (pr & 3) * 2, lead, tile < 2 ? 1 : -1);
      const bool odd = lane & 1;
      bf16* dst = g_part + (size_t)(kq * 2048 + tile * 64 + w * 16 + (lane >> 2)) * 640 + cg * 80 + (lane & 1) * 8 + (lane & 2) * 2;
#pragma unroll
      for (int q = 0; q < 5; q++)
#pragma unroll
        for (int hh = 0; hh < 2; hh++) {
          const uint32_t A = pack_bf16(acc[8 * q + 2 * hh], acc[8 * q + 2 * hh + 1]), B = pack_bf16(acc[8 * q + 4 + 2 * hh], acc[8 * q + 5 + 2 * hh]);
          const uint32_t x = __shfl_xor_sync(~0u, odd ? A : B, 1);
          *(uint2*)(dst + hh * 8 * 640 + q * 16) = odd ? make_uint2(x, B) : make_uint2(A, x);
        }
      wg_publish(wg);
      if ((threadIdx.x & 127) == 0) LOG(64 + pr * 2 + rank, 32 + tile);
    }
  }
  if (wg == 0) bar_sync(BAR_T, 256);
}

DEVINL void gemm_producer(uint32_t sb, int pr, int rank, const ArgsA& args, const CUtensorMap* tq, const CUtensorMap* tk, const CUtensorMap* tv,
                          const CUtensorMap* to32, const CUtensorMap* tx, const CUtensorMap* tao) {
  const uint32_t bWF = sb + S_BAR + B_WF;
  auto load_w = [&](const CUtensorMap* tm, int col, int st) {
    const int r = ((st + pr) % 5) * 2; mbar_arrive_tx(bWF + st * 8, 32768);
#pragma unroll 1
    for (int i = 0; i < 4; i++) tma_2d(sb + (i & 1) * 81920 + (r + (i >> 1)) * 8192, tm, col + (i & 1) * 64, (r + (i >> 1)) * 64, bWF + st * 8); };
  uint32_t u = 0;
  auto push = [&](const CUtensorMap* tm, int c0, int c1) {
    const uint32_t slot = u & 3, full = sb + S_BAR + B_FULL + slot * 8;
    mbar_wait(sb + S_BAR + B_EMPTY + slot * 8, ((u >> 2) & 1) ^ 1);
    mbar_arrive_tx(full, 16384);
    tma_2d_mc(sb + G_ST + slot * 16384 + rank * 8192, tm, c0 + rank * 64, c1, full);
    u++; };
#pragma unroll 1
  for (int st = 0; st < 5; st++) load_w(rank ? tv : tk, pr * 128, st);
  if (args.layer == 0) { flag_wait(args.flags + F_X, 128); fence_proxy_async(); } else pdl_wait();
#pragma unroll 1
  for (int tile = 0; tile < 32; tile++) {
    l2_prefetch((const char*)g_xn + ((tile + 2) & 31) * 81920 + (pr * 2 + rank) * 1280, 1280);
    if (tile >= 20 && tile < 30) l2_prefetch((rank ? args.wo : args.wq) + (pr * 10 + tile - 20) * 16384, 16384);
#pragma unroll 1
    for (int st = 0; st < 5; st++) push(tx, ((st + pr) % 5) * 128, tile * 64);
  }
  pdl_launch();
  if (pr < 16) {
    load_w(tq, (2 * pr + rank) * 128, 0);
#pragma unroll 1
    for (int tile = 0; tile < 32; tile++) {
      if (tile < 30) {
        l2_prefetch((const char*)g_xn + (tile + 2) * 81920 + (pr * 2 + rank) * 2560, 2560);
        const int q = (tile * 2 + 4) * 32 + 2 * pr + rank;
        l2_prefetch(g_kv + (size_t)q * 16384, 16384); l2_prefetch(g_kv + (size_t)(q + 32) * 16384, 16384);
        if (lds32(sb + S_BAR + B_PROG) > tile * 2 + 5) { l2_prefetch(g_kvm + (size_t)q * 4096, 4096); l2_prefetch(g_kvm + (size_t)(q + 32) * 4096, 4096); }
      }
#pragma unroll 1
      for (int st = 0; st < 5; st++) { push(tx, ((st + pr) % 5) * 128, tile * 64); if (tile == 0 && st < 4) load_w(tq, (2 * pr + rank) * 128, st + 1); }
    }
  } else {
    const int kq = (pr - 16) >> 2, cg = 2 * (pr & 3) + rank;
    mbar_wait(sb + S_BAR + B_WD, 0);
    mbar_arrive_tx(bWF, 163840);
#pragma unroll 1
    for (int i = 0; i < 20; i++) { tma_2d(sb + (i % 5) * 32768 + (i / 5) * 8192, to32, cg * 80 + (i % 5) * 16, kq * 1024 + (i / 5) * 256, bWF); __nanosleep(OPACE); }
#pragma unroll 1
    for (int tile = 0; tile < 32; tile++) {
      flag_wait(args.flags + F_O + tile * 4 + kq, 8);
      fence_proxy_async();
#pragma unroll 1
      for (int st = 0; st < 8; st++) push(tao, kq * 1024 + ((st + (pr & 3) * 2) & 7) * 128, tile * 64);
    }
  }
#pragma unroll 1
  for (int i = 0; i < 4; i++, u++) mbar_wait(sb + S_BAR + B_EMPTY + (u & 3) * 8, ((u >> 2) & 1) ^ 1);
}

DEVINL void gemm_publisher(int wg, int pr, int rank, const ArgsA& args) {
#pragma unroll 1
  for (int i = 0; i < 32; i++) {
    const int tile = (i & 15) * 2 + wg;
    bar_sync(BAR_G + wg, 160);
    if ((threadIdx.x & 31) == 0) {
      flag_add(args.flags + (i < 16 ? F_KV + tile * 32 + pr : pr < 16 ? F_O + tile * 4 + (pr >> 2) : F_P + tile * 32));
    }
    __syncwarp();
  }
}

DEVINL void filter_prep(uint32_t* sm, int part, const ArgsA& args) {
  const int tid = threadIdx.x, lane = tid & 31, w = tid >> 5;
  const unsigned short* wr = (const unsigned short*)args.wr; const unsigned short* wi = (const unsigned short*)args.wi;
#pragma unroll 1
  for (int it = part; it < 32; it += 4) {
#pragma unroll 1
    for (int rr = 0; rr < 8; rr += 2) {
      uint32_t a[2][11], b[2][11];
#pragma unroll
      for (int r = 0; r < 2; r++) {
        const int pos = it * 64 + w * 8 + rr + r, th = (pos >> 2) & 127, v = (pos >> 9) * 4 + (pos & 3);
        const int o = ((th >> 3) + 16 * ((th & 7) + (v & 8)) + 256 * (v & 7)) * 321 + lane;
#pragma unroll
        for (int c = 0; c < 11; c++) if (c < 10 || lane == 0) { a[r][c] = wr[o + c * 32]; b[r][c] = wi[o + c * 32]; }
      }
#pragma unroll
      for (int r = 0; r < 2; r++)
#pragma unroll
        for (int c = 0; c < 11; c++) if (c < 10 || lane == 0) sm[(c * 32 + lane) * 65 + w * 8 + rr + r] = a[r][c] | (b[r][c] << 16);
    }
    bar_sync(1, 256);
#pragma unroll 2
    for (int i = tid; i < 64 * 321; i += 256) g_wt[(i >> 6) * 2048 + it * 64 + (i & 63)] = sm[(i >> 6) * 65 + (i & 63)];
    bar_sync(1, 256);
  }
}

__global__ void __cluster_dims__(2, 1, 1) __launch_bounds__(384, 1)
layer_a_kernel(const __grid_constant__ CUtensorMap tq, const __grid_constant__ CUtensorMap tk, const __grid_constant__ CUtensorMap tv,
               const __grid_constant__ CUtensorMap to, const __grid_constant__ CUtensorMap to32, const __grid_constant__ CUtensorMap tx,
               const __grid_constant__ CUtensorMap tao, const __grid_constant__ ArgsA args) {
  extern __shared__ __align__(1024) char smraw[];
  const uint32_t sb = (smem_u32(smraw) + 1023) & ~1023u;
  uint32_t rank; asm volatile("mov.u32 %0, %%cluster_ctarank;" : "=r"(rank));
  rank = __reduce_max_sync(~0u, rank);
  const uint32_t px = __reduce_max_sync(~0u, mapa(sb, rank ^ 1) - sb);
  if (PDLAT == 0) pdl_launch();
  if (args.layer == 0) LOGK(0, 0);
  uint32_t smid; asm volatile("mov.u32 %0, %%smid;" : "=r"(smid));
  if (threadIdx.x >= 256) {
    const uint32_t b = sb + S_BAR;
    if (threadIdx.x == 320) {
      mbar_init(b + B_W, 1); mbar_init(b + B_W2, 1); mbar_init(b + B_WV, 1); mbar_init(b + B_WO, 1); mbar_init(b + B_S, 9); mbar_init(b + B_KV, 1); mbar_init(b + B_KV + 8, 1);
      for (int i = 0; i < 4; i++) { mbar_init(b + B_FULL + i * 8, 1); mbar_init(b + B_EMPTY + i * 8, 2); }
      for (int i = 0; i < 5; i++) mbar_init(b + B_WF + i * 8, 1);
      mbar_init(b + B_WD, 2); sts32(b + B_PROG, 0);
      asm volatile("fence.mbarrier_init.release.cluster;" ::: "memory");
    }
    if (rank == 0 && threadIdx.x < 320) {
      if (args.layer == 0) {
        uint32_t* p = (uint32_t*)(args.comm + 0x20000 + (threadIdx.x < 288 ? 0x1000 : 0) + (blockIdx.x >> 1) * 32);
        if ((threadIdx.x & 31) < 8) p[threadIdx.x & 31] = 0;
        __syncwarp();
        if ((threadIdx.x & 31) == 0) {
          uint32_t v, best = ~0u;
#pragma unroll 1
          for (int i = 0; i < NPROBE; i++) { const uint32_t t0 = clk(); asm volatile("atom.relaxed.gpu.global.add.u32 %0, [%1], 1;" : "=r"(v) : "l"(p) : "memory"); asm volatile("st.volatile.shared.u32 [%0], %1;" ::"r"(b + 208), "r"(v) : "memory"); best = min(best, clk() - t0); }
          sts32(b + 200 + ((threadIdx.x >> 5) & 1) * 4, best);
        }
        bar_sync(1, 64);
      }
      if (threadIdx.x == 256) {
        int d;
        if (args.layer == 0) { d = (int)(lds32(b + 200) - lds32(b + 204)); g_side[smid & 254] = d; g_side[(smid & 254) + 1] = d; } else d = g_side[smid & 255];
        uint32_t* cnt = args.flags + F_ROLE; uint32_t role;
        if (d < 0) { role = atomicAdd(cnt, 1); if (role >= 32) role = 32 + atomicAdd(cnt + 1, 1); }
        else { role = 32 + atomicAdd(cnt + 1, 1); if (role >= 66) role = atomicAdd(cnt, 1); }
        sts32(b + B_ROLE, role);
      }
    }
  } else if (args.layer == 0 && blockIdx.x < 128) {
    const size_t off = (size_t)(blockIdx.x * 16 + (threadIdx.x >> 4)) * 640 + (threadIdx.x & 15) * 8;
    float f[40];
#pragma unroll
    for (int i = 0; i < 5; i++) unpack8(*(const uint4*)(args.x + off + i * 128), f + 8 * i);
    ln_row(f);
#pragma unroll
    for (int i = 0; i < 5; i++) *(uint4*)(g_xn + off + i * 128) = pack8(f + 8 * i);
  }
  __syncthreads();
  asm volatile("barrier.cluster.arrive.release.aligned;" ::: "memory");
  if (threadIdx.x == 0 && args.layer == 0 && blockIdx.x < 128) flag_add(args.flags + F_X);
  __syncwarp();
  asm volatile("barrier.cluster.wait.acquire.aligned;" ::: "memory");
  uint32_t role; asm volatile("ld.shared::cluster.u32 %0, [%1];" : "=r"(role) : "r"(sb + S_BAR + B_ROLE + (rank ? px : 0)) : "memory");
  role = __reduce_max_sync(~0u, role);
  if (PDLAT == 1 || (PDLAT == 2 && role != 32)) pdl_launch();
  if (role >= 64) cluster_sync();
  const int wg = __reduce_max_sync(~0u, threadIdx.x >> 7);
  auto U = [](uint32_t x) { return __reduce_max_sync(~0u, opaque(x)); };
  if (wg < 2) {
    asm volatile("setmaxnreg.inc.sync.aligned.u32 224;");
    if (role >= 32) {
      if (role >= 64) { if (args.layer == 0) { filter_prep((uint32_t*)smraw, (role - 64) * 2 + rank, args); if (threadIdx.x == 0) LOG(role * 2 + rank, 0); } }
      else gemm_consumer(U(sb), U(px), U(wg), U(role - 32), U(rank), args);
    } else { if (wg == 0) chain_mma<0>(sb, args); else chain_mma<1>(sb, args); }
  } else {
    asm volatile("setmaxnreg.dec.sync.aligned.u32 56;");
    if (role >= 32) {
      if (role < 64) {
        if (threadIdx.x == 256) gemm_producer(sb, role - 32, rank, args, &tq, &tk, &tv, &to32, &tx, &tao);
        else if (threadIdx.x >= 288 && threadIdx.x < 352) gemm_publisher((threadIdx.x >> 5) - 9, role - 32, rank, args);
        else if (threadIdx.x == 352 && role < 48) km_watcher(sb, args.flags + F_KM + (2 * (role - 32) + rank) * 32);
      }
    } else chain_helper(U(sb), U(px), U(role), U(rank), args, &tq, &tk, &tv, &to);
  }
}

DEVINL float2 cadd(float2 a, float2 b) { return make_float2(a.x + b.x, a.y + b.y); }
DEVINL float2 csub(float2 a, float2 b) { return make_float2(a.x - b.x, a.y - b.y); }
DEVINL float2 cmul(float2 a, float2 b) { return make_float2(fmaf(a.x, b.x, -a.y * b.y), fmaf(a.x, b.y, a.y * b.x)); }
DEVINL float2 cmulc(float2 a, float2 b) { return make_float2(fmaf(a.x, b.x, a.y * b.y), fmaf(a.y, b.x, -a.x * b.y)); }
template <int INV> DEVINL float2 ctw(float2 a, float2 w) { return INV ? cmulc(a, w) : cmul(a, w); }
template <int INV> DEVINL float2 rot(float2 a) { return INV ? make_float2(-a.y, a.x) : make_float2(a.y, -a.x); }
template <int INV> DEVINL void fft4(float2& a, float2& b, float2& c, float2& d) {
  const float2 s0 = cadd(a, c), d0 = csub(a, c), s1 = cadd(b, d), d1 = rot<INV>(csub(b, d));
  a = cadd(s0, s1); b = cadd(d0, d1); c = csub(s0, s1); d = csub(d0, d1);
}
template <int INV> DEVINL float2 w8(float2 a) { const float h = 0.70710678118654752f; const float2 r = rot<INV>(a); return make_float2((a.x + r.x) * h, (a.y + r.y) * h); }
template <int INV> DEVINL void fft8(float2* x) {
  fft4<INV>(x[0], x[2], x[4], x[6]); fft4<INV>(x[1], x[3], x[5], x[7]);
  const float2 e0 = x[0], e1 = x[2], e2 = x[4], e3 = x[6], o0 = x[1], o1 = w8<INV>(x[3]), o2 = rot<INV>(x[5]), o3 = rot<INV>(w8<INV>(x[7]));
  x[0] = cadd(e0, o0); x[1] = cadd(e1, o1); x[2] = cadd(e2, o2); x[3] = cadd(e3, o3);
  x[4] = csub(e0, o0); x[5] = csub(e1, o1); x[6] = csub(e2, o2); x[7] = csub(e3, o3);
}
template <int INV> DEVINL void fft16(float2* x) {
  const float c = 0.92387953251128674f, s = 0.38268343236508977f;
  const float2 w1 = make_float2(c, -s), w3 = make_float2(s, -c);
#pragma unroll
  for (int i = 0; i < 4; i++) fft4<INV>(x[i], x[i + 4], x[i + 8], x[i + 12]);
  x[5] = ctw<INV>(x[5], w1); x[9] = w8<INV>(x[9]); x[13] = ctw<INV>(x[13], w3);
  x[6] = w8<INV>(x[6]); x[10] = rot<INV>(x[10]); x[14] = rot<INV>(w8<INV>(x[14]));
  x[7] = ctw<INV>(x[7], w3); x[11] = rot<INV>(w8<INV>(x[11])); x[15] = ctw<INV>(x[15], make_float2(-c, s));
#pragma unroll
  for (int k = 0; k < 4; k++) fft4<INV>(x[4 * k], x[4 * k + 1], x[4 * k + 2], x[4 * k + 3]);
#pragma unroll
  for (int k = 0; k < 4; k++)
#pragma unroll
    for (int m = k + 1; m < 4; m++) { const float2 t = x[4 * k + m]; x[4 * k + m] = x[4 * m + k]; x[4 * m + k] = t; }
}
template <int INV> DEVINL void fft5(float2& x0, float2& x1, float2& x2, float2& x3, float2& x4) {
  const float c1 = 0.30901699437494742f, c2 = -0.80901699437494742f, s1 = 0.95105651629515357f, s2 = 0.58778525229247313f;
  const float2 a1 = cadd(x1, x4), a2 = cadd(x2, x3), b1 = rot<INV>(csub(x1, x4)), b2 = rot<INV>(csub(x2, x3));
  const float2 p1 = make_float2(fmaf(c1, a1.x, fmaf(c2, a2.x, x0.x)), fmaf(c1, a1.y, fmaf(c2, a2.y, x0.y)));
  const float2 p2 = make_float2(fmaf(c2, a1.x, fmaf(c1, a2.x, x0.x)), fmaf(c2, a1.y, fmaf(c1, a2.y, x0.y)));
  const float2 q1 = make_float2(fmaf(s1, b1.x, s2 * b2.x), fmaf(s1, b1.y, s2 * b2.y));
  const float2 q2 = make_float2(fmaf(s2, b1.x, -s1 * b2.x), fmaf(s2, b1.y, -s1 * b2.y));
  x0 = cadd(x0, cadd(a1, a2)); x1 = cadd(p1, q1); x4 = csub(p1, q1); x2 = cadd(p2, q2); x3 = csub(p2, q2);
}
template <int INV> DEVINL void fft20(const float2* in, float2* out) {
  float2 t[4][5];
#pragma unroll
  for (int a = 0; a < 4; a++) {
#pragma unroll
    for (int b = 0; b < 5; b++) t[a][b] = in[(5 * a + 4 * b) % 20];
    fft5<INV>(t[a][0], t[a][1], t[a][2], t[a][3], t[a][4]);
  }
#pragma unroll
  for (int d = 0; d < 5; d++) {
    fft4<INV>(t[0][d], t[1][d], t[2][d], t[3][d]);
#pragma unroll
    for (int c = 0; c < 4; c++) out[(5 * c + 16 * d) % 20] = t[c][d];
  }
}
constexpr int ZP = 336;
struct RowSmem { float2 T[320 * 17]; uint32_t Z[16 * ZP]; float2 tw[320]; float2 tp[160]; };
DEVINL float2 cis(int k, int n) {
  float sn, cs; __sincosf((float)(2 * k > n ? k - n : k) * (-6.283185307179586f / (float)n), &sn, &cs); return make_float2(cs, sn);
}
DEVINL void row_tables(RowSmem& sm) {
  const int t = threadIdx.x;
  sm.tw[t] = cis((t >> 4) * (t & 15), 320);
  if (t < 160) sm.tp[t] = cis(t, 640);
}

#define CUNR 1
#define CDRY 0
#define RDRY 1

__global__ void __launch_bounds__(320, 1) rows_fwd_kernel(const bf16* __restrict__ xin, const uint32_t* flags) {
  extern __shared__ __align__(1024) char smraw[]; RowSmem& sm = *(RowSmem*)smraw;
  const int tid = threadIdx.x, s0 = blockIdx.x * 16, wp = __reduce_max_sync(~0u, tid >> 5);
  const uint32_t* flag = flags + F_P + (blockIdx.x >> 2) * 32;
  LOGK(1 + 3 * (xin == g_x), 0);
  if (tid == 0) l2_prefetch(xin + s0 * 640, 20480);
  row_tables(sm);
#pragma unroll 1
  for (int live = !RDRY || wp != 1 || __any_sync(~0u, ldg_rlx32(flag) >= 32); live < 2; live++) {
    if (live) {
      if (wp == 0) { uint32_t v; int n = 0;
        while (true) { asm volatile("ld.acquire.gpu.global.u32 %0, [%1];" : "=r"(v) : "l"(flag) : "memory"); if (__all_sync(~0u, v >= 32 || ++n >= 8 * POLL_LIMIT)) break; __nanosleep(v ? 20 : 200); } }
      __syncthreads();
      pdl_launch();
      LOGK(1 + 3 * (xin == g_x), 1);
    }
    if (wp < 8) {
      const int row = tid >> 4, j = tid & 15; const size_t off = (size_t)(s0 + row) * 640 + j * 8;
      float f[40]; uint4 in[5][5];
#pragma unroll
      for (int i = 0; i < 5; i++) {
#pragma unroll
        for (int q = 0; q < 4; q++) in[i][q] = ldg128_if(g_part + q * 2048 * 640 + off + i * 128, live);
        in[i][4] = ldg128_if(xin + off + i * 128, live);
      }
#pragma unroll
      for (int i = 0; i < 5; i++) {
        float a[8], b[8], c[8], d[8];
        unpack8(in[i][0], a); unpack8(in[i][1], b); unpack8(in[i][2], c); unpack8(in[i][3], d);
#pragma unroll
        for (int e = 0; e < 8; e++) a[e] = (a[e] + b[e]) + (c[e] + d[e]);
        const uint4 o = pack8(a), x = in[i][4];
        const uint4 r = make_uint4(hadd2bf(o.x, x.x), hadd2bf(o.y, x.y), hadd2bf(o.z, x.z), hadd2bf(o.w, x.w));
        stg128_if(g_x + off + i * 128, r, live); unpack8(r, f + 8 * i);
      }
      ln_row(f);
#pragma unroll
      for (int i = 0; i < 5; i++) *(uint4*)(sm.Z + row * ZP + i * 64 + j * 4) = pack8(f + 8 * i);
      __syncwarp();
      float2 z[20], y[20];
#pragma unroll
      for (int n1 = 0; n1 < 20; n1++) { const uint32_t w = sm.Z[row * ZP + n1 * 16 + j]; z[n1] = make_float2(bf_lo(w), bf_hi(w)); }
      fft20<0>(z, y);
#pragma unroll
      for (int k1 = 0; k1 < 20; k1++) sm.T[(k1 * 16 + j) * 17 + row] = k1 ? cmul(y[k1], sm.tw[k1 * 16 + j]) : y[0];
    }
    if (live) __syncthreads();
    const int up = (tid >> 4) & 1, row = tid & 15, k1 = wp ? (up ? 20 - wp : wp) : up * 10;
    float2 x[16];
#pragma unroll
    for (int n2 = 0; n2 < 16; n2++) x[n2] = sm.T[(k1 * 16 + n2) * 17 + row];
    fft16<0>(x);
    uint32_t* ya = g_y + s0 + row + k1 * 2048; uint32_t* yb = g_y + s0 + row + (320 - k1) * 2048;
    stg32_if(g_y + s0 + row + 160 * 2048, pack_f16(2.f * x[8].x, -2.f * x[8].y), live && k1 == 0);
    const int src = (tid & 31) ^ (wp ? 16 : 0);
#pragma unroll
    for (int k2 = 0; k2 < 8; k2++) {
      const float2 c = k1 ? x[15 - k2] : x[(16 - k2) & 15], b = make_float2(__shfl_sync(~0u, c.x, src), __shfl_sync(~0u, c.y, src)), a = x[k2];
      const float2 E = make_float2(a.x + b.x, a.y - b.y), O = cmul(make_float2(a.y + b.y, b.x - a.x), sm.tp[k1 + 20 * k2]);
      stg32_if(ya + k2 * 20 * 2048, pack_f16(E.x + O.x, E.y + O.y), live); stg32_if(yb - k2 * 20 * 2048, pack_f16(E.x - O.x, O.y - E.y), live);
    }
  }
  LOGK(1 + 3 * (xin == g_x), 2);
  if (blockIdx.x == gridDim.x - 1) pdl_wait();
}

__global__ void __launch_bounds__(384) cols_kernel(int layer) {
  extern __shared__ __align__(1024) char smraw[];
  const int sub = threadIdx.x >> 7, tid = threadIdx.x & 127, col = blockIdx.x * 3 + sub, k1 = tid >> 3, j0 = tid & 7;
  float2* sm = (float2*)smraw + sub * (16 * 152);
  float2* tw = (float2*)smraw + 3 * 16 * 152;
  LOGK(2 + 3 * layer, 0);
  pdl_launch();
  uint32_t* y = g_y + col * 2048 + tid;
  if (tid < 2) l2_prefetch((tid ? g_wt : g_y) + col * 2048, 8192);
#pragma unroll 1
  for (int i = threadIdx.x; i < 2176; i += 384) {
    const int a = i < 2048 ? i >> 7 : (i - 2048) >> 3, b = i < 2048 ? i & 127 : i & 7;
    tw[i < 2048 ? a * 136 + b : 2176 + a * 9 + b] = cis(i < 2048 ? a * b : a * b * 16, 2048);
  }
  float2* reg = sm + k1 * 152;
  uint4 wf[4];
#pragma unroll
  for (int q = 0; q < 4; q++) {
    const int live = q >= 0, it = live ? q : q == -3 ? 0 : q == -2 ? 1 : 3;
    float2 x[16];
    if (it == 0) {
      if (live) { __syncthreads(); pdl_wait(); LOGK(2 + 3 * layer, 1); }
#pragma unroll
      for (int i = 0; i < 16; i++) { const uint32_t w = ldg32_if(y + i * 128, live); x[i] = __half22float2(*(const __half2*)&w); }
#pragma unroll
      for (int i = 0; i < 4; i++) wf[i] = ldg128_if(g_wt + col * 2048 + i * 512 + tid * 4, live);
    } else {
      const float2* in = it == 3 ? sm + tid : reg + j0; const int is = it == 1 ? 8 : it == 2 ? 9 : 152;
#pragma unroll
      for (int i = 0; i < 16; i++) x[i] = in[i * is];
    }
    fft16<0>(x);
    if (it == 3) {
      const float sc = 1.f / 4096.f;
#pragma unroll
      for (int i = 0; i < 16; i++) stg32_if(y + i * 128, pack_bf16(x[i].y * sc, x[i].x * sc), live);
    } else {
      const float2* t = it == 0 ? tw + tid : it == 1 ? tw + 2176 + j0 : tw + k1 * 136 + j0; const int ts = it == 0 ? 136 : it == 1 ? 9 : 8;
      float2* o = it == 0 ? sm + tid : reg + j0; const int os = it == 0 ? 152 : it == 1 ? 9 : 8;
      __syncwarp();
#pragma unroll
      for (int k = 0; k < 16; k++) o[k * os] = (CUNR && k == 0 && it < 2) ? x[0] : cmul(x[k], t[k * ts]);
      if (it == 1) {
        __syncwarp();
        float2* r9 = reg + j0 * 9;
#pragma unroll
        for (int i = 0; i < 16; i++) x[i] = r9[(i & 8) * 9 + (i & 7)];
#pragma unroll
        for (int h = 0; h < 2; h++) {
          fft8<0>(x); fft8<0>(x + 8);
          if (h == 0) {
#pragma unroll
            for (int i = 0; i < 16; i++) {
              const uint32_t w = (i & 3) == 0 ? wf[i >> 2].x : (i & 3) == 1 ? wf[i >> 2].y : (i & 3) == 2 ? wf[i >> 2].z : wf[i >> 2].w;
              const float2 v = cmul(x[i], make_float2(bf_lo(w), bf_hi(w))); x[i] = make_float2(v.y, v.x);
            }
          }
        }
        const float2* t9 = tw + 2176 + j0 * 9;
#pragma unroll
        for (int i = 0; i < 16; i++) r9[(i & 8) * 9 + (i & 7)] = (i & 7) ? cmul(x[i], t9[(i & 8) * 9 + (i & 7)]) : x[i];
        __syncwarp();
      } else if (live) bar_sync(sub + 1, 128);
    }
  }
  LOGK(2 + 3 * layer, 2);
}

__global__ void __launch_bounds__(320) rows_inv_kernel(bf16* __restrict__ xout, int do_ln) {
  extern __shared__ __align__(1024) char smraw[]; RowSmem& sm = *(RowSmem*)smraw;
  const int tid = threadIdx.x, s0 = blockIdx.x * 16, wp = __reduce_max_sync(~0u, tid >> 5);
  LOGK(3 + 3 * !do_ln, 0);
  if (tid == 0) l2_prefetch(g_x + s0 * 640, 20480);
  row_tables(sm);
  const size_t off = (size_t)(s0 + ((tid >> 4) & 15)) * 640 + (tid & 15) * 8;
#pragma unroll 1
  for (int live = !RDRY || wp != 1; live < 2; live++) {
    if (live) {
      __syncthreads();
      pdl_wait();
      pdl_launch();
      LOGK(3 + 3 * !do_ln, 1);
    }
    uint4 xr[5];
    {
      const int up = (tid >> 4) & 1, row = tid & 15, k1 = wp ? (up ? 20 - wp : wp) : up * 10;
      const uint32_t* ya = g_y + s0 + row + k1 * 2048; const uint32_t* yb = g_y + s0 + row + (320 - k1) * 2048;
      uint32_t wa[8], wb[8];
#pragma unroll
      for (int k2 = 0; k2 < 8; k2++) { wa[k2] = ldg32_if(ya + k2 * 20 * 2048, live); wb[k2] = ldg32_if(yb - k2 * 20 * 2048, live); }
      const uint32_t wm = ldg32_if(g_y + s0 + row + 160 * 2048, live && k1 == 0);
#pragma unroll
      for (int i = 0; i < 5; i++) xr[i] = ldg128_if(g_x + off + i * 128, live && wp < 8);
      stg32_if(g_flags + blockIdx.x * 320 + tid, 0, live && !do_ln && blockIdx.x * 320 + tid < 2 * F_LAYER);
      if (k1 == 0) { wa[0] &= 0xffffu; wb[0] &= 0xffffu; }
      float2 x[16], r[8];
#pragma unroll
      for (int k2 = 0; k2 < 8; k2++) {
        const float2 a = make_float2(bf_lo(wa[k2]), bf_hi(wa[k2])), b = make_float2(bf_lo(wb[k2]), bf_hi(wb[k2]));
        const float2 E = make_float2(a.x + b.x, a.y - b.y), O = cmulc(make_float2(a.x - b.x, a.y + b.y), sm.tp[k1 + 20 * k2]);
        x[k2] = make_float2(E.x - O.y, E.y + O.x); r[k2] = make_float2(E.x + O.y, O.x - E.y);
      }
      if (k1 == 0) r[0] = make_float2(2.f * bf_lo(wm), -2.f * bf_hi(wm));
      const int src = (tid & 31) ^ (wp ? 16 : 0);
#pragma unroll
      for (int i = 8; i < 16; i++) { const float2 c = k1 ? r[15 - i] : r[(16 - i) & 7]; x[i] = make_float2(__shfl_sync(~0u, c.x, src), __shfl_sync(~0u, c.y, src)); }
      fft16<1>(x);
#pragma unroll
      for (int n2 = 0; n2 < 16; n2++) sm.T[(k1 * 16 + n2) * 17 + row] = x[n2];
    }
    if (live) __syncthreads();
    if (wp < 8) {
      const int row = tid >> 4, n2 = tid & 15;
      float2 z[20], y[20];
#pragma unroll
      for (int k1 = 0; k1 < 20; k1++) { const float2 t = sm.T[(k1 * 16 + n2) * 17 + row]; z[k1] = k1 ? cmulc(t, sm.tw[k1 * 16 + n2]) : t; }
      fft20<1>(z, y);
      const float sc = 1.f / 640.f;
#pragma unroll
      for (int n1 = 0; n1 < 20; n1++) sm.Z[row * ZP + n1 * 16 + n2] = pack_bf16(y[n1].x * sc, y[n1].y * sc);
      __syncwarp();
      float f[40];
#pragma unroll
      for (int i = 0; i < 5; i++) {
        const uint4 o = *(const uint4*)(sm.Z + row * ZP + i * 64 + n2 * 4), x = xr[i];
        const uint4 r = make_uint4(hadd2bf(o.x, x.x), hadd2bf(o.y, x.y), hadd2bf(o.z, x.z), hadd2bf(o.w, x.w));
        stg128_if(xout + off + i * 128, r, live); unpack8(r, f + 8 * i);
      }
      if (do_ln) {
        ln_row(f);
#pragma unroll
        for (int i = 0; i < 5; i++) stg128_if(g_xn + off + i * 128, pack8(f + 8 * i), live);
      }
    }
  }
  LOGK(3 + 3 * !do_ln, 2);
}

typedef CUresult (*EncFn)(CUtensorMap*, CUtensorMapDataType, cuuint32_t, void*, const cuuint64_t*, const cuuint64_t*, const cuuint32_t*, const cuuint32_t*,
                          CUtensorMapInterleave, CUtensorMapSwizzle, CUtensorMapL2promotion, CUtensorMapFloatOOBfill);
static void make_map(EncFn fn, CUtensorMap* m, const void* p, uint64_t cols, uint64_t rows, uint32_t bc, uint32_t br, CUtensorMapSwizzle sw) {
  cuuint64_t gd[2] = {cols, rows}, gs[1] = {cols * 2}; cuuint32_t bd[2] = {bc, br}, es[2] = {1, 1};
  fn(m, CU_TENSOR_MAP_DATA_TYPE_BFLOAT16, 2, (void*)p, gd, gs, bd, es, CU_TENSOR_MAP_INTERLEAVE_NONE, sw, CU_TENSOR_MAP_L2_PROMOTION_L2_128B, CU_TENSOR_MAP_FLOAT_OOB_FILL_NONE);
}
template <class... P, class... A>
static void launch(void (*k)(P...), int grid, int block, int smem, bool pdl, A... a) {
  cudaLaunchConfig_t cfg = {}; cfg.gridDim = dim3(grid); cfg.blockDim = dim3(block); cfg.dynamicSmemBytes = smem; cfg.stream = cudaStreamPerThread;
  cudaLaunchAttribute at[1]; at[0].id = cudaLaunchAttributeProgrammaticStreamSerialization; at[0].val.programmaticStreamSerializationAllowed = 1;
  cfg.attrs = at; cfg.numAttrs = pdl ? 1 : 0;
  cudaLaunchKernelEx(&cfg, k, a...);
}
static const int tune_t[10] = {1505, 1635, 1830, 2060, 2200, 2385, 2610, 2790, 1950, 3045}; constexpr int dev_stop = 100, dev_pdl = 1;

extern "C" void kernel_launch(void* const* d_in, const int* in_sizes, int n_in, void* d_out, int out_size) {
  const bf16 *x = (const bf16*)d_in[0], *mem0 = (const bf16*)d_in[1], *Wq = (const bf16*)d_in[2], *Wk = (const bf16*)d_in[3], *Wv = (const bf16*)d_in[4], *Wo = (const bf16*)d_in[5];
  const bf16 *wr = (const bf16*)d_in[8], *wi = (const bf16*)d_in[9];
  constexpr int SM_A = S_END + 1024, SM_R = sizeof(RowSmem), SM_C = 76 * 1024, SM_I = 116 * 1024;
  void *p_xn, *p_o, *p_x, *p_comm, *p_flags, *fn; cudaDriverEntryPointQueryResult qr;
  cudaGetSymbolAddress(&p_xn, g_xn); cudaGetSymbolAddress(&p_o, g_o); cudaGetSymbolAddress(&p_x, g_x); cudaGetSymbolAddress(&p_comm, g_comm); cudaGetSymbolAddress(&p_flags, g_flags);
  cudaGetDriverEntryPoint("cuTensorMapEncodeTiled", &fn, cudaEnableDefault, &qr);
  cudaFuncSetAttribute(layer_a_kernel, cudaFuncAttributeMaxDynamicSharedMemorySize, SM_A);
  cudaFuncSetAttribute(rows_fwd_kernel, cudaFuncAttributeMaxDynamicSharedMemorySize, SM_R);
  cudaFuncSetAttribute(rows_inv_kernel, cudaFuncAttributeMaxDynamicSharedMemorySize, SM_I);
  cudaFuncSetAttribute(cols_kernel, cudaFuncAttributeMaxDynamicSharedMemorySize, SM_C);
  cudaFuncSetAttribute(rows_fwd_kernel, cudaFuncAttributePreferredSharedMemoryCarveout, 100);
  cudaFuncSetAttribute(cols_kernel, cudaFuncAttributePreferredSharedMemoryCarveout, 100);
  cudaFuncSetAttribute(rows_inv_kernel, cudaFuncAttributePreferredSharedMemoryCarveout, 100);
  CUtensorMap tq, tk, tv, to, to32, tx, tao; EncFn enc = (EncFn)fn;
  make_map(enc, &tq, Wq, 4096, 640, 64, 64, CU_TENSOR_MAP_SWIZZLE_128B); make_map(enc, &tk, Wk, 4096, 640, 64, 64, CU_TENSOR_MAP_SWIZZLE_128B);
  make_map(enc, &tv, Wv, 4096, 640, 64, 64, CU_TENSOR_MAP_SWIZZLE_128B); make_map(enc, &to, Wo, 640, 4096, 64, 64, CU_TENSOR_MAP_SWIZZLE_128B);
  make_map(enc, &to32, Wo, 640, 4096, 16, 256, CU_TENSOR_MAP_SWIZZLE_32B);
  make_map(enc, &tx, p_xn, 640, 2048, 64, 64, CU_TENSOR_MAP_SWIZZLE_128B); make_map(enc, &tao, p_o, 4096, 2048, 64, 64, CU_TENSOR_MAP_SWIZZLE_128B);
  char* comm = (char*)(((uintptr_t)p_comm + (2 << 20) - 1) & ~(uintptr_t)((2 << 20) - 1));
  const bool pdl = dev_pdl;
#define L0PDL 0
  for (int l = 0; l < 2; l++) {
    ArgsA a{x, mem0, comm, (uint32_t*)p_flags + l * F_LAYER, wr, wi, (const char*)Wq, (const char*)Wo, l, {tune_t[0], tune_t[1], tune_t[2], tune_t[3]}, {tune_t[4], tune_t[5], tune_t[6], tune_t[7]}, {tune_t[8], tune_t[9]}};
    if (dev_stop > 4 * l + 0) launch(layer_a_kernel, 132, 384, SM_A, pdl && (l || L0PDL), tq, tk, tv, to, to32, tx, tao, a);
    if (dev_stop > 4 * l + 1) launch(rows_fwd_kernel, 128, 320, SM_R, pdl, l ? (const bf16*)p_x : x, (const uint32_t*)a.flags);
    if (dev_stop > 4 * l + 2) launch(cols_kernel, 107, 384, SM_C, pdl, l);
    if (dev_stop > 4 * l + 3) launch(rows_inv_kernel, 128, 320, SM_I, pdl, l ? (bf16*)d_out : (bf16*)p_x, l == 0);
  }
}
```

```cpp
#include <cuda_runtime.h>
#include <cuda_bf16.h>
#include <cuda_fp16.h>
#include <cuda.h>
#include <stdint.h>

typedef __nv_bfloat16 bf16;
#define DEVINL __device__ __forceinline__

__device__ __align__(1024) bf16 g_xn[2048 * 640];
__device__ __align__(1024) bf16 g_x[2048 * 640];
__device__ __align__(1024) char g_kv[64 * 32 * 16384];
__device__ __align__(1024) char g_kvm[64 * 32 * 4096];
__device__ __align__(1024) bf16 g_o[2048 * 4096];
__device__ __align__(1024) bf16 g_part[4 * 2048 * 640];
__device__ __align__(1024) uint32_t g_y[321 * 2048];
__device__ __align__(1024) uint32_t g_wt[321 * 2048];
__device__ __align__(4096) char g_comm[4 << 20];
constexpr int F_KV = 0, F_KM = 1024, F_O = F_KM + 1024, F_P = F_O + 128, F_ROLE = F_P + 32 * 32, F_X = F_ROLE + 64, F_LAYER = F_X + 32;
__device__ __align__(1024) uint32_t g_flags[2 * F_LAYER];
__device__ int g_side[256];

template <int V> struct IC { static constexpr int value = V; };
template <int B, int E, class F> DEVINL void static_for(F&& f) { if constexpr (B < E) { f(IC<B>{}); static_for<B + 1, E>(f); } }

#define POLL_LIMIT (1 << 17)
DEVINL uint32_t smem_u32(const void* p) { return (uint32_t)__cvta_generic_to_shared(p); }
DEVINL uint32_t mapa(uint32_t a, uint32_t r) { uint32_t o; asm volatile("mapa.shared::cluster.u32 %0, %1, %2;" : "=r"(o) : "r"(a), "r"(r)); return o; }
DEVINL uint32_t clk() { uint32_t v; asm volatile("{.reg .b64 w; mov.u64 w, %%clock64; cvt.u32.u64 %0, w;}" : "=r"(v)::"memory"); return v; }
DEVINL void mbar_init(uint32_t bar, uint32_t cnt) { asm volatile("mbarrier.init.shared::cta.b64 [%0], %1;" ::"r"(bar), "r"(cnt) : "memory"); }
DEVINL void mbar_arrive(uint32_t bar) { asm volatile("mbarrier.arrive.shared::cta.b64 _, [%0];" ::"r"(bar) : "memory"); }
DEVINL void mbar_arrive_remote(uint32_t bar) { asm volatile("mbarrier.arrive.shared::cluster.b64 _, [%0];" ::"r"(bar) : "memory"); }
DEVINL void mbar_arrive_tx(uint32_t bar, uint32_t tx) { asm volatile("mbarrier.arrive.expect_tx.shared::cta.b64 _, [%0], %1;" ::"r"(bar), "r"(tx) : "memory"); }
DEVINL void mbar_wait(uint32_t bar, uint32_t ph) {
  asm volatile("{.reg .pred p; .reg .b32 c,q; shl.b32 c, %1, 20;\n"
               "W0: bfe.u32 q, c, 20, 1; mbarrier.try_wait.parity.shared::cta.b64 p, [%0], q; add.u32 c,c,1; @!p bra.uni W0;}" ::"r"(bar), "r"(ph) : "memory");
}
DEVINL void bar_sync(int id, int n) { asm volatile("bar.sync %0, %1;" ::"r"(id), "r"(n) : "memory"); }
DEVINL void bar_arrive(int id, int n) { asm volatile("bar.arrive %0, %1;" ::"r"(id), "r"(n) : "memory"); }
DEVINL void cluster_sync() { asm volatile("barrier.cluster.arrive.release.aligned; barrier.cluster.wait.acquire.aligned;" ::: "memory"); }
DEVINL void tma_2d(uint32_t dst, const CUtensorMap* tm, int c0, int c1, uint32_t bar) {
  asm volatile("cp.async.bulk.tensor.2d.shared::cluster.global.mbarrier::complete_tx::bytes [%0], [%1, {%2, %3}], [%4];" ::"r"(dst), "l"(tm), "r"(c0), "r"(c1), "r"(bar) : "memory");
}
DEVINL void tma_2d_mc(uint32_t dst, const CUtensorMap* tm, int c0, int c1, uint32_t bar) {
  asm volatile("cp.async.bulk.tensor.2d.shared::cluster.global.mbarrier::complete_tx::bytes.multicast::cluster [%0], [%1, {%2, %3}], [%4], %5;" ::"r"(dst), "l"(tm), "r"(c0), "r"(c1), "r"(bar), "h"((uint16_t)3) : "memory");
}
DEVINL void bulk_g2s(uint32_t dst, const void* src, uint32_t bytes, uint32_t bar) {
  asm volatile("cp.async.bulk.shared::cluster.global.mbarrier::complete_tx::bytes [%0], [%1], %2, [%3];" ::"r"(dst), "l"(src), "r"(bytes), "r"(bar) : "memory");
}
DEVINL void l2_prefetch(const void* p, uint32_t bytes) { asm volatile("cp.async.bulk.prefetch.L2.global [%0], %1;" ::"l"(p), "r"(bytes) : "memory"); }
DEVINL void fence_proxy_async() { asm volatile("fence.proxy.async.global;" ::: "memory"); }
DEVINL void ldsm4t(uint32_t* r, uint32_t a) { asm volatile("ldmatrix.sync.aligned.m8n8.x4.trans.shared.b16 {%0,%1,%2,%3}, [%4];" : "=r"(r[0]), "=r"(r[1]), "=r"(r[2]), "=r"(r[3]) : "r"(a) : "memory"); }
DEVINL void stsm4(uint32_t a, uint32_t r0, uint32_t r1, uint32_t r2, uint32_t r3) { asm volatile("stmatrix.sync.aligned.m8n8.x4.shared.b16 [%0], {%1,%2,%3,%4};" ::"r"(a), "r"(r0), "r"(r1), "r"(r2), "r"(r3) : "memory"); }
DEVINL void mma16816(float* d, const uint32_t* a, uint32_t b0, uint32_t b1) {
  asm volatile("mma.sync.aligned.m16n8k16.row.col.f32.bf16.bf16.f32 {%0,%1,%2,%3}, {%4,%5,%6,%7}, {%8,%9}, {%0,%1,%2,%3};"
               : "+f"(d[0]), "+f"(d[1]), "+f"(d[2]), "+f"(d[3]) : "r"(a[0]), "r"(a[1]), "r"(a[2]), "r"(a[3]), "r"(b0), "r"(b1));
}
DEVINL void mma16816z(float* d, const uint32_t* a, uint32_t b0, uint32_t b1) {
  asm volatile("mma.sync.aligned.m16n8k16.row.col.f32.bf16.bf16.f32 {%0,%1,%2,%3}, {%4,%5,%6,%7}, {%8,%9}, {%10,%10,%10,%10};"
               : "=f"(d[0]), "=f"(d[1]), "=f"(d[2]), "=f"(d[3]) : "r"(a[0]), "r"(a[1]), "r"(a[2]), "r"(a[3]), "r"(b0), "r"(b1), "f"(0.f));
}
DEVINL void mma1688z(float* d, uint32_t a0, uint32_t a1, uint32_t b0) {
  asm volatile("mma.sync.aligned.m16n8k8.row.col.f32.bf16.bf16.f32 {%0,%1,%2,%3}, {%4,%5}, {%6}, {%7,%7,%7,%7};"
               : "=f"(d[0]), "=f"(d[1]), "=f"(d[2]), "=f"(d[3]) : "r"(a0), "r"(a1), "r"(b0), "f"(0.f));
}
DEVINL uint32_t movm(uint32_t a) { uint32_t r; asm volatile("movmatrix.sync.aligned.m8n8.trans.b16 %0, %1;" : "=r"(r) : "r"(a)); return r; }
DEVINL uint32_t pack_bf16(float lo, float hi) { uint32_t r; asm("cvt.rn.bf16x2.f32 %0, %1, %2;" : "=r"(r) : "f"(hi), "f"(lo)); return r; }
DEVINL uint32_t pack_f16(float lo, float hi) { uint32_t r; asm("cvt.rn.f16x2.f32 %0, %1, %2;" : "=r"(r) : "f"(hi), "f"(lo)); return r; }
DEVINL float bf_lo(uint32_t w) { return __uint_as_float(w << 16); }
DEVINL float bf_hi(uint32_t w) { return __uint_as_float(w & 0xffff0000u); }
DEVINL uint32_t hadd2bf(uint32_t a, uint32_t b) { uint32_t r; asm("add.rn.bf16x2 %0, %1, %2;" : "=r"(r) : "r"(a), "r"(b)); return r; }
DEVINL uint32_t hmax2bf(uint32_t a, uint32_t b) { uint32_t r; asm("max.bf16x2 %0, %1, %2;" : "=r"(r) : "r"(a), "r"(b)); return r; }
DEVINL uint32_t lds32(uint32_t a) { uint32_t v; asm volatile("ld.shared.u32 %0, [%1];" : "=r"(v) : "r"(a) : "memory"); return v; }
DEVINL uint2 lds64(uint32_t a) { uint2 v; asm volatile("ld.shared.v2.u32 {%0,%1}, [%2];" : "=r"(v.x), "=r"(v.y) : "r"(a) : "memory"); return v; }
DEVINL uint4 lds128(uint32_t a) { uint4 v; asm volatile("ld.shared.v4.u32 {%0,%1,%2,%3}, [%4];" : "=r"(v.x), "=r"(v.y), "=r"(v.z), "=r"(v.w) : "r"(a) : "memory"); return v; }
DEVINL void sts32(uint32_t a, uint32_t v) { asm volatile("st.shared.u32 [%0], %1;" ::"r"(a), "r"(v) : "memory"); }
DEVINL void sts64(uint32_t a, uint32_t x, uint32_t y) { asm volatile("st.shared.v2.u32 [%0], {%1,%2};" ::"r"(a), "r"(x), "r"(y) : "memory"); }
DEVINL void sts128(uint32_t a, uint4 v) { asm volatile("st.shared.v4.u32 [%0], {%1,%2,%3,%4};" ::"r"(a), "r"(v.x), "r"(v.y), "r"(v.z), "r"(v.w) : "memory"); }
DEVINL void stasync64(uint32_t a, uint32_t x, uint32_t y, uint32_t bar) { asm volatile("st.async.weak.shared::cluster.mbarrier::complete_tx::bytes.v2.b32 [%0], {%1,%2}, [%3];" ::"r"(a), "r"(x), "r"(y), "r"(bar) : "memory"); }
DEVINL uint4 ldg_rlx128(const void* p) { uint4 v; asm volatile("{.reg .b64 a,b; ld.relaxed.gpu.global.v2.b64 {a,b}, [%4]; mov.b64 {%0,%1}, a; mov.b64 {%2,%3}, b;}" : "=r"(v.x), "=r"(v.y), "=r"(v.z), "=r"(v.w) : "l"(p) : "memory"); return v; }
DEVINL uint2 ldg_rlx64(const void* p) { uint2 v; asm volatile("ld.relaxed.gpu.global.v2.u32 {%0,%1}, [%2];" : "=r"(v.x), "=r"(v.y) : "l"(p) : "memory"); return v; }
DEVINL void stg_rlx64(void* p, uint32_t x, uint32_t y) { asm volatile("{.reg .b64 a; mov.b64 a, {%1,%2}; st.relaxed.gpu.global.b64 [%0], a;}" ::"l"(p), "r"(x), "r"(y) : "memory"); }
DEVINL void stg_rlx128(void* p, uint32_t x, uint32_t y, uint32_t z, uint32_t w) { asm volatile("{.reg .b64 a,b; mov.b64 a, {%1,%2}; mov.b64 b, {%3,%4}; st.relaxed.gpu.global.v2.b64 [%0], {a,b};}" ::"l"(p), "r"(x), "r"(y), "r"(z), "r"(w) : "memory"); }
DEVINL void stg_rlx32(void* p, uint32_t x) { asm volatile("st.relaxed.gpu.global.u32 [%0], %1;" ::"l"(p), "r"(x) : "memory"); }
DEVINL uint4 ldg_cg128(const void* p) { uint4 v; asm volatile("ld.global.cg.v4.u32 {%0,%1,%2,%3}, [%4];" : "=r"(v.x), "=r"(v.y), "=r"(v.z), "=r"(v.w) : "l"(p) : "memory"); return v; }
DEVINL uint32_t ldg_cg32(const void* p) { uint32_t v; asm volatile("ld.global.cg.u32 %0, [%1];" : "=r"(v) : "l"(p) : "memory"); return v; }
DEVINL uint32_t ldg32_if(const void* p, int on) { uint32_t v; asm volatile("{.reg .pred q; setp.ne.s32 q, %2, 0; mov.u32 %0, 0; @q ld.global.cg.u32 %0, [%1];}" : "=r"(v) : "l"(p), "r"(on) : "memory"); return v; }
DEVINL uint4 ldg128_if(const void* p, int on) { uint4 v; asm volatile("{.reg .pred q; setp.ne.s32 q, %5, 0; mov.u32 %0, 0; mov.u32 %1, 0; mov.u32 %2, 0; mov.u32 %3, 0; @q ld.global.cg.v4.u32 {%0,%1,%2,%3}, [%4];}" : "=r"(v.x), "=r"(v.y), "=r"(v.z), "=r"(v.w) : "l"(p), "r"(on) : "memory"); return v; }
DEVINL void stg32_if(void* p, uint32_t v, int on) { asm volatile("{.reg .pred q; setp.ne.s32 q, %2, 0; @q st.global.u32 [%0], %1;}" ::"l"(p), "r"(v), "r"(on) : "memory"); }
DEVINL void stg128_if(void* p, uint4 v, int on) { asm volatile("{.reg .pred q; setp.ne.s32 q, %5, 0; @q st.global.v4.u32 [%0], {%1,%2,%3,%4};}" ::"l"(p), "r"(v.x), "r"(v.y), "r"(v.z), "r"(v.w), "r"(on) : "memory"); }
DEVINL uint4 ldg_ca128(const void* p) { uint4 v; asm volatile("ld.global.ca.v4.u32 {%0,%1,%2,%3}, [%4];" : "=r"(v.x), "=r"(v.y), "=r"(v.z), "=r"(v.w) : "l"(p) : "memory"); return v; }
DEVINL uint32_t ldg_ca32(const void* p) { uint32_t v; asm volatile("ld.global.ca.u32 %0, [%1];" : "=r"(v) : "l"(p) : "memory"); return v; }
DEVINL void flag_wait(const uint32_t* p, uint32_t want) {
  uint32_t v;
#pragma unroll 1
  for (int n = 0; n < POLL_LIMIT; n++) { asm volatile("ld.acquire.gpu.global.u32 %0, [%1];" : "=r"(v) : "l"(p) : "memory"); if (v >= want) break; __nanosleep(40); }
}
DEVINL void flag_wait_warp(const uint32_t* p, uint32_t want) {
  uint32_t v; int n = 0;
  do { asm volatile("ld.acquire.gpu.global.u32 %0, [%1];" : "=r"(v) : "l"(p) : "memory"); } while (__any_sync(~0u, v < want && ++n < POLL_LIMIT));
}
DEVINL void flag_add(uint32_t* p) { asm volatile("red.release.gpu.global.add.u32 [%0], 1;" ::"l"(p) : "memory"); }
DEVINL void flag_set(uint32_t* p, uint32_t v) { asm volatile("fence.acq_rel.gpu; st.relaxed.gpu.global.u32 [%0], %1;" ::"l"(p), "r"(v) : "memory"); }
DEVINL uint32_t ldg_rlx32(const void* p) { uint32_t v; asm volatile("ld.relaxed.gpu.global.u32 %0, [%1];" : "=r"(v) : "l"(p) : "memory"); return v; }
DEVINL float ex2(float x) { float y; asm("ex2.approx.ftz.f32 %0, %1;" : "=f"(y) : "f"(x)); return y; }
DEVINL float rcp(float x) { float y; asm("rcp.approx.ftz.f32 %0, %1;" : "=f"(y) : "f"(x)); return y; }
DEVINL uint32_t opaque(uint32_t x) { return __shfl_sync(~0u, x, threadIdx.x & 31); }
DEVINL uint32_t launder(uint32_t x) { asm volatile("" : "+r"(x)); return x; }
DEVINL void pdl_wait() { asm volatile("griddepcontrol.wait;" ::: "memory"); }
DEVINL void pdl_launch() { asm volatile("griddepcontrol.launch_dependents;" ::: "memory"); }
#define LOGS(cta, i)
#define LOGK(k, i)
#define LOG(cta, i)
#define LOGV(cta, i, v)
#define EV(i, v)
constexpr float SM_SCALE = 0.08838834764831845f * 1.4426950408889634f;

DEVINL void unpack8(uint4 v, float* f) { f[0] = bf_lo(v.x); f[1] = bf_hi(v.x); f[2] = bf_lo(v.y); f[3] = bf_hi(v.y); f[4] = bf_lo(v.z); f[5] = bf_hi(v.z); f[6] = bf_lo(v.w); f[7] = bf_hi(v.w); }
DEVINL uint4 pack8(const float* f) { return make_uint4(pack_bf16(f[0], f[1]), pack_bf16(f[2], f[3]), pack_bf16(f[4], f[5]), pack_bf16(f[6], f[7])); }
DEVINL void ln_row(float* f) {
  float s = 0.f;
#pragma unroll
  for (int i = 0; i < 40; i++) s += f[i];
#pragma unroll
  for (int o = 1; o < 16; o <<= 1) s += __shfl_xor_sync(~0u, s, o);
  const float mean = s * (1.f / 640.f); float q = 0.f;
#pragma unroll
  for (int i = 0; i < 40; i++) { f[i] -= mean; q = fmaf(f[i], f[i], q); }
#pragma unroll
  for (int o = 1; o < 16; o <<= 1) q += __shfl_xor_sync(~0u, q, o);
  const float rs = rsqrtf(q * (1.f / 640.f) + 1e-5f);
#pragma unroll
  for (int i = 0; i < 40; i++) f[i] *= rs;
}

struct ArgsA {
  const bf16* x; const bf16* mem0; char* comm; uint32_t* flags; const bf16* wr; const bf16* wi; const char* wq; const char* wo;
  int layer; int ta[4], tb[4], tc[2];
};

#define VP 4
#define HELD 0x2557
#define PRE 4
#define VPRE0 2
#define VPRE1 4
#define R0 2
#define TRK 30
#define TEXP 200
#define TRD 0
#define TKV 300
#define KB1 5
#define W2D 0
#define WD 4
#define VPW 2
#define P1F 1
#define W0D 0
#define XD 0
#define TSF 1
#define XP 0
#define PW 1
#define VXE 0
#define LA 0
#define KB2 9
#define KB3 13
#define TSE 7
#define PRP 0
#define W1D 60
constexpr int C_WV = 0;
constexpr int C_WO = 81920;
constexpr int C_KV = 163840;
constexpr int C_M  = C_KV + 24576;
constexpr int C_QK = C_M + 10240;
constexpr int C_VP = C_QK + 4096;
constexpr int C_S  = C_VP + 4096;
constexpr int C_O  = C_S + 2048;
constexpr int C_R  = C_O + 2048;
constexpr int C_T  = C_R + 256;
constexpr int S_BAR = 229376;
constexpr int S_END = S_BAR + 256;
enum { BAR_QK = 2, BAR_O = 3, BAR_H = 4, BAR_X = 5, BAR_W = 7  , BAR_E = 9, BAR_M1 = 10  , BAR_M3 = 12, BAR_M2 = 13   };
constexpr int B_W = 0, B_S = 8, B_W2 = 16, B_KV = 24, B_WV = 40, B_WO = 48;
constexpr int G2_OFF = 0x130000, TS_OFF = 0x11000;

#define FEN() asm volatile("pmevent 0;" ::: "memory")
#define SCHED(x, c) asm volatile("{.reg .pred p; setp.eq.u32 p, %0, %1; @p exit;}" ::"r"(x), "r"(0x7fff0001u + 2 * (c)) : "memory")
DEVINL uint32_t g1page(uint32_t L) { L = ((L & 7) | ((L & 24) << 2)) << 1; return (L | (__popc(L & 0xb2) & 1)) << 12; }
DEVINL void spin_until(uint32_t t) {
  asm volatile("{.reg .pred p; .reg .b32 c; .reg .b64 w;\nS0: mov.u64 w, %%clock64; cvt.u32.u64 c, w; sub.u32 c, %0, c; setp.lt.u32 p, c, 16384; @p bra.uni S0;}" ::"r"(t) : "memory");
}
DEVINL uint32_t wait_until(uint32_t t, uint32_t z) { uint32_t r;
  asm volatile("{.reg .pred p; .reg .b32 c,x,y; .reg .b64 w;\nT0: .branchtargets L0, L1, L2, L3, L4, L5, L6, L7, L8, L9, L10;\n mov.u32 x, %2;\n"
               "mov.u64 w, %%clock64; cvt.u32.u64 c, w; sub.u32 c, %1, c; setp.ge.u32 p, c, 16384; @p bra.uni L0;\n"
               "S0: mov.u64 w, %%clock64; cvt.u32.u64 c, w; sub.u32 c, %1, c; setp.gt.s32 p, c, 40; @p bra.uni S0;\n"
               "mad.lo.s32 c, c, 37, 1200; shr.s32 c, c, 8; max.s32 c, c, 0;\nbrx.idx.uni c, T0;\n"
               "L10: mul.lo.u32 x, x, x; L9: mul.lo.u32 x, x, x; L8: mul.lo.u32 x, x, x; L7: mul.lo.u32 x, x, x; L6: mul.lo.u32 x, x, x; L5: mul.lo.u32 x, x, x; L4: mul.lo.u32 x, x, x; L3: mul.lo.u32 x, x, x; L2: mul.lo.u32 x, x, x; L1: mul.lo.u32 x, x, x; L0: mov.u32 %0, x;}" : "=r"(r) : "r"(t), "r"(z) : "memory"); return r;
}
DEVINL void gtime(uint32_t& G16, uint32_t& C) {
  asm volatile("{.reg .b64 w; .reg .b32 g,g0,a;\n mov.u64 w, %%clock64; cvt.u32.u64 %1, w; mov.u64 w, %%globaltimer; cvt.u32.u64 g0, w; mul.lo.u32 a, g0, -11;\n"
               "mov.u64 w, %%globaltimer; cvt.u32.u64 g, w; add.u32 a, a, g; mov.u64 w, %%globaltimer; cvt.u32.u64 g, w; add.u32 a, a, g; mov.u64 w, %%globaltimer; cvt.u32.u64 g, w; add.u32 a, a, g; mov.u64 w, %%globaltimer; cvt.u32.u64 g, w; add.u32 a, a, g; mov.u64 w, %%globaltimer; cvt.u32.u64 g, w; add.u32 a, a, g; mov.u64 w, %%globaltimer; cvt.u32.u64 g, w; add.u32 a, a, g; mov.u64 w, %%globaltimer; cvt.u32.u64 g, w; add.u32 a, a, g; mov.u64 w, %%globaltimer; cvt.u32.u64 g, w; add.u32 a, a, g; mov.u64 w, %%globaltimer; cvt.u32.u64 g, w; add.u32 a, a, g; mov.u64 w, %%globaltimer; cvt.u32.u64 g, w; add.u32 a, a, g; mov.u64 w, %%globaltimer; cvt.u32.u64 g, w; add.u32 a, a, g; \n mul.lo.u32 a, a, 341; shr.u32 a, a, 8; mad.lo.u32 %0, g0, 16, a;}" : "=r"(G16), "=r"(C)::"memory");
}
DEVINL uint32_t pack_tag(float lo, float hi, uint32_t tg) {
  const uint32_t w = pack_bf16(lo, __uint_as_float(tg | 0x3F800000u)), a = __float_as_uint(hi) + (tg ^ 0x10000u); uint32_t r;
  asm("lop3.b32 %0, %1, %2, 0xFFFE0000, 0xE4;" : "=r"(r) : "r"(a), "r"(w)); return r;
}
DEVINL float ex2v(float x) { float y; asm volatile("ex2.approx.ftz.f32 %0, %1;" : "=f"(y) : "f"(x)); return y; }
DEVINL void load_kv(uint32_t sb, int h, int j, int s) {
  asm volatile("{.reg .pred p; elect.sync _|p, 0xffffffff;\n fence.proxy.async.global;\n @p mbarrier.arrive.expect_tx.shared::cta.b64 _, [%2], 12288;\n"
               " @p cp.async.bulk.shared::cluster.global.mbarrier::complete_tx::bytes [%0], [%1], 12288, [%2];}"
               ::"r"(sb + C_KV + (s & 1) * 12288), "l"(g_kv + (size_t)(s * 32 + h) * 16384 + j * 4096), "r"(sb + S_BAR + B_KV + (s & 1) * 8) : "memory");
}

template <int KH>
DEVINL void chain_mma(uint32_t sb0, const ArgsA& args) {
  const int lane = threadIdx.x & 31, mg = (threadIdx.x >> 5) & 3, mi = lane >> 3, r = lane & 7;
  const uint32_t aW = opaque(sb0 + (uint32_t)(((mi >> 1) * 8 + r) * 128 + (((mg + 4 * (mi & 1)) ^ r) << 4)));
  const uint32_t aL = opaque(sb0 + lane * 16);
  const uint32_t aLm = opaque(sb0 + mg * 512 + lane * 16);
#define sb (launder(aL) & ~511u)
  constexpr int OV = C_WV + KH * 40960, OM = C_M + KH * 5120, NF = KH ? 16 : 24;
  auto owo = [](int f) { return C_WO + (KH + 2 * (f >> 3)) * 16384 + (f & 7) * 2048; };
  auto held = [](int k) { return (HELD >> k) & 1; };
  auto rank = [](int k) { return __popc(HELD & ((1 << k) - 1)); };
  uint32_t wq[20][4], wk[20][4];
  mbar_wait(sb + S_BAR + B_W, 0);
#pragma unroll
  for (int k = 0; k < 12; k++) { ldsm4t(wq[k], aW + OV + k * 2048); ldsm4t(wk[k], aW + C_WO + KH * 40960 + k * 2048); }
  bar_arrive(BAR_H, 288);
  mbar_wait(sb + S_BAR + B_W2, 0);
#pragma unroll
  for (int k = 12; k < 20; k++) { ldsm4t(wq[k], aW + OV + k * 2048); ldsm4t(wk[k], aW + C_WO + KH * 40960 + k * 2048); }
  bar_sync(BAR_E, 384);
  mbar_wait(sb + S_BAR + B_WV, 0);
  uint32_t sx = args.layer << 16;
#pragma unroll 1
  while (true) {
    uint32_t v[20][4], b[10][4];
    {
      const uint32_t o = launder(aLm) - sb, on = (sx >> 16) != (uint32_t)args.layer;
      const char* p = args.comm + lds32(sb + C_T + KH * 1024 + 4 + (o >> 1));
      constexpr int NB = KH ? VPRE1 : VPRE0;
      const uint32_t zero = (uint32_t)(uintptr_t)p & 1, tt = lds32(sb + C_R + 48) + args.tb[0]; uint32_t av = aW;
#pragma unroll
      for (int k = 0; k < 20; k++) if (held(k) && rank(k) < NB) { ldsm4t(v[k], av + OV + k * 2048); if (rank(k) % VPW == VPW - 1 && rank(k) < NB - 1) av = aW + (v[k][0] & zero); }
      p += wait_until(tt, zero);
      uint4 a = ldg_rlx128(p);
      __syncwarp();
#pragma unroll
      for (int k = 0; k < 20; k++) if (held(k) && rank(k) >= NB) { ldsm4t(v[k], av + OV + k * 2048); if ((rank(k) - NB) % VPW == VPW - 1) av = aW + (v[k][0] & zero); }
      SCHED(o ^ on, 29);
      if (on) sts128(aLm + OM, a);
      if (__builtin_expect(__any_sync(~0u, on && (((a.x ^ sx) | (a.z ^ sx)) & 0x10000u)), 0)) {
        int lim = 0;
        do a = ldg_rlx128(p); while (__any_sync(~0u, (((a.x ^ sx) | (a.z ^ sx)) & 0x10000u) && ++lim < POLL_LIMIT));
        sts128(aLm + OM, a);
      }
      bar_sync(BAR_W + KH, 128);
      ldsm4t(b[0], aL + OM); ldsm4t(b[1], aL + OM + 512);
    }
    float cq[4], ck[4], cv[4];
    static_for<0, 20>([&](auto I) {
      constexpr int k = I.value, p = k >> 1;
      const uint32_t b0 = b[p][(k & 1) * 2], b1 = b[p][(k & 1) * 2 + 1];
      if (k == 0) { mma16816z(cv, v[0], b0, b1); mma16816z(cq, wq[k], b0, b1); mma16816z(ck, wk[k], b0, b1); }
      else { if (k < 20 - VP) mma16816(cv, v[k], b0, b1); mma16816(cq, wq[k], b0, b1); mma16816(ck, wk[k], b0, b1); }
      if (k == KB1) bar_sync(BAR_M1 + KH, 160);
      if (k == KB2) bar_sync(BAR_M2 + KH, 160);
      if (k == KB3) bar_sync(BAR_M3, 320);
      static_for<2, 10>([&](auto J) {
        constexpr int q = J.value, st = q < 4 ? 0 : q < 6 ? KB1 : q < 8 ? KB2 : KB3;
        if constexpr (k == (2 * q - 3 > st ? 2 * q - 3 : st)) ldsm4t(b[q], aL + OM + q * 512); });
      if constexpr (k + 3 < 20 - VP && !((HELD >> (k + 3)) & 1)) ldsm4t(v[k + 3], aW + OV + (k + 3) * 2048);
      if (k >= 20 - VP && k < 20 - VP + PRE && !held(k)) ldsm4t(v[k], aW + OV + k * 2048);
      if (P1F && (k & 1) && k >= P1F && k < 19) FEN();
    });
    stsm4(aLm + C_QK + KH * 2048, pack_bf16(cq[0], cq[1]), pack_bf16(cq[2], cq[3]), pack_bf16(ck[0], ck[1]), pack_bf16(ck[2], ck[3]));
    bar_arrive(BAR_QK, 384);
    FEN();
    const uint32_t l8 = (launder(aL) & 511) >> 1, px = lds32(sb + C_R + 80);
#pragma unroll
    for (int k = 20 - VP + PRE; k < 20; k++) if (!held(k)) ldsm4t(v[k], aW + OV + k * 2048);
#pragma unroll
    for (int k = 20 - VP; k < 20; k++) {
      const int p = k >> 1, q = k - 20 + VP; const uint32_t b0 = b[p][(k & 1) * 2], b1 = b[p][(k & 1) * 2 + 1];
      if (q % 3 == 0) mma16816(cv, v[k], b0, b1); else if (q == 1) mma16816z(cq, v[k], b0, b1); else if (q == 2) mma16816z(ck, v[k], b0, b1);
      else if (q % 3 == 1) mma16816(cq, v[k], b0, b1); else mma16816(ck, v[k], b0, b1);
    }
    if (VP >= 3) {
#pragma unroll
      for (int i = 0; i < 4; i++) cv[i] += cq[i] + ck[i];
    }
    { const uint32_t vx = pack_bf16(cv[0], cv[1]), vy = pack_bf16(cv[2], cv[3]);
      const uint32_t av = aLm - l8 + C_VP + KH * 256;
      stasync64(av + 2048 + px, vx, vy, sb + S_BAR + B_S + px);
      sts64(av, vx, vy);
      __syncwarp();
      if (l8 == 0) mbar_arrive(sb + S_BAR + B_S); }
    sx += 0x10000;
    if ((sx >> 16) == args.layer + 64u) break;
    uint32_t w[NF][4];
    {
      const uint32_t zero = px & 1; uint32_t a = aW;
      const bool tsw = KH == 1 && __any_sync(~0u, launder(aLm) == aL); uint2 ts = make_uint2(0, 0); uint4 cal = make_uint4(0, 0, 0, 0);
      if ((sx >> 16) == args.layer + 1u) mbar_wait(sb + S_BAR + B_WO, 0);
#pragma unroll
      for (int f = 0; f < 8 + XP; f++) { ldsm4t(w[f], a + owo(f));
        if (KH == 1 && f == TSF && tsw) { ts = ldg_rlx64(args.comm + TS_OFF + l8); cal = lds128(sb + C_R + 64); }
      if (KH == 1 && f == TSE && tsw) {
        const uint32_t d0 = ts.x - cal.x, d1 = ts.y - cal.x;
        const int dt = (int)__reduce_max_sync(~0u, max(d0 < 32768u ? d0 : 0u, d1 < 32768u ? d1 : 0u));
        sts32(sb + C_R + 48, cal.y + min((dt * cal.z) >> 16, 8192u));
      }
        uint32_t d = w[f][0] & zero;
#pragma unroll
        for (int q = 0; q < TRD; q++) d = __popc(d);
        if (f % PW == PW - 1) a = aW + d; }
    }
    const uint32_t go = lds32(sb + C_T + KH * 1024 + ((launder(aLm) - sb) >> 1));
    SCHED(go, 30);
    bar_sync(BAR_O, 384);
    uint32_t ob[16];
#pragma unroll
    for (int p = 0; p < 4; p++) ldsm4t(ob + 4 * p, aL + C_O + p * 512);
    __syncwarp();
    float r0, r1; uint32_t y0, y1;
    { const uint2 rr = lds64(sb + C_R + 128 + ((launder(aL) >> 1) & 24)); r0 = rcp(__uint_as_float(rr.x)); r1 = rcp(__uint_as_float(rr.y)); }
    constexpr int RA = KH ? 0 : R0;
    static_for<0, NF>([&](auto I) {
      constexpr int f = I.value, k = f & 7; const uint32_t* A = w[f];
      if (k == 0) mma16816z(cq, A, ob[0], ob[1]); else if (k == 1) mma16816z(ck, A, ob[2], ob[3]);
      else if (k & 1) mma16816(ck, A, ob[2 * k], ob[2 * k + 1]); else mma16816(cq, A, ob[2 * k], ob[2 * k + 1]);
      if (f == 5 && RA) {
#pragma unroll
        for (int q = XP; q < XP + RA; q++) ldsm4t(w[8 + q], aW + owo(8 + q));
        FEN();
      }
      if constexpr (f >= 8 && (f & 1) && f + WD < NF && (LA || k + WD < 8)) {
        const uint32_t a = aW + (A[0] & go & 1); ldsm4t(w[f + WD - 1], a + owo(f + WD - 1)); ldsm4t(w[f + WD], a + owo(f + WD)); }
      if constexpr (XD != 0) { if (f == 15) spin_until(clk() + XD); }
      if (k == 7) { y0 = pack_tag((cq[0] + ck[0]) * r0, (cq[1] + ck[1]) * r1, sx & 0x10000u); y1 = pack_bf16((cq[2] + ck[2]) * r0, (cq[3] + ck[3]) * r1);
        stg_rlx64(args.comm + go + (f < 8 ? 0 : f < 16 ? 0x30000 : 0x100000), y0, y1); }
      if (f == 7) {
        if constexpr ((KH ? W1D : W0D) != 0) spin_until(clk() + (KH ? W1D : W0D)); else FEN();
#pragma unroll
        for (int q = XP + RA; q < WD; q++) ldsm4t(w[8 + q], aW + owo(8 + q));
      }
      if constexpr (!LA && f == 15 && NF > 16) { FEN();
#pragma unroll
        for (int q = 0; q < WD; q++) ldsm4t(w[16 + q], aW + owo(16 + q)); }
      if (f >= 8 && k == 3) SCHED(y0 & y1 & go, 40 + f);
      else if (f >= 7 && (f & 1)) FEN();
    });
  }
}

#undef sb
DEVINL void chain_helper(uint32_t sb, uint32_t px, int h, int j, const ArgsA& args, const CUtensorMap* tq, const CUtensorMap* tk, const CUtensorMap* tv, const CUtensorMap* to) {
  const int c = 2 * h + j;
  const uint32_t bW = sb + S_BAR + B_W, bS = sb + S_BAR + B_S, bKV = sb + S_BAR + B_KV;
  const uint32_t lane0 = opaque(threadIdx.x & 31);
  const uint32_t warp = __reduce_max_sync(~0u, (threadIdx.x >> 5) & 3);
  { const int tid = threadIdx.x - 256;
    if (tid == 0) { mbar_arrive_tx(bW, 98304); mbar_arrive_tx(bW + B_W2, 65536); mbar_arrive_tx(bW + B_WV, 81920); mbar_arrive_tx(bW + B_WO, 81920);
#pragma unroll 1
      for (int q = 0; q < 10; q++) { const int i = (q & 1) * 5 + (q >> 1); const uint32_t bar = q < 6 ? bW : bW + B_W2;
        tma_2d(sb + C_WV + i * 8192, tq, h * 128 + j * 64, i * 64, bar); tma_2d(sb + C_WO + i * 8192, tk, h * 128 + j * 64, i * 64, bar); } }
    uint32_t G0, C0; gtime(G0, C0);
    if (warp == 0) sts64(sb + C_R + 96, G0, C0);
    { const uint32_t g = lane0 >> 2, t = lane0 & 3;
      sts128(sb + C_T + 2048 + tid * 16, make_uint4(g1page(c >> 1) + (c & 1) * 2048 + (warp == 0 ? 0 : warp == 1 ? 0x30000 : 0x100000) + ((g >> 2) * 4 + t) * 64 + (g & 3) * 16,
                                                    g1page(((t >> 1) + (g >> 2) * 2) * 4 + warp) + G2_OFF + (c >> 4) * 1024 + (t & 1) * 512 + (c & 15) * 32 + (g & 3) * 8,
                                                    g1page((h & 3) * 4 + (warp == 2 ? 2 : 1)) + G2_OFF + (warp == 1 ? 1024 : warp == 3 ? 2048 : 0) + lane0 * 16, (g & 1) ? 0x3F800000u : 0x00003F80u)); }
    sts32(sb + C_R + 80, px); sts32(sb + C_R + 48, C0 - 65536);
#pragma unroll
    for (int kh = 0; kh < 2; kh++)
      sts64(sb + C_T + kh * 1024 + tid * 8, g1page(j * 16 + kh * 8 + (tid >> 4)) + (tid & 8) * 256 + h * 64 + (tid & 7) * 8, g1page((h & 3) * 4) + G2_OFF + kh * 2048 + tid * 16);
#pragma unroll
    for (int i = 0; i < 5; i++) { const int q = tid + i * 128, n = q & 7, d0 = (q >> 3) * 8; const uint4 v = *(const uint4*)(args.mem0 + n * 640 + d0); const uint32_t w[4] = {v.x, v.y, v.z, v.w};
#pragma unroll
      for (int e = 0; e < 8; e++) asm volatile("st.shared.u16 [%0], %1;" ::"r"(sb + C_M + (d0 + e) * 16 + n * 2), "h"((unsigned short)(w[e >> 1] >> ((e & 1) * 16))) : "memory"); }
    auto round2 = [&](int q0, int q1) {
#pragma unroll 1
      for (int q = q0; q < q1; q++) { const int i = (q & 1) * 5 + (q >> 1); tma_2d(sb + C_WV + i * 8192, tv, h * 128 + j * 64, i * 64, bW + B_WV); }
#pragma unroll 1
      for (int q = q0; q < q1; q++) { const int i = (q & 1) * 5 + (q >> 1); tma_2d(sb + C_WO + i * 8192, to, j * 320 + (i >> 1) * 64, h * 128 + ((i & 1) ^ j) * 64, bW + B_WO); } };
    if (warp == 0) { bar_sync(BAR_H, 288); if (tid == 0) round2(0, 6); __syncwarp(); }
    bar_sync(BAR_E, 384);
    if (tid == 0) round2(6, 10);
    if (warp == 3) {
      if (tid == 96) LOG(c, 250);
      flag_wait_warp(args.flags + F_KV + h * 32, 2);
      load_kv(sb, h, j, 0); load_kv(sb, h, j, 1); if (tid == 96) LOG(c, 251);
    }
  }
  auto calib = [&]() { uint32_t G, C; gtime(G, C);
    const uint2 o = lds64(sb + C_R + 96); const float rt = (float)(C - o.y) * rcp((float)(G - o.x));
    sts128(sb + C_R + 32, make_uint4(G, C, __float2uint_rn(rt * 65536.f) & 0xffffu, __float_as_uint(rcp(rt)))); __syncwarp(); };
  auto do_export = [&](int s, uint32_t lane) {
    uint32_t k0[2][4], k1[2][4]; uint2 a[4], b[4];
    const uint32_t ak = sb + C_QK + 256 + (lane >> 4) * 512 + (lane & 15) * 16, av = sb + C_VP + (lane >> 3) * 512 + (lane & 7) * 8;
#pragma unroll
    for (int i = 0; i < 2; i++) { ldsm4t(k0[i], ak + i * 1024); ldsm4t(k1[i], ak + i * 1024 + 2048); }
#pragma unroll
    for (int i = 0; i < 4; i++) { a[i] = lds64(av + i * 64); b[i] = lds64(av + i * 64 + 256); }
    char* dst = g_kvm + ((s * 32 + h) * 4096 + j * 1024 + lane * 16);
    const uint32_t tg = (args.layer ^ 1) << 16;
    auto put = [&](char* q, uint32_t x, uint32_t y, uint32_t z, uint32_t w) { stg_rlx128(q, (x & ~0x10000u) | tg, y, (z & ~0x10000u) | tg, w); };
#pragma unroll
    for (int i = 0; i < 2; i++) put(dst + i * 512, hadd2bf(k0[i][0], k1[i][0]), hadd2bf(k0[i][1], k1[i][1]), hadd2bf(k0[i][2], k1[i][2]), hadd2bf(k0[i][3], k1[i][3]));
    put(dst + 2048, hadd2bf(a[0].x, b[0].x), hadd2bf(a[1].x, b[1].x), hadd2bf(a[2].x, b[2].x), hadd2bf(a[3].x, b[3].x));
    put(dst + 2560, hadd2bf(a[0].y, b[0].y), hadd2bf(a[1].y, b[1].y), hadd2bf(a[2].y, b[2].y), hadd2bf(a[3].y, b[3].y));
    stg_rlx32(args.flags + F_KM + h * 32 + j, s + 1);
  };
  auto staged = [&]() { if (warp == 2) bar_arrive(BAR_M3, 320); else if (warp == 1) { bar_arrive(BAR_M2, 160); bar_arrive(BAR_M2 + 1, 160); } else bar_arrive(BAR_M1 + (warp >> 1), 160); };
  if (warp == 0) calib();
  staged();
  int kv_ok = 1;
  uint32_t vx[4][4];
  auto load_vx = [&](int s, uint32_t lane) {
    const uint32_t aVx = sb + C_KV + (s & 1) * 12288 + 4096 + (warp >> 1) * (j ? -4096 : 4096) + (warp & 1) * 1024 + lane * 16, zero = lane >> 5;
#pragma unroll
    for (int i = 0; i < 4; i++) { const uint4 q = lds128(aVx + (i & 1) * 2048 + (i >> 1) * 512); vx[i][0] = q.x ^ zero; vx[i][1] = q.z ^ zero; vx[i][2] = q.y ^ zero; vx[i][3] = q.w ^ zero; }
  };
  uint2 kb[4];
  auto prep = [&](int s, uint32_t lane) {
    if (s < 63) mbar_wait(bKV + (s & 1) * 8, (s >> 1) & 1);
    const uint32_t aK = sb + C_KV + (s & 1) * 12288 + j * 8192 + warp * 1024 + lane * 16;
#pragma unroll
    for (int i = 0; i < 4; i++) kb[i] = lds64(aK + ((warp ^ i) >> 1) * 512 + ((warp ^ i) & 1) * 8);
    if (VXE) load_vx(s, lane);
    asm volatile("{.reg .pred p; setp.eq.u32 p, %2, 32; @p mbarrier.arrive.expect_tx.shared::cta.b64 _, [%0], %1;}" ::"r"(bS), "r"(s < 63 ? 3072 : 2048), "r"(warp * 32 + lane) : "memory");
  };
  prep(0, lane0);
#pragma unroll 1
  for (int s = 0;; s++) {
    const uint32_t ph = s & 1;
    const uint32_t lane = __shfl_sync(~0u, lane0, lane0);
    const uint32_t mi = lane >> 3, r = lane & 7;
    const uint32_t aQ = sb + C_QK + (mi & 1) * 2048 + ((mi >> 1) * 8 + r) * 16;
    const uint32_t aKm = sb + C_QK + 256 + warp * 512 + (lane >> 4) * 2048 + (lane & 15) * 16;
    const uint32_t aH = sb + C_S + warp * 256 + lane * 8, aR = aH + 1024 + px;
    SCHED(aQ ^ aR ^ aKm, 60);
    if (warp == 0) {
      const uint4 cal = lds128(sb + C_R + 32);
      bar_sync(BAR_M3, 320);
      sts32(sb + C_R + 52, 0);
      const uint32_t E = clk(), e16 = cal.x + (uint32_t)__float2int_rn((float)(int)(E - cal.y) * __uint_as_float(cal.w));
      stg_rlx32(args.comm + TS_OFF + c * 4, e16); sts128(sb + C_R + 64, make_uint4(e16, E, cal.z, 0));
    }
    if (s == 63) { bar_sync(BAR_QK, 384); mbar_wait(bS, 1); if (warp == 3) do_export(63, lane); break; }
    {
      uint32_t qa[4][4], km[4]; float s0[4], s1[4], s2[4];
      bar_sync(BAR_QK, 384);
      ldsm4t(qa[0], aQ + warp * 512); ldsm4t(km, aKm); ldsm4t(qa[1], aQ + (warp ^ 1) * 512); ldsm4t(qa[2], aQ + (warp ^ 2) * 512); ldsm4t(qa[3], aQ + (warp ^ 3) * 512);
      mma16816z(s0, qa[0], kb[0].x, kb[0].y); mma16816z(s2, qa[0], km[0], km[1]); mma16816z(s1, qa[1], kb[1].x, kb[1].y);
      FEN();
      mma16816(s2, qa[0], km[2], km[3]); mma16816(s0, qa[2], kb[2].x, kb[2].y); mma16816(s1, qa[3], kb[3].x, kb[3].y);
      const uint32_t w0 = pack_bf16((s0[0] + s0[2]) + (s1[0] + s1[2]), (s0[1] + s0[3]) + (s1[1] + s1[3]));
      const uint32_t w1 = pack_bf16(s2[0] + s2[2], s2[1] + s2[3]);
      stasync64(aR, w0, w1, bS + px);
      sts64(aH, w0, w1);
    }
    {
      uint32_t sl[5];
      const uint32_t a8 = sb + lane * 8, av = a8 + C_VP + warp * 1024;
      const uint32_t aO = sb + C_O + ((warp >> 1) * 64 + (warp & 1) * 16 + (mi & 1) * 32 + (mi >> 1) * 8 + r) * 16, aU = sb + C_R + (lane & 28);
      bar_sync(BAR_X, 128);
      { uint2 t[4];
#pragma unroll
        for (int u = 0; u < 4; u++) t[u] = lds64(a8 + C_S + u * 256);
        if (!VXE) load_vx(s, lane);
#pragma unroll
        for (int u = 0; u < 4; u++) sl[u] = t[u].x;
        sl[4] = pack_bf16((bf_lo(t[0].y) + bf_lo(t[1].y)) + (bf_lo(t[2].y) + bf_lo(t[3].y)), (bf_hi(t[0].y) + bf_hi(t[1].y)) + (bf_hi(t[2].y) + bf_hi(t[3].y))); }
      mbar_wait(bS, ph);
      uint32_t vm[2][4];
      { uint2 t[4];
#pragma unroll
        for (int u = 0; u < 4; u++) t[u] = lds64(a8 + C_S + 1024 + u * 256);
#pragma unroll
        for (int u = 0; u < 4; u++) sl[u] = hadd2bf(sl[u], t[u].x);
        sl[4] = hadd2bf(hadd2bf(hadd2bf(sl[4], t[0].y), t[1].y), hadd2bf(t[2].y, t[3].y)); }
      uint32_t m2 = hmax2bf(hmax2bf(hmax2bf(sl[0], sl[1]), hmax2bf(sl[2], sl[3])), sl[4]);
      const uint32_t x1 = __shfl_xor_sync(~0u, m2, 1), x2 = __shfl_xor_sync(~0u, m2, 2), x3 = __shfl_xor_sync(~0u, m2, 3);
#pragma unroll
      for (int i = 0; i < 4; i++) { const uint2 q = lds64(av + i * 256); vm[i >> 1][(i & 1) * 2] = q.x; vm[i >> 1][(i & 1) * 2 + 1] = q.y; }
      float sv[10];
#pragma unroll
      for (int u = 0; u < 5; u++) { sv[2 * u] = bf_lo(sl[u]) * SM_SCALE; sv[2 * u + 1] = bf_hi(sl[u]) * SM_SCALE; }
      FEN();
      m2 = hmax2bf(hmax2bf(m2, x1), hmax2bf(x2, x3));
      const float mx = fmaxf(bf_lo(m2), bf_hi(m2));
      float o0[4], o1[4];
#pragma unroll
      for (int i = 0; i < 10; i++) sv[i] = fmaf(mx, -SM_SCALE, sv[i]);
      sv[8] = ex2v(sv[8]); sv[9] = ex2v(sv[9]);
#pragma unroll
      for (int i = 0; i < 8; i++) sv[i] = ex2v(sv[i]);
      { const uint32_t p = pack_bf16(sv[8], sv[9]); mma16816z(o0, vm[0], p, p); mma16816z(o1, vm[1], p, p); }
      { const uint32_t p0 = pack_bf16(sv[0], sv[1]), p1 = pack_bf16(sv[2], sv[3]); mma16816(o0, vx[0], p0, p1); mma16816(o1, vx[2], p0, p1); }
      { const uint32_t p0 = pack_bf16(sv[4], sv[5]), p1 = pack_bf16(sv[6], sv[7]); mma16816(o0, vx[1], p0, p1); mma16816(o1, vx[3], p0, p1); }
      float su = (((sv[8] + sv[9]) + ((sv[0] + sv[1]) + (sv[2] + sv[3]))) + (sv[4] + sv[5])) + (sv[6] + sv[7]);
      { const float a1 = __shfl_xor_sync(~0u, su, 1), a2 = __shfl_xor_sync(~0u, su, 2), a3 = __shfl_xor_sync(~0u, su, 3); su = (su + a1) + (a2 + a3); }
      sts32(aU + 128, __float_as_uint(su));
      stsm4(aO, pack_bf16(o0[0], o0[1]), pack_bf16(o0[2], o0[3]), pack_bf16(o1[0], o1[1]), pack_bf16(o1[2], o1[3]));
      bar_sync(BAR_O, 384);
    }
    const uint32_t t0 = lds32(sb + C_R + 48);
    const uint4 xo = lds128(sb + C_T + 2048 + warp * 512 + lane * 16);
    uint32_t rdy = 0;
    const uint32_t tag = (s + args.layer + 1) & 1, tm = 0u - tag;
    if (warp == 3) {
      if (lane == 0) { LOGS(c, s); LOGV(c, 192 + (s >> 1), clk()); }
      if (((s + 2) >> 1) >= kv_ok) rdy = ldg_rlx32(args.flags + F_KV + h * 32 + lane);
      spin_until(t0 + args.tc[0]);
      do_export(s, lane);
      if (lane == 0) LOG(c, 64 + s);
    }
    if (warp == 2) calib();
    if (warp < 2 || (warp == 2 && !(c & 16))) {
      const char* p = args.comm + xo.x; char* g2w = args.comm + xo.y;
      const uint32_t s0 = (lane & 8) ? 0u : xo.w, s1 = (lane & 8) ? xo.w : 0u;
      int lim = 0; bool bad;
      p += wait_until(t0 + args.ta[warp == 0 ? 0 : warp == 2 ? 3 : 1 + ((c >> 4) & 1)], lane >> 5);
      do {
        uint4 a[4]; float z0[4], z1[4], y[4];
#pragma unroll
        for (int i = 0; i < 4; i++) a[i] = ldg_rlx128(p + i * 512);
        ++lim;
        { const uint32_t A[4] = {a[0].x, a[0].y, a[0].z, a[0].w}; mma16816z(z0, A, s0, s1); }
        { const uint32_t A[4] = {a[1].x, a[1].y, a[1].z, a[1].w}; mma16816z(z1, A, s0, s1); }
        { const uint32_t A[4] = {a[2].x, a[2].y, a[2].z, a[2].w}; mma16816(z0, A, s0, s1); }
        { const uint32_t A[4] = {a[3].x, a[3].y, a[3].z, a[3].w}; mma16816(z1, A, s0, s1); }
        const uint32_t m0 = launder((a[0].x ^ tm) | (a[0].z ^ tm)), m1 = launder((a[1].x ^ tm) | (a[1].z ^ tm)), m2 = launder((a[2].x ^ tm) | (a[2].z ^ tm)), m3 = launder((a[3].x ^ tm) | (a[3].z ^ tm));
        bad = __any_sync(~0u, ((launder(m0 | m1 | m2) | m3) & 0x10000u) && lim < POLL_LIMIT);
#pragma unroll
        for (int i = 0; i < 4; i++) y[i] = z0[i] + z1[i];
        const bool odd = lane & 1; const float k0 = odd ? y[2] : y[0], k1 = odd ? y[3] : y[1], e0 = odd ? y[0] : y[2], e1 = odd ? y[1] : y[3];
        const float o0 = __shfl_xor_sync(~0u, e0, 1) + __shfl_xor_sync(~0u, e0, 17), o1 = __shfl_xor_sync(~0u, e1, 1) + __shfl_xor_sync(~0u, e1, 17);
        const float q0 = k0 + __shfl_xor_sync(~0u, k0, 16), q1 = k1 + __shfl_xor_sync(~0u, k1, 16);
        const uint32_t w0 = pack_tag(odd ? o0 : q0, odd ? o1 : q1, tag << 16), w1 = pack_bf16(odd ? q0 : o0, odd ? q1 : o1);
        if (!bad) stg_rlx64(g2w, w0, w1);
      } while (bad);
      if (lane == 0 && warp == 0) LOGV(c, 128 + s, lim);
      if (lane == 0) { EV(warp, clk() - t0); EV(3 + warp, lim); }
    }
    if (!PRP || warp != 1) prep(s + 1, lane); else kb[0] = kb[1] = kb[2] = kb[3] = make_uint2(0, 0);
    {
      const char* p = args.comm + xo.z;
      const uint32_t aMw = sb + C_M + 2048 + (warp == 3 ? 5120 : warp * 1024) + lane * 16;
      int lim = 0; bool bad;
      p += wait_until(t0 + args.tb[warp == 3 ? 1 : warp + 1], lane >> 5);
      if (warp == 0 || warp == 3) {
        do { const uint4 a = ldg_rlx128(p), b = ldg_rlx128(p + 512); ++lim;
          sts128(aMw, a); sts128(aMw + 512, b);
          bad = __any_sync(~0u, ((launder((a.x ^ tm) | (a.z ^ tm)) | launder((b.x ^ tm) | (b.z ^ tm))) & 0x10000u) && lim < POLL_LIMIT);
        } while (bad);
      } else {
        do { uint4 a[4]; uint32_t m[4]; ++lim;
#pragma unroll
          for (int i = 0; i < 4; i++) a[i] = ldg_rlx128(p + (i & 1) * 512 + (i >> 1) * 2048);
#pragma unroll
          for (int i = 0; i < 4; i++) { sts128(aMw + (i & 1) * 512 + (i >> 1) * 5120, a[i]); m[i] = launder((a[i].x ^ tm) | (a[i].z ^ tm)); }
          bad = __any_sync(~0u, ((launder(m[0] | m[1] | m[2]) | m[3]) & 0x10000u) && lim < POLL_LIMIT);
        } while (bad);
      }
      staged();
      if (lane == 0 && warp < 3) { EV(6 + warp, clk() - t0); EV(9 + warp, lim); }
    }
    if (PRP && warp == 1) prep(s + 1, lane);
    if (warp == 3 && s < 61) {
      spin_until(t0 + args.tc[1]);
      if (((s + 2) >> 1) >= kv_ok) {
        for (int n = 0; (kv_ok = __clz(__brev(~__ballot_sync(~0u, rdy >= 2)))) <= ((s + 2) >> 1) && n < POLL_LIMIT; n++) rdy = ldg_rlx32(args.flags + F_KV + h * 32 + lane);
        asm volatile("fence.acquire.gpu;" ::: "memory");
      }
      load_kv(sb, h, j, s + 2);
    }
  }
}

#define PF0 14
#define NPROBE 3
#define OPACE 400
constexpr int G_ST = 163840;
constexpr int B_FULL = 64, B_EMPTY = 96, B_RB = 128, B_WD = 136, B_ROLE = 144, B_PROG = 152, B_WF = 160  ;
enum { BAR_T = 1  , BAR_G = 3  , BAR_V = 5   };
DEVINL uint64_t mkdesc(uint32_t a, uint32_t lbo, uint32_t sbo, uint32_t sw) { return (uint64_t)((a & 0x3FFFF) >> 4) | ((uint64_t)(lbo >> 4) << 16) | ((uint64_t)(sbo >> 4) << 32) | ((uint64_t)sw << 62); }
DEVINL void wgmma_n128(float* d, uint64_t a, uint64_t b, int acc) {
  asm volatile("{.reg .pred p; setp.ne.b32 p, %66, 0; wgmma.mma_async.sync.aligned.m64n128k16.f32.bf16.bf16 {%0,%1,%2,%3,%4,%5,%6,%7,%8,%9,%10,%11,%12,%13,%14,%15,%16,%17,%18,%19,%20,%21,%22,%23,%24,%25,%26,%27,%28,%29,%30,%31,%32,%33,%34,%35,%36,%37,%38,%39,%40,%41,%42,%43,%44,%45,%46,%47,%48,%49,%50,%51,%52,%53,%54,%55,%56,%57,%58,%59,%60,%61,%62,%63}, %64, %65, p, 1, 1, 0, 1;}"
               : "+f"(d[0]),"+f"(d[1]),"+f"(d[2]),"+f"(d[3]),"+f"(d[4]),"+f"(d[5]),"+f"(d[6]),"+f"(d[7]),"+f"(d[8]),"+f"(d[9]),"+f"(d[10]),"+f"(d[11]),"+f"(d[12]),"+f"(d[13]),"+f"(d[14]),"+f"(d[15]),"+f"(d[16]),"+f"(d[17]),"+f"(d[18]),"+f"(d[19]),"+f"(d[20]),"+f"(d[21]),"+f"(d[22]),"+f"(d[23]),"+f"(d[24]),"+f"(d[25]),"+f"(d[26]),"+f"(d[27]),"+f"(d[28]),"+f"(d[29]),"+f"(d[30]),"+f"(d[31]),"+f"(d[32]),"+f"(d[33]),"+f"(d[34]),"+f"(d[35]),"+f"(d[36]),"+f"(d[37]),"+f"(d[38]),"+f"(d[39]),"+f"(d[40]),"+f"(d[41]),"+f"(d[42]),"+f"(d[43]),"+f"(d[44]),"+f"(d[45]),"+f"(d[46]),"+f"(d[47]),"+f"(d[48]),"+f"(d[49]),"+f"(d[50]),"+f"(d[51]),"+f"(d[52]),"+f"(d[53]),"+f"(d[54]),"+f"(d[55]),"+f"(d[56]),"+f"(d[57]),"+f"(d[58]),"+f"(d[59]),"+f"(d[60]),"+f"(d[61]),"+f"(d[62]),"+f"(d[63]) : "l"(a), "l"(b), "r"(acc));
}
DEVINL void wgmma_n80(float* d, uint64_t a, uint64_t b, int acc) {
  asm volatile("{.reg .pred p; setp.ne.b32 p, %42, 0; wgmma.mma_async.sync.aligned.m64n80k16.f32.bf16.bf16 {%0,%1,%2,%3,%4,%5,%6,%7,%8,%9,%10,%11,%12,%13,%14,%15,%16,%17,%18,%19,%20,%21,%22,%23,%24,%25,%26,%27,%28,%29,%30,%31,%32,%33,%34,%35,%36,%37,%38,%39}, %40, %41, p, 1, 1, 0, 1;}"
               : "+f"(d[0]),"+f"(d[1]),"+f"(d[2]),"+f"(d[3]),"+f"(d[4]),"+f"(d[5]),"+f"(d[6]),"+f"(d[7]),"+f"(d[8]),"+f"(d[9]),"+f"(d[10]),"+f"(d[11]),"+f"(d[12]),"+f"(d[13]),"+f"(d[14]),"+f"(d[15]),"+f"(d[16]),"+f"(d[17]),"+f"(d[18]),"+f"(d[19]),"+f"(d[20]),"+f"(d[21]),"+f"(d[22]),"+f"(d[23]),"+f"(d[24]),"+f"(d[25]),"+f"(d[26]),"+f"(d[27]),"+f"(d[28]),"+f"(d[29]),"+f"(d[30]),"+f"(d[31]),"+f"(d[32]),"+f"(d[33]),"+f"(d[34]),"+f"(d[35]),"+f"(d[36]),"+f"(d[37]),"+f"(d[38]),"+f"(d[39]) : "l"(a), "l"(b), "r"(acc));
}

template <int N, int NST, bool HAND>
DEVINL void gemm_tile(float* acc, uint32_t sb, uint32_t px, int wg, uint32_t u0, int rot, bool lead, int wph) {
  const uint64_t db = N == 128 ? mkdesc(sb, 81920, 1024, 1) : mkdesc(sb, 32768, 256, 3);
#pragma unroll
  for (int i = 0; i < N / 2; i++) acc[i] = 0.f;
  bar_sync(BAR_T + wg, 256);
#pragma unroll 1
  for (int st = 0; st < NST; st++) {
    const uint32_t u = u0 + st, slot = u & 3, ks = (st + rot >= NST ? st + rot - NST : st + rot) * 8;
    if (wph >= 0) mbar_wait(sb + S_BAR + B_WF + (N == 128 ? st * 8 : 0), wph);
    mbar_wait(sb + S_BAR + B_FULL + slot * 8, (u >> 2) & 1);
    const uint64_t da = mkdesc(sb + G_ST + slot * 16384, 16, 1024, 1);
    asm volatile("wgmma.fence.sync.aligned;" ::: "memory");
#pragma unroll
    for (int k = 0; k < 8; k++) {
      const uint64_t a = da + (k >> 2) * 512 + (k & 3) * 2;
      if (N == 128) wgmma_n128(acc, a, db + (ks + k) * 128, 1); else wgmma_n80(acc, a, db + (ks + k) * 32, 1);
    }
    asm volatile("wgmma.commit_group.sync.aligned;" ::: "memory");
    if (HAND && st == NST - 1) bar_arrive(BAR_T + (wg ^ 1), 256);
    if (st > 0) {
      asm volatile("wgmma.wait_group.sync.aligned 1;" ::: "memory");
      if (lead) { const uint32_t e = sb + S_BAR + B_EMPTY + ((u - 1) & 3) * 8; mbar_arrive(e); mbar_arrive_remote(e + px); }
    }
  }
  asm volatile("wgmma.wait_group.sync.aligned 0;" ::: "memory");
  if (lead) { const uint32_t e = sb + S_BAR + B_EMPTY + ((u0 + NST - 1) & 3) * 8; mbar_arrive(e); mbar_arrive_remote(e + px); }
}
DEVINL void wg_publish(int wg) { bar_sync(BAR_G + wg, 160); }
DEVINL uint32_t km_known(uint32_t sb) { uint32_t v; asm volatile("ld.volatile.shared.u32 %0, [%1];" : "=r"(v) : "r"(sb + S_BAR + B_PROG) : "memory"); return __reduce_min_sync(~0u, v); }
DEVINL void km_load(uint4* f, const char* p) {
#pragma unroll
  for (int G = 0; G < 4; G++) f[G] = ldg_rlx128(p + G * 512);
}
DEVINL void km_check(uint4* f, const char* p, uint32_t tg) {
  int n = 0;
  while (__any_sync(~0u, (((f[0].x ^ tg) | (f[0].z ^ tg) | (f[1].x ^ tg) | (f[1].z ^ tg) | (f[2].x ^ tg) | (f[2].z ^ tg) | (f[3].x ^ tg) | (f[3].z ^ tg)) & 0x10000u) && ++n < POLL_LIMIT)) km_load(f, p);
}
DEVINL void km_watcher(uint32_t sb, const uint32_t* p) {
  uint32_t v = 0;
#pragma unroll 1
  for (int n = 0; n < 16 * POLL_LIMIT && v < 64; n++) {
    const uint2 q = ldg_rlx64(p);
    if (min(q.x, q.y) != v) { v = min(q.x, q.y); asm volatile("st.volatile.shared.u32 [%0], %1;" ::"r"(sb + S_BAR + B_PROG), "r"(v) : "memory"); }
    __nanosleep(v < 61 ? 300 : 20);
  }
}

template <int HF>
DEVINL void attend(const float* acc, uint4 (*kf)[4], uint4* kmf, uint4* op, const char* kvp, const char* mp, bf16* orow, int lane, int wg, uint32_t sb, int tile, bool& pend, uint32_t tg) {
  constexpr int NT = HF ? 4 : 2;
  const int g = lane >> 2, t = lane & 3;
  km_check(kmf, mp + lane * 16, tg);
  float sc[NT + 1][4];
#pragma unroll
  for (int k = 0; k < 8; k++) {
    uint32_t qa[4];
#pragma unroll
    for (int i = 0; i < 4; i++) { const float* a = acc + 32 * (k >> 2) + 4 * (k & 3) + 16 * (i >> 1) + 2 * (i & 1); qa[i] = pack_bf16(a[0], a[1]); }
#pragma unroll
    for (int kt = 0; kt <= NT; kt++) {
      const uint4 b = kt < NT ? kf[kt][k >> 1] : kmf[k >> 1];
      if (k == 0) mma16816z(sc[kt], qa, b.x, b.y); else if (k & 1) mma16816(sc[kt], qa, b.z, b.w); else mma16816(sc[kt], qa, b.x, b.y);
    }
  }
  FEN();
  bar_arrive(BAR_T + (wg ^ 1), 256);
  if (pend) {
#pragma unroll
    for (int q = 0; q < 4; q++) { *(uint4*)(orow - 128 * 4096 + q * 32) = op[2 * q]; *(uint4*)(orow - 120 * 4096 + q * 32) = op[2 * q + 1]; }
    wg_publish(wg);
  }
  {
    uint32_t go; asm volatile("{.reg .pred p,q; setp.ne.u32 q, %1, 0; bar.red.and.pred p, %2, 128, q; selp.u32 %0, 1, 0, p;}" : "=r"(go) : "r"((uint32_t)(tile < 30 && km_known(sb) > tile * 2 + 5)), "r"(BAR_V + wg) : "memory");
    pend = __reduce_max_sync(~0u, go); }
  uint4 vf[HF + 1][8], vm[4];
  const char* vp = kvp + 4096 + (g >> 1) * 512 + ((g & 1) * 4 + t) * 16;
  km_load(vm, mp + 2048 + lane * 16);
#pragma unroll
  for (int i = 0; i < 8; i++) vf[0][i] = ldg_ca128(vp + (i >> 2) * 4096 + (i & 3) * 128);
  if (tile < 30) {
#pragma unroll
    for (int i = 0; i < 8; i++) kf[i >> 2][i & 3] = ldg_ca128(kvp + 4 * 32 * 16384 + ((i >> 1) & 1) * 12288 + (i >> 2) * 1024 + (i & 1) * 512 + lane * 16);
  }
  if (pend) km_load(kmf, mp + 4 * 32 * 4096 + lane * 16);
  if (HF) {
#pragma unroll
    for (int i = 0; i < 8; i++) vf[HF][i] = ldg_cg128(vp + 2048 + (i >> 2) * 4096 + (i & 3) * 128);
    if (tile < 30) {
#pragma unroll
      for (int i = 8; i < 16; i++) kf[i >> 2][i & 3] = ldg_cg128(kvp + 4 * 32 * 16384 + ((i >> 1) & 1) * 12288 + (i >> 2) * 1024 + (i & 1) * 512 + lane * 16);
    }
  }
  const float NINF = __int_as_float(0xff800000);
  if (2 * t > g) { sc[NT - 2][0] = NINF; sc[NT - 1][2] = NINF; }
  if (2 * t + 1 > g) { sc[NT - 2][1] = NINF; sc[NT - 1][3] = NINF; }
  sc[NT - 1][0] = NINF; sc[NT - 1][1] = NINF;
  float m0 = fmaxf(sc[NT][0], sc[NT][1]), m1 = fmaxf(sc[NT][2], sc[NT][3]);
#pragma unroll
  for (int kt = 0; kt < NT; kt++) { m0 = fmaxf(m0, fmaxf(sc[kt][0], sc[kt][1])); m1 = fmaxf(m1, fmaxf(sc[kt][2], sc[kt][3])); }
  m0 = fmaxf(fmaxf(m0, __shfl_xor_sync(~0u, m0, 1)), fmaxf(__shfl_xor_sync(~0u, m0, 2), __shfl_xor_sync(~0u, m0, 3)));
  m1 = fmaxf(fmaxf(m1, __shfl_xor_sync(~0u, m1, 1)), fmaxf(__shfl_xor_sync(~0u, m1, 2), __shfl_xor_sync(~0u, m1, 3)));
  m0 *= -SM_SCALE; m1 *= -SM_SCALE;
  float s0 = 0.f, s1 = 0.f; uint32_t p[NT + 1][2];
#pragma unroll
  for (int kt = 0; kt <= NT; kt++) {
    const float a = ex2(fmaf(sc[kt][0], SM_SCALE, m0)), b = ex2(fmaf(sc[kt][1], SM_SCALE, m0)), c = ex2(fmaf(sc[kt][2], SM_SCALE, m1)), d = ex2(fmaf(sc[kt][3], SM_SCALE, m1));
    s0 += a + b; s1 += c + d; p[kt][0] = pack_bf16(a, b); p[kt][1] = pack_bf16(c, d);
  }
  s0 = (s0 + __shfl_xor_sync(~0u, s0, 1)) + (__shfl_xor_sync(~0u, s0, 2) + __shfl_xor_sync(~0u, s0, 3));
  s1 = (s1 + __shfl_xor_sync(~0u, s1, 1)) + (__shfl_xor_sync(~0u, s1, 2) + __shfl_xor_sync(~0u, s1, 3));
  s0 = rcp(s0); s1 = rcp(s1);
  km_check(vm, mp + 2048 + lane * 16, tg);
#pragma unroll
  for (int grp = 0; grp < 4; grp++) {
    float o[4][4];
#pragma unroll
    for (int L = 0; L < 4; L++) {
      mma1688z(o[L], p[NT][0], p[NT][1], L == 0 ? vm[grp].x : L == 1 ? vm[grp].y : L == 2 ? vm[grp].z : vm[grp].w);
#pragma unroll
      for (int kh = 0; kh <= HF; kh++) {
        const uint4 w = vf[kh][(grp >> 1) * 4 + L]; const uint32_t A[4] = {p[2 * kh][0], p[2 * kh][1], p[2 * kh + 1][0], p[2 * kh + 1][1]};
        if (grp & 1) mma16816(o[L], A, w.z, w.w); else mma16816(o[L], A, w.x, w.y);
      }
    }
    op[2 * grp] = make_uint4(pack_bf16(o[0][0] * s0, o[0][1] * s0), pack_bf16(o[1][0] * s0, o[1][1] * s0), pack_bf16(o[2][0] * s0, o[2][1] * s0), pack_bf16(o[3][0] * s0, o[3][1] * s0));
    op[2 * grp + 1] = make_uint4(pack_bf16(o[0][2] * s1, o[0][3] * s1), pack_bf16(o[1][2] * s1, o[1][3] * s1), pack_bf16(o[2][2] * s1, o[2][3] * s1), pack_bf16(o[3][2] * s1, o[3][3] * s1));
  }
}

DEVINL void gemm_consumer(uint32_t sb, uint32_t px, int wg, int pr, int rank, const ArgsA& args) {
  const int lane = opaque(threadIdx.x & 31), w = __reduce_max_sync(~0u, (threadIdx.x >> 5) & 3);
  const bool lead = lane == 0 && w == 0;
  const int rot5 = pr % 5;
  if (wg == 1) bar_arrive(BAR_T, 256);
  if (threadIdx.x == 0) LOG(64 + pr * 2 + rank, 250);
#pragma unroll 1
  for (int tile = wg; tile < 32; tile += 2) {
    float acc[64];
    gemm_tile<128, 5, true>(acc, sb, px, wg, tile * 5, rot5, lead, tile < 2 ? 0 : -1);
    if (tile >= 30 && lead) mbar_arrive(sb + S_BAR + B_WD);
    char* dst = g_kv + (size_t)((tile * 2 + (w >> 1)) * 32 + pr) * 16384 + (w & 1) * 2048 + lane * 16;
    if (rank == 0) {
#pragma unroll
      for (int G = 0; G < 4; G++)
#pragma unroll
        for (int hh = 0; hh < 2; hh++) {
          const float* a = acc + 32 * (G >> 1) + 8 * (G & 1) + 2 * hh;
          *(uint4*)(dst + (G >> 1) * 12288 + hh * 1024 + (G & 1) * 512) = make_uint4(pack_bf16(a[0], a[1]), pack_bf16(a[16], a[17]), pack_bf16(a[4], a[5]), pack_bf16(a[20], a[21]));
        }
    } else {
#pragma unroll
      for (int i = 0; i < 8; i++) {
        const float* a = acc + (i >> 2) * 32 + (i & 3) * 4;
        *(uint4*)(dst + 4096 + (i >> 2) * 4096 + (i & 3) * 512) = make_uint4(movm(pack_bf16(a[0], a[1])), movm(pack_bf16(a[2], a[3])), movm(pack_bf16(a[16], a[17])), movm(pack_bf16(a[18], a[19])));
      }
    }
    wg_publish(wg);
    if ((threadIdx.x & 127) == 0) LOG(64 + pr * 2 + rank, tile);
  }
  if (threadIdx.x == 0) LOG(64 + pr * 2 + rank, 251);
  if (pr < 16) {
    const int h = 2 * pr + rank;
    flag_wait_warp(args.flags + F_KV + h * 32 + 16 + (lane & 1), 2);
    bool pend = false; uint4 op[8], kf[4][4], kmf[4];
#pragma unroll
    for (int i = 0; i < 16; i++) kf[i >> 2][i & 3] = ldg_cg128(g_kv + (size_t)((wg * 2 + (w >> 1)) * 32 + h) * 16384 + ((i >> 1) & 1) * 12288 + (i >> 2) * 1024 + (i & 1) * 512 + lane * 16);
#pragma unroll
    for (int i = 0; i < 8; i++) op[i] = kmf[i & 3] = make_uint4(0, 0, 0, 0);
#pragma unroll 1
    for (int tile = wg; tile < 32; tile += 2) {
      const uint32_t seg = tile * 2 + (w >> 1);
      const char* kvp = g_kv + (size_t)(seg * 32 + h) * 16384;
      const char* mp = g_kvm + (size_t)(seg * 32 + h) * 4096;
      bf16* orow = g_o + (size_t)(tile * 64 + w * 16 + (lane >> 2)) * 4096 + h * 128 + (lane & 3) * 8;
      if ((tile >> 1) == 6) flag_wait_warp(args.flags + F_KV + h * 32 + 30 + (lane & 1), 2);
      float acc[64];
      gemm_tile<128, 5, false>(acc, sb, px, wg, 160 + tile * 5, rot5, lead, tile < 2 ? 1 : -1);
      if ((threadIdx.x & 127) == 96) LOG(64 + pr * 2 + rank, 64 + tile);
      if (!pend) {
        int n = 0;
        while (km_known(sb) <= seg && ++n < 16 * POLL_LIMIT) {}
        km_load(kmf, mp + lane * 16);
      }
      if ((threadIdx.x & 127) == 96) LOG(64 + pr * 2 + rank, 96 + tile);
      if (w & 1) attend<1>(acc, kf, kmf, op, kvp, mp, orow, lane, wg, sb, tile, pend, (args.layer ^ 1) << 16); else attend<0>(acc, kf, kmf, op, kvp, mp, orow, lane, wg, sb, tile, pend, (args.layer ^ 1) << 16);
      if (!pend) {
#pragma unroll
        for (int q = 0; q < 4; q++) { *(uint4*)(orow + q * 32) = op[2 * q]; *(uint4*)(orow + 8 * 4096 + q * 32) = op[2 * q + 1]; }
        wg_publish(wg);
      }
      if ((threadIdx.x & 127) == 0) LOG(64 + pr * 2 + rank, 32 + tile);
    }
  } else {
    const int kq = (pr - 16) >> 2, cg = 2 * (pr & 3) + rank;
#pragma unroll 1
    for (int tile = wg; tile < 32; tile += 2) {
      float acc[40];
      gemm_tile<80, 8, true>(acc, sb, px, wg, 160 + tile * 8, (pr & 3) * 2, lead, tile < 2 ? 1 : -1);
      const bool odd = lane & 1;
      bf16* dst = g_part + (size_t)(kq * 2048 + tile * 64 + w * 16 + (lane >> 2)) * 640 + cg * 80 + (lane & 1) * 8 + (lane & 2) * 2;
#pragma unroll
      for (int q = 0; q < 5; q++)
#pragma unroll
        for (int hh = 0; hh < 2; hh++) {
          const uint32_t A = pack_bf16(acc[8 * q + 2 * hh], acc[8 * q + 2 * hh + 1]), B = pack_bf16(acc[8 * q + 4 + 2 * hh], acc[8 * q + 5 + 2 * hh]);
          const uint32_t x = __shfl_xor_sync(~0u, odd ? A : B, 1);
          *(uint2*)(dst + hh * 8 * 640 + q * 16) = odd ? make_uint2(x, B) : make_uint2(A, x);
        }
      wg_publish(wg);
      if ((threadIdx.x & 127) == 0) LOG(64 + pr * 2 + rank, 32 + tile);
    }
  }
  if (wg == 0) bar_sync(BAR_T, 256);
}

DEVINL void gemm_producer(uint32_t sb, int pr, int rank, const ArgsA& args, const CUtensorMap* tq, const CUtensorMap* tk, const CUtensorMap* tv,
                          const CUtensorMap* to32, const CUtensorMap* tx, const CUtensorMap* tao) {
  const uint32_t bWF = sb + S_BAR + B_WF;
  auto load_w = [&](const CUtensorMap* tm, int col, int st) {
    const int r = ((st + pr) % 5) * 2; mbar_arrive_tx(bWF + st * 8, 32768);
#pragma unroll 1
    for (int i = 0; i < 4; i++) tma_2d(sb + (i & 1) * 81920 + (r + (i >> 1)) * 8192, tm, col + (i & 1) * 64, (r + (i >> 1)) * 64, bWF + st * 8); };
  uint32_t u = 0;
  auto push = [&](const CUtensorMap* tm, int c0, int c1) {
    const uint32_t slot = u & 3, full = sb + S_BAR + B_FULL + slot * 8;
    mbar_wait(sb + S_BAR + B_EMPTY + slot * 8, ((u >> 2) & 1) ^ 1);
    mbar_arrive_tx(full, 16384);
    tma_2d_mc(sb + G_ST + slot * 16384 + rank * 8192, tm, c0 + rank * 64, c1, full);
    u++; };
#pragma unroll 1
  for (int st = 0; st < 5; st++) load_w(rank ? tv : tk, pr * 128, st);
  if (args.layer == 0) { flag_wait(args.flags + F_X, 128); fence_proxy_async(); } else pdl_wait();
#pragma unroll 1
  for (int tile = 0; tile < 32; tile++) {
    l2_prefetch((const char*)g_xn + ((tile + 2) & 31) * 81920 + (pr * 2 + rank) * 1280, 1280);
#pragma unroll 1
    for (int st = 0; st < 5; st++) {
      push(tx, ((st + pr) % 5) * 128, tile * 64);
      if (tile >= PF0 && tile < PF0 + 16) l2_prefetch((rank ? args.wo : args.wq) + (pr * 80 + (tile - PF0) * 5 + st) * 2048, 2048);
    }
  }
  pdl_launch();
  if (pr < 16) {
    load_w(tq, (2 * pr + rank) * 128, 0);
#pragma unroll 1
    for (int tile = 0; tile < 32; tile++) {
      if (tile < 30) {
        l2_prefetch((const char*)g_xn + (tile + 2) * 81920 + (pr * 2 + rank) * 2560, 2560);
        const int q = (tile * 2 + 4) * 32 + 2 * pr + rank;
        l2_prefetch(g_kv + (size_t)q * 16384, 16384); l2_prefetch(g_kv + (size_t)(q + 32) * 16384, 16384);
        if (lds32(sb + S_BAR + B_PROG) > tile * 2 + 5) { l2_prefetch(g_kvm + (size_t)q * 4096, 4096); l2_prefetch(g_kvm + (size_t)(q + 32) * 4096, 4096); }
      }
#pragma unroll 1
      for (int st = 0; st < 5; st++) { push(tx, ((st + pr) % 5) * 128, tile * 64); if (tile == 0 && st < 4) load_w(tq, (2 * pr + rank) * 128, st + 1); }
    }
  } else {
    const int kq = (pr - 16) >> 2, cg = 2 * (pr & 3) + rank;
    mbar_wait(sb + S_BAR + B_WD, 0);
    mbar_arrive_tx(bWF, 163840);
#pragma unroll 1
    for (int i = 0; i < 20; i++) { tma_2d(sb + (i % 5) * 32768 + (i / 5) * 8192, to32, cg * 80 + (i % 5) * 16, kq * 1024 + (i / 5) * 256, bWF); __nanosleep(OPACE); }
#pragma unroll 1
    for (int tile = 0; tile < 32; tile++) {
      flag_wait(args.flags + F_O + tile * 4 + kq, 8);
      fence_proxy_async();
#pragma unroll 1
      for (int st = 0; st < 8; st++) push(tao, kq * 1024 + ((st + (pr & 3) * 2) & 7) * 128, tile * 64);
    }
  }
#pragma unroll 1
  for (int i = 0; i < 4; i++, u++) mbar_wait(sb + S_BAR + B_EMPTY + (u & 3) * 8, ((u >> 2) & 1) ^ 1);
}

DEVINL void gemm_publisher(int wg, int pr, int rank, const ArgsA& args) {
#pragma unroll 1
  for (int i = 0; i < 32; i++) {
    const int tile = (i & 15) * 2 + wg;
    bar_sync(BAR_G + wg, 160);
    if ((threadIdx.x & 31) == 0) {
      flag_add(args.flags + (i < 16 ? F_KV + pr * 32 + tile : pr < 16 ? F_O + tile * 4 + (pr >> 2) : F_P + tile * 32));
    }
    __syncwarp();
  }
}

DEVINL void filter_prep(uint32_t* sm, int part, const ArgsA& args) {
  const int tid = threadIdx.x, lane = tid & 31, w = tid >> 5;
  const unsigned short* wr = (const unsigned short*)args.wr; const unsigned short* wi = (const unsigned short*)args.wi;
#pragma unroll 1
  for (int it = part; it < 32; it += 4) {
#pragma unroll 1
    for (int rr = 0; rr < 8; rr += 2) {
      uint32_t a[2][11], b[2][11];
#pragma unroll
      for (int r = 0; r < 2; r++) {
        const int pos = it * 64 + w * 8 + rr + r, th = (pos >> 2) & 127, v = (pos >> 9) * 4 + (pos & 3);
        const int o = ((th >> 3) + 16 * ((th & 7) + (v & 8)) + 256 * (v & 7)) * 321 + lane;
#pragma unroll
        for (int c = 0; c < 11; c++) if (c < 10 || lane == 0) { a[r][c] = wr[o + c * 32]; b[r][c] = wi[o + c * 32]; }
      }
#pragma unroll
      for (int r = 0; r < 2; r++)
#pragma unroll
        for (int c = 0; c < 11; c++) if (c < 10 || lane == 0) sm[(c * 32 + lane) * 65 + w * 8 + rr + r] = a[r][c] | (b[r][c] << 16);
    }
    bar_sync(1, 256);
#pragma unroll 2
    for (int i = tid; i < 64 * 321; i += 256) g_wt[(i >> 6) * 2048 + it * 64 + (i & 63)] = sm[(i >> 6) * 65 + (i & 63)];
    bar_sync(1, 256);
  }
}

__global__ void __cluster_dims__(2, 1, 1) __launch_bounds__(384, 1)
layer_a_kernel(const __grid_constant__ CUtensorMap tq, const __grid_constant__ CUtensorMap tk, const __grid_constant__ CUtensorMap tv,
               const __grid_constant__ CUtensorMap to, const __grid_constant__ CUtensorMap to32, const __grid_constant__ CUtensorMap tx,
               const __grid_constant__ CUtensorMap tao, const __grid_constant__ ArgsA args) {
  extern __shared__ __align__(1024) char smraw[];
  const uint32_t sb = (smem_u32(smraw) + 1023) & ~1023u;
  uint32_t rank; asm volatile("mov.u32 %0, %%cluster_ctarank;" : "=r"(rank));
  rank = __reduce_max_sync(~0u, rank);
  const uint32_t px = __reduce_max_sync(~0u, mapa(sb, rank ^ 1) - sb);
  if (args.layer == 0) LOGK(0, 0);
  uint32_t smid; asm volatile("mov.u32 %0, %%smid;" : "=r"(smid));
  const uint32_t b = sb + S_BAR;
  if (threadIdx.x == 320) {
    mbar_init(b + B_W, 1); mbar_init(b + B_W2, 1); mbar_init(b + B_WV, 1); mbar_init(b + B_WO, 1); mbar_init(b + B_S, 9); mbar_init(b + B_KV, 1); mbar_init(b + B_KV + 8, 1);
    for (int i = 0; i < 4; i++) { mbar_init(b + B_FULL + i * 8, 1); mbar_init(b + B_EMPTY + i * 8, 2); }
    for (int i = 0; i < 5; i++) mbar_init(b + B_WF + i * 8, 1);
    mbar_init(b + B_WD, 2); mbar_init(b + B_RB, 1); sts32(b + B_PROG, 0);
    mbar_arrive_tx(b + B_RB, 8);
    asm volatile("fence.mbarrier_init.release.cluster;" ::: "memory");
  }
  __syncwarp();
  asm volatile("barrier.cluster.arrive.relaxed.aligned;" ::: "memory");
  uint32_t role = 0; uint4 xr[5];
  const bool ln = args.layer == 0 && blockIdx.x < 128 && threadIdx.x < 256;
  const size_t off = (size_t)(blockIdx.x * 16 + (threadIdx.x >> 4)) * 640 + (threadIdx.x & 15) * 8;
#pragma unroll
  for (int i = 0; i < 5; i++) xr[i] = ldg128_if(args.x + off + i * 128, ln);
  if (rank == 0 && threadIdx.x >= 256 && threadIdx.x < 320) {
    if (args.layer == 0) {
      uint32_t* p = (uint32_t*)(args.comm + 0x20000 + (threadIdx.x < 288 ? 0x1000 : 0) + (blockIdx.x >> 1) * 32);
      if ((threadIdx.x & 31) < 8) p[threadIdx.x & 31] = 0;
      __syncwarp();
      if ((threadIdx.x & 31) == 0) {
        uint32_t v, best = ~0u;
#pragma unroll 1
        for (int i = 0; i < NPROBE; i++) { const uint32_t t0 = clk(); asm volatile("atom.relaxed.gpu.global.add.u32 %0, [%1], 1;" : "=r"(v) : "l"(p) : "memory"); asm volatile("st.volatile.shared.u32 [%0], %1;" ::"r"(b + 216), "r"(v) : "memory"); best = min(best, clk() - t0); }
        sts32(b + 208 + ((threadIdx.x >> 5) & 1) * 4, best);
      }
      bar_sync(1, 64);
    }
    if (threadIdx.x == 256) {
      int d;
      if (args.layer == 0) { d = (int)(lds32(b + 208) - lds32(b + 212)); g_side[smid & 254] = d; g_side[(smid & 254) + 1] = d; } else d = g_side[smid & 255];
      uint32_t* cnt = args.flags + F_ROLE;
      if (d < 0) { role = atomicAdd(cnt, 1); if (role >= 32) role = 32 + atomicAdd(cnt + 1, 1); }
      else { role = 32 + atomicAdd(cnt + 1, 1); if (role >= 66) role = atomicAdd(cnt, 1); }
    }
    __syncwarp();
  }
  asm volatile("barrier.cluster.wait.aligned;" ::: "memory");
  if (rank == 0 && threadIdx.x == 256) { stasync64(b + B_ROLE, role, 0, b + B_RB); stasync64(b + B_ROLE + px, role, 0, b + B_RB + px); }
  if (ln) {
    float f[40];
#pragma unroll
    for (int i = 0; i < 5; i++) unpack8(xr[i], f + 8 * i);
    ln_row(f);
#pragma unroll
    for (int i = 0; i < 5; i++) *(uint4*)(g_xn + off + i * 128) = pack8(f + 8 * i);
    bar_sync(2, 256);
    if (threadIdx.x == 0) flag_add(args.flags + F_X);
  }
  __syncwarp();
  mbar_wait(b + B_RB, 0);
  role = __reduce_max_sync(~0u, lds32(b + B_ROLE));
  if (role != 32) pdl_launch();
  const int wg = __reduce_max_sync(~0u, threadIdx.x >> 7);
  auto U = [](uint32_t x) { return __reduce_max_sync(~0u, opaque(x)); };
  if (wg < 2) {
    asm volatile("setmaxnreg.inc.sync.aligned.u32 224;");
    if (role >= 32) {
      if (role >= 64) { if (args.layer == 0) { filter_prep((uint32_t*)smraw, (role - 64) * 2 + rank, args); if (threadIdx.x == 0) LOG(role * 2 + rank, 0); } }
      else gemm_consumer(U(sb), U(px), U(wg), U(role - 32), U(rank), args);
    } else { if (wg == 0) chain_mma<0>(sb, args); else chain_mma<1>(sb, args); }
  } else {
    asm volatile("setmaxnreg.dec.sync.aligned.u32 56;");
    if (role >= 32) {
      if (role < 64) {
        if (threadIdx.x == 256) gemm_producer(sb, role - 32, rank, args, &tq, &tk, &tv, &to32, &tx, &tao);
        else if (threadIdx.x >= 288 && threadIdx.x < 352) gemm_publisher((threadIdx.x >> 5) - 9, role - 32, rank, args);
        else if (threadIdx.x == 352 && role < 48) km_watcher(sb, args.flags + F_KM + (2 * (role - 32) + rank) * 32);
      }
    } else chain_helper(U(sb), U(px), U(role), U(rank), args, &tq, &tk, &tv, &to);
  }
}

DEVINL float2 cadd(float2 a, float2 b) { return make_float2(a.x + b.x, a.y + b.y); }
DEVINL float2 csub(float2 a, float2 b) { return make_float2(a.x - b.x, a.y - b.y); }
DEVINL float2 cmul(float2 a, float2 b) { return make_float2(fmaf(a.x, b.x, -a.y * b.y), fmaf(a.x, b.y, a.y * b.x)); }
DEVINL float2 cmulc(float2 a, float2 b) { return make_float2(fmaf(a.x, b.x, a.y * b.y), fmaf(a.y, b.x, -a.x * b.y)); }
template <int INV> DEVINL float2 ctw(float2 a, float2 w) { return INV ? cmulc(a, w) : cmul(a, w); }
template <int INV> DEVINL float2 rot(float2 a) { return INV ? make_float2(-a.y, a.x) : make_float2(a.y, -a.x); }
template <int INV> DEVINL void fft4(float2& a, float2& b, float2& c, float2& d) {
  const float2 s0 = cadd(a, c), d0 = csub(a, c), s1 = cadd(b, d), d1 = rot<INV>(csub(b, d));
  a = cadd(s0, s1); b = cadd(d0, d1); c = csub(s0, s1); d = csub(d0, d1);
}
template <int INV> DEVINL float2 w8(float2 a) { const float h = 0.70710678118654752f; const float2 r = rot<INV>(a); return make_float2((a.x + r.x) * h, (a.y + r.y) * h); }
template <int INV> DEVINL void fft8(float2* x) {
  fft4<INV>(x[0], x[2], x[4], x[6]); fft4<INV>(x[1], x[3], x[5], x[7]);
  const float2 e0 = x[0], e1 = x[2], e2 = x[4], e3 = x[6], o0 = x[1], o1 = w8<INV>(x[3]), o2 = rot<INV>(x[5]), o3 = rot<INV>(w8<INV>(x[7]));
  x[0] = cadd(e0, o0); x[1] = cadd(e1, o1); x[2] = cadd(e2, o2); x[3] = cadd(e3, o3);
  x[4] = csub(e0, o0); x[5] = csub(e1, o1); x[6] = csub(e2, o2); x[7] = csub(e3, o3);
}
template <int INV> DEVINL void fft16(float2* x) {
  const float c = 0.92387953251128674f, s = 0.38268343236508977f;
  const float2 w1 = make_float2(c, -s), w3 = make_float2(s, -c);
#pragma unroll
  for (int i = 0; i < 4; i++) fft4<INV>(x[i], x[i + 4], x[i + 8], x[i + 12]);
  x[5] = ctw<INV>(x[5], w1); x[9] = w8<INV>(x[9]); x[13] = ctw<INV>(x[13], w3);
  x[6] = w8<INV>(x[6]); x[10] = rot<INV>(x[10]); x[14] = rot<INV>(w8<INV>(x[14]));
  x[7] = ctw<INV>(x[7], w3); x[11] = rot<INV>(w8<INV>(x[11])); x[15] = ctw<INV>(x[15], make_float2(-c, s));
#pragma unroll
  for (int k = 0; k < 4; k++) fft4<INV>(x[4 * k], x[4 * k + 1], x[4 * k + 2], x[4 * k + 3]);
#pragma unroll
  for (int k = 0; k < 4; k++)
#pragma unroll
    for (int m = k + 1; m < 4; m++) { const float2 t = x[4 * k + m]; x[4 * k + m] = x[4 * m + k]; x[4 * m + k] = t; }
}
template <int INV> DEVINL void fft5(float2& x0, float2& x1, float2& x2, float2& x3, float2& x4) {
  const float c1 = 0.30901699437494742f, c2 = -0.80901699437494742f, s1 = 0.95105651629515357f, s2 = 0.58778525229247313f;
  const float2 a1 = cadd(x1, x4), a2 = cadd(x2, x3), b1 = rot<INV>(csub(x1, x4)), b2 = rot<INV>(csub(x2, x3));
  const float2 p1 = make_float2(fmaf(c1, a1.x, fmaf(c2, a2.x, x0.x)), fmaf(c1, a1.y, fmaf(c2, a2.y, x0.y)));
  const float2 p2 = make_float2(fmaf(c2, a1.x, fmaf(c1, a2.x, x0.x)), fmaf(c2, a1.y, fmaf(c1, a2.y, x0.y)));
  const float2 q1 = make_float2(fmaf(s1, b1.x, s2 * b2.x), fmaf(s1, b1.y, s2 * b2.y));
  const float2 q2 = make_float2(fmaf(s2, b1.x, -s1 * b2.x), fmaf(s2, b1.y, -s1 * b2.y));
  x0 = cadd(x0, cadd(a1, a2)); x1 = cadd(p1, q1); x4 = csub(p1, q1); x2 = cadd(p2, q2); x3 = csub(p2, q2);
}
template <int INV> DEVINL void fft20(const float2* in, float2* out) {
  float2 t[4][5];
#pragma unroll
  for (int a = 0; a < 4; a++) {
#pragma unroll
    for (int b = 0; b < 5; b++) t[a][b] = in[(5 * a + 4 * b) % 20];
    fft5<INV>(t[a][0], t[a][1], t[a][2], t[a][3], t[a][4]);
  }
#pragma unroll
  for (int d = 0; d < 5; d++) {
    fft4<INV>(t[0][d], t[1][d], t[2][d], t[3][d]);
#pragma unroll
    for (int c = 0; c < 4; c++) out[(5 * c + 16 * d) % 20] = t[c][d];
  }
}
constexpr int ZP = 336;
struct RowSmem { float2 T[320 * 17]; uint32_t Z[16 * ZP]; float2 tw[320]; float2 tp[160]; };
DEVINL float2 cis(int k, int n) {
  float sn, cs; __sincosf((float)(2 * k > n ? k - n : k) * (-6.283185307179586f / (float)n), &sn, &cs); return make_float2(cs, sn);
}
DEVINL void row_tables(RowSmem& sm) {
  const int t = threadIdx.x;
  sm.tw[t] = cis((t >> 4) * (t & 15), 320);
  if (t < 160) sm.tp[t] = cis(t, 640);
}

#define CUNR 1
#define CDRY 0
#define RDRY 1

__global__ void __launch_bounds__(320, 1) rows_fwd_kernel(const bf16* __restrict__ xin, const uint32_t* flags) {
  extern __shared__ __align__(1024) char smraw[]; RowSmem& sm = *(RowSmem*)smraw;
  const int tid = threadIdx.x, s0 = blockIdx.x * 16, wp = __reduce_max_sync(~0u, tid >> 5);
  const uint32_t* flag = flags + F_P + (blockIdx.x >> 2) * 32;
  LOGK(1 + 3 * (xin == g_x), 0);
  if (tid == 0) l2_prefetch(xin + s0 * 640, 20480);
  row_tables(sm);
#pragma unroll 1
  for (int live = !RDRY || wp != 1 || __any_sync(~0u, ldg_rlx32(flag) >= 32); live < 2; live++) {
    if (live) {
      if (wp == 0) { uint32_t v; int n = 0;
        while (true) { asm volatile("ld.acquire.gpu.global.u32 %0, [%1];" : "=r"(v) : "l"(flag) : "memory"); if (__all_sync(~0u, v >= 32 || ++n >= 8 * POLL_LIMIT)) break; __nanosleep(v ? 20 : 200); } }
      __syncthreads();
      pdl_launch();
      LOGK(1 + 3 * (xin == g_x), 1);
    }
    if (wp < 8) {
      const int row = tid >> 4, j = tid & 15; const size_t off = (size_t)(s0 + row) * 640 + j * 8;
      float f[40]; uint4 in[5][5];
#pragma unroll
      for (int i = 0; i < 5; i++) {
#pragma unroll
        for (int q = 0; q < 4; q++) in[i][q] = ldg128_if(g_part + q * 2048 * 640 + off + i * 128, live);
        in[i][4] = ldg128_if(xin + off + i * 128, live);
      }
#pragma unroll
      for (int i = 0; i < 5; i++) {
        float a[8], b[8], c[8], d[8];
        unpack8(in[i][0], a); unpack8(in[i][1], b); unpack8(in[i][2], c); unpack8(in[i][3], d);
#pragma unroll
        for (int e = 0; e < 8; e++) a[e] = (a[e] + b[e]) + (c[e] + d[e]);
        const uint4 o = pack8(a), x = in[i][4];
        const uint4 r = make_uint4(hadd2bf(o.x, x.x), hadd2bf(o.y, x.y), hadd2bf(o.z, x.z), hadd2bf(o.w, x.w));
        stg128_if(g_x + off + i * 128, r, live); unpack8(r, f + 8 * i);
      }
      ln_row(f);
#pragma unroll
      for (int i = 0; i < 5; i++) *(uint4*)(sm.Z + row * ZP + i * 64 + j * 4) = pack8(f + 8 * i);
      __syncwarp();
      float2 z[20], y[20];
#pragma unroll
      for (int n1 = 0; n1 < 20; n1++) { const uint32_t w = sm.Z[row * ZP + n1 * 16 + j]; z[n1] = make_float2(bf_lo(w), bf_hi(w)); }
      fft20<0>(z, y);
#pragma unroll
      for (int k1 = 0; k1 < 20; k1++) sm.T[(k1 * 16 + j) * 17 + row] = k1 ? cmul(y[k1], sm.tw[k1 * 16 + j]) : y[0];
    }
    if (live) __syncthreads();
    const int up = (tid >> 4) & 1, row = tid & 15, k1 = wp ? (up ? 20 - wp : wp) : up * 10;
    float2 x[16];
#pragma unroll
    for (int n2 = 0; n2 < 16; n2++) x[n2] = sm.T[(k1 * 16 + n2) * 17 + row];
    fft16<0>(x);
    uint32_t* ya = g_y + s0 + row + k1 * 2048; uint32_t* yb = g_y + s0 + row + (320 - k1) * 2048;
    stg32_if(g_y + s0 + row + 160 * 2048, pack_f16(2.f * x[8].x, -2.f * x[8].y), live && k1 == 0);
    const int src = (tid & 31) ^ (wp ? 16 : 0);
#pragma unroll
    for (int k2 = 0; k2 < 8; k2++) {
      const float2 c = k1 ? x[15 - k2] : x[(16 - k2) & 15], b = make_float2(__shfl_sync(~0u, c.x, src), __shfl_sync(~0u, c.y, src)), a = x[k2];
      const float2 E = make_float2(a.x + b.x, a.y - b.y), O = cmul(make_float2(a.y + b.y, b.x - a.x), sm.tp[k1 + 20 * k2]);
      stg32_if(ya + k2 * 20 * 2048, pack_f16(E.x + O.x, E.y + O.y), live); stg32_if(yb - k2 * 20 * 2048, pack_f16(E.x - O.x, O.y - E.y), live);
    }
  }
  LOGK(1 + 3 * (xin == g_x), 2);
  if (blockIdx.x == gridDim.x - 1) pdl_wait();
}

__global__ void __launch_bounds__(384) cols_kernel(int layer) {
  extern __shared__ __align__(1024) char smraw[];
  const int sub = threadIdx.x >> 7, tid = threadIdx.x & 127, col = blockIdx.x * 3 + sub, k1 = tid >> 3, j0 = tid & 7;
  float2* sm = (float2*)smraw + sub * (16 * 152);
  float2* tw = (float2*)smraw + 3 * 16 * 152;
  LOGK(2 + 3 * layer, 0);
  pdl_launch();
  uint32_t* y = g_y + col * 2048 + tid;
  if (tid < 2) l2_prefetch((tid ? g_wt : g_y) + col * 2048, 8192);
#pragma unroll 1
  for (int i = threadIdx.x; i < 2176; i += 384) {
    const int a = i < 2048 ? i >> 7 : (i - 2048) >> 3, b = i < 2048 ? i & 127 : i & 7;
    tw[i < 2048 ? a * 136 + b : 2176 + a * 9 + b] = cis(i < 2048 ? a * b : a * b * 16, 2048);
  }
  float2* reg = sm + k1 * 152;
  uint4 wf[4];
#pragma unroll
  for (int q = 0; q < 4; q++) {
    const int live = q >= 0, it = live ? q : q == -3 ? 0 : q == -2 ? 1 : 3;
    float2 x[16];
    if (it == 0) {
      if (live) { __syncthreads(); pdl_wait(); LOGK(2 + 3 * layer, 1); }
#pragma unroll
      for (int i = 0; i < 16; i++) { const uint32_t w = ldg32_if(y + i * 128, live); x[i] = __half22float2(*(const __half2*)&w); }
#pragma unroll
      for (int i = 0; i < 4; i++) wf[i] = ldg128_if(g_wt + col * 2048 + i * 512 + tid * 4, live);
    } else {
      const float2* in = it == 3 ? sm + tid : reg + j0; const int is = it == 1 ? 8 : it == 2 ? 9 : 152;
#pragma unroll
      for (int i = 0; i < 16; i++) x[i] = in[i * is];
    }
    fft16<0>(x);
    if (it == 3) {
      const float sc = 1.f / 4096.f;
#pragma unroll
      for (int i = 0; i < 16; i++) stg32_if(y + i * 128, pack_bf16(x[i].y * sc, x[i].x * sc), live);
    } else {
      const float2* t = it == 0 ? tw + tid : it == 1 ? tw + 2176 + j0 : tw + k1 * 136 + j0; const int ts = it == 0 ? 136 : it == 1 ? 9 : 8;
      float2* o = it == 0 ? sm + tid : reg + j0; const int os = it == 0 ? 152 : it == 1 ? 9 : 8;
      __syncwarp();
#pragma unroll
      for (int k = 0; k < 16; k++) o[k * os] = (CUNR && k == 0 && it < 2) ? x[0] : cmul(x[k], t[k * ts]);
      if (it == 1) {
        __syncwarp();
        float2* r9 = reg + j0 * 9;
#pragma unroll
        for (int i = 0; i < 16; i++) x[i] = r9[(i & 8) * 9 + (i & 7)];
#pragma unroll
        for (int h = 0; h < 2; h++) {
          fft8<0>(x); fft8<0>(x + 8);
          if (h == 0) {
#pragma unroll
            for (int i = 0; i < 16; i++) {
              const uint32_t w = (i & 3) == 0 ? wf[i >> 2].x : (i & 3) == 1 ? wf[i >> 2].y : (i & 3) == 2 ? wf[i >> 2].z : wf[i >> 2].w;
              const float2 v = cmul(x[i], make_float2(bf_lo(w), bf_hi(w))); x[i] = make_float2(v.y, v.x);
            }
          }
        }
        const float2* t9 = tw + 2176 + j0 * 9;
#pragma unroll
        for (int i = 0; i < 16; i++) r9[(i & 8) * 9 + (i & 7)] = (i & 7) ? cmul(x[i], t9[(i & 8) * 9 + (i & 7)]) : x[i];
        __syncwarp();
      } else if (live) bar_sync(sub + 1, 128);
    }
  }
  LOGK(2 + 3 * layer, 2);
}

__global__ void __launch_bounds__(320) rows_inv_kernel(bf16* __restrict__ xout, int do_ln) {
  extern __shared__ __align__(1024) char smraw[]; RowSmem& sm = *(RowSmem*)smraw;
  const int tid = threadIdx.x, s0 = blockIdx.x * 16, wp = __reduce_max_sync(~0u, tid >> 5);
  LOGK(3 + 3 * !do_ln, 0);
  if (tid == 0) l2_prefetch(g_x + s0 * 640, 20480);
  row_tables(sm);
  const size_t off = (size_t)(s0 + ((tid >> 4) & 15)) * 640 + (tid & 15) * 8;
#pragma unroll 1
  for (int live = !RDRY || wp != 1; live < 2; live++) {
    if (live) {
      __syncthreads();
      pdl_wait();
      pdl_launch();
      LOGK(3 + 3 * !do_ln, 1);
    }
    uint4 xr[5];
    {
      const int up = (tid >> 4) & 1, row = tid & 15, k1 = wp ? (up ? 20 - wp : wp) : up * 10;
      const uint32_t* ya = g_y + s0 + row + k1 * 2048; const uint32_t* yb = g_y + s0 + row + (320 - k1) * 2048;
      uint32_t wa[8], wb[8];
#pragma unroll
      for (int k2 = 0; k2 < 8; k2++) { wa[k2] = ldg32_if(ya + k2 * 20 * 2048, live); wb[k2] = ldg32_if(yb - k2 * 20 * 2048, live); }
      const uint32_t wm = ldg32_if(g_y + s0 + row + 160 * 2048, live && k1 == 0);
#pragma unroll
      for (int i = 0; i < 5; i++) xr[i] = ldg128_if(g_x + off + i * 128, live && wp < 8);
      stg32_if(g_flags + blockIdx.x * 320 + tid, 0, live && !do_ln && blockIdx.x * 320 + tid < 2 * F_LAYER);
      if (k1 == 0) { wa[0] &= 0xffffu; wb[0] &= 0xffffu; }
      float2 x[16], r[8];
#pragma unroll
      for (int k2 = 0; k2 < 8; k2++) {
        const float2 a = make_float2(bf_lo(wa[k2]), bf_hi(wa[k2])), b = make_float2(bf_lo(wb[k2]), bf_hi(wb[k2]));
        const float2 E = make_float2(a.x + b.x, a.y - b.y), O = cmulc(make_float2(a.x - b.x, a.y + b.y), sm.tp[k1 + 20 * k2]);
        x[k2] = make_float2(E.x - O.y, E.y + O.x); r[k2] = make_float2(E.x + O.y, O.x - E.y);
      }
      if (k1 == 0) r[0] = make_float2(2.f * bf_lo(wm), -2.f * bf_hi(wm));
      const int src = (tid & 31) ^ (wp ? 16 : 0);
#pragma unroll
      for (int i = 8; i < 16; i++) { const float2 c = k1 ? r[15 - i] : r[(16 - i) & 7]; x[i] = make_float2(__shfl_sync(~0u, c.x, src), __shfl_sync(~0u, c.y, src)); }
      fft16<1>(x);
#pragma unroll
      for (int n2 = 0; n2 < 16; n2++) sm.T[(k1 * 16 + n2) * 17 + row] = x[n2];
    }
    if (live) __syncthreads();
    if (wp < 8) {
      const int row = tid >> 4, n2 = tid & 15;
      float2 z[20], y[20];
#pragma unroll
      for (int k1 = 0; k1 < 20; k1++) { const float2 t = sm.T[(k1 * 16 + n2) * 17 + row]; z[k1] = k1 ? cmulc(t, sm.tw[k1 * 16 + n2]) : t; }
      fft20<1>(z, y);
      const float sc = 1.f / 640.f;
#pragma unroll
      for (int n1 = 0; n1 < 20; n1++) sm.Z[row * ZP + n1 * 16 + n2] = pack_bf16(y[n1].x * sc, y[n1].y * sc);
      __syncwarp();
      float f[40];
#pragma unroll
      for (int i = 0; i < 5; i++) {
        const uint4 o = *(const uint4*)(sm.Z + row * ZP + i * 64 + n2 * 4), x = xr[i];
        const uint4 r = make_uint4(hadd2bf(o.x, x.x), hadd2bf(o.y, x.y), hadd2bf(o.z, x.z), hadd2bf(o.w, x.w));
        stg128_if(xout + off + i * 128, r, live); unpack8(r, f + 8 * i);
      }
      if (do_ln) {
        ln_row(f);
#pragma unroll
        for (int i = 0; i < 5; i++) stg128_if(g_xn + off + i * 128, pack8(f + 8 * i), live);
      }
    }
  }
  LOGK(3 + 3 * !do_ln, 2);
}

typedef CUresult (*EncFn)(CUtensorMap*, CUtensorMapDataType, cuuint32_t, void*, const cuuint64_t*, const cuuint64_t*, const cuuint32_t*, const cuuint32_t*,
                          CUtensorMapInterleave, CUtensorMapSwizzle, CUtensorMapL2promotion, CUtensorMapFloatOOBfill);
static void make_map(EncFn fn, CUtensorMap* m, const void* p, uint64_t cols, uint64_t rows, uint32_t bc, uint32_t br, CUtensorMapSwizzle sw) {
  cuuint64_t gd[2] = {cols, rows}, gs[1] = {cols * 2}; cuuint32_t bd[2] = {bc, br}, es[2] = {1, 1};
  fn(m, CU_TENSOR_MAP_DATA_TYPE_BFLOAT16, 2, (void*)p, gd, gs, bd, es, CU_TENSOR_MAP_INTERLEAVE_NONE, sw, CU_TENSOR_MAP_L2_PROMOTION_L2_128B, CU_TENSOR_MAP_FLOAT_OOB_FILL_NONE);
}
template <class... P, class... A>
static void launch(void (*k)(P...), int grid, int block, int smem, bool pdl, A... a) {
  cudaLaunchConfig_t cfg = {}; cfg.gridDim = dim3(grid); cfg.blockDim = dim3(block); cfg.dynamicSmemBytes = smem; cfg.stream = cudaStreamPerThread;
  cudaLaunchAttribute at[1]; at[0].id = cudaLaunchAttributeProgrammaticStreamSerialization; at[0].val.programmaticStreamSerializationAllowed = 1;
  cfg.attrs = at; cfg.numAttrs = pdl ? 1 : 0;
  cudaLaunchKernelEx(&cfg, k, a...);
}
static const int tune_t[10] = {1505, 1635, 1830, 2060, 2200, 2385, 2610, 2790, 1950, 3045}; constexpr int dev_stop = 100, dev_pdl = 1;

extern "C" void kernel_launch(void* const* d_in, const int* in_sizes, int n_in, void* d_out, int out_size) {
  const bf16 *x = (const bf16*)d_in[0], *mem0 = (const bf16*)d_in[1], *Wq = (const bf16*)d_in[2], *Wk = (const bf16*)d_in[3], *Wv = (const bf16*)d_in[4], *Wo = (const bf16*)d_in[5];
  const bf16 *wr = (const bf16*)d_in[8], *wi = (const bf16*)d_in[9];
  constexpr int SM_A = S_END + 1024, SM_R = sizeof(RowSmem), SM_C = 76 * 1024, SM_I = 116 * 1024;
  void *p_xn, *p_o, *p_x, *p_comm, *p_flags, *fn; cudaDriverEntryPointQueryResult qr;
  cudaGetSymbolAddress(&p_xn, g_xn); cudaGetSymbolAddress(&p_o, g_o); cudaGetSymbolAddress(&p_x, g_x); cudaGetSymbolAddress(&p_comm, g_comm); cudaGetSymbolAddress(&p_flags, g_flags);
  cudaGetDriverEntryPoint("cuTensorMapEncodeTiled", &fn, cudaEnableDefault, &qr);
  cudaFuncSetAttribute(layer_a_kernel, cudaFuncAttributeMaxDynamicSharedMemorySize, SM_A);
  cudaFuncSetAttribute(rows_fwd_kernel, cudaFuncAttributeMaxDynamicSharedMemorySize, SM_R);
  cudaFuncSetAttribute(rows_inv_kernel, cudaFuncAttributeMaxDynamicSharedMemorySize, SM_I);
  cudaFuncSetAttribute(cols_kernel, cudaFuncAttributeMaxDynamicSharedMemorySize, SM_C);
  cudaFuncSetAttribute(rows_fwd_kernel, cudaFuncAttributePreferredSharedMemoryCarveout, 100);
  cudaFuncSetAttribute(cols_kernel, cudaFuncAttributePreferredSharedMemoryCarveout, 100);
  cudaFuncSetAttribute(rows_inv_kernel, cudaFuncAttributePreferredSharedMemoryCarveout, 100);
  CUtensorMap tq, tk, tv, to, to32, tx, tao; EncFn enc = (EncFn)fn;
  make_map(enc, &tq, Wq, 4096, 640, 64, 64, CU_TENSOR_MAP_SWIZZLE_128B); make_map(enc, &tk, Wk, 4096, 640, 64, 64, CU_TENSOR_MAP_SWIZZLE_128B);
  make_map(enc, &tv, Wv, 4096, 640, 64, 64, CU_TENSOR_MAP_SWIZZLE_128B); make_map(enc, &to, Wo, 640, 4096, 64, 64, CU_TENSOR_MAP_SWIZZLE_128B);
  make_map(enc, &to32, Wo, 640, 4096, 16, 256, CU_TENSOR_MAP_SWIZZLE_32B);
  make_map(enc, &tx, p_xn, 640, 2048, 64, 64, CU_TENSOR_MAP_SWIZZLE_128B); make_map(enc, &tao, p_o, 4096, 2048, 64, 64, CU_TENSOR_MAP_SWIZZLE_128B);
  char* comm = (char*)(((uintptr_t)p_comm + (2 << 20) - 1) & ~(uintptr_t)((2 << 20) - 1));
  const bool pdl = dev_pdl;
#define L0PDL 0
  for (int l = 0; l < 2; l++) {
    ArgsA a{x, mem0, comm, (uint32_t*)p_flags + l * F_LAYER, wr, wi, (const char*)Wq, (const char*)Wo, l, {tune_t[0], tune_t[1], tune_t[2], tune_t[3]}, {tune_t[4], tune_t[5], tune_t[6], tune_t[7]}, {tune_t[8], tune_t[9]}};
    if (dev_stop > 4 * l + 0) launch(layer_a_kernel, 132, 384, SM_A, pdl && (l || L0PDL), tq, tk, tv, to, to32, tx, tao, a);
    if (dev_stop > 4 * l + 1) launch(rows_fwd_kernel, 128, 320, SM_R, pdl, l ? (const bf16*)p_x : x, (const uint32_t*)a.flags);
    if (dev_stop > 4 * l + 2) launch(cols_kernel, 107, 384, SM_C, pdl, l);
    if (dev_stop > 4 * l + 3) launch(rows_inv_kernel, 128, 320, SM_I, pdl, l ? (bf16*)d_out : (bf16*)p_x, l == 0);
  }
}
```

```cpp
#include <cuda_runtime.h>
#include <cuda_bf16.h>
#include <cuda_fp16.h>
#include <cuda.h>
#include <stdint.h>

typedef __nv_bfloat16 bf16;
#define DEVINL __device__ __forceinline__

__device__ __align__(1024) bf16 g_xn[2048 * 640];
__device__ __align__(1024) bf16 g_x[2048 * 640];
__device__ __align__(1024) char g_kv[64 * 32 * 16384];
__device__ __align__(1024) char g_kvm[64 * 32 * 4096];
__device__ __align__(1024) bf16 g_o[2048 * 4096];
__device__ __align__(1024) bf16 g_part[4 * 2048 * 640];
__device__ __align__(1024) uint32_t g_y[321 * 2048];
__device__ __align__(1024) uint32_t g_wt[321 * 2048];
__device__ __align__(4096) char g_comm[4 << 20];
constexpr int F_KV = 0, F_KM = 1024, F_O = F_KM + 1024, F_P = F_O + 128, F_ROLE = F_P + 32 * 32, F_X = F_ROLE + 64, F_LAYER = F_X + 32;
__device__ __align__(1024) uint32_t g_flags[2 * F_LAYER];
__device__ int g_side[256];
__device__ uint32_t g_role[256];

template <int V> struct IC { static constexpr int value = V; };
template <int B, int E, class F> DEVINL void static_for(F&& f) { if constexpr (B < E) { f(IC<B>{}); static_for<B + 1, E>(f); } }

#define POLL_LIMIT (1 << 17)
DEVINL uint32_t smem_u32(const void* p) { return (uint32_t)__cvta_generic_to_shared(p); }
DEVINL uint32_t mapa(uint32_t a, uint32_t r) { uint32_t o; asm volatile("mapa.shared::cluster.u32 %0, %1, %2;" : "=r"(o) : "r"(a), "r"(r)); return o; }
DEVINL uint32_t clk() { uint32_t v; asm volatile("{.reg .b64 w; mov.u64 w, %%clock64; cvt.u32.u64 %0, w;}" : "=r"(v)::"memory"); return v; }
DEVINL void mbar_init(uint32_t bar, uint32_t cnt) { asm volatile("mbarrier.init.shared::cta.b64 [%0], %1;" ::"r"(bar), "r"(cnt) : "memory"); }
DEVINL void mbar_arrive(uint32_t bar) { asm volatile("mbarrier.arrive.shared::cta.b64 _, [%0];" ::"r"(bar) : "memory"); }
DEVINL void mbar_arrive_remote(uint32_t bar) { asm volatile("mbarrier.arrive.shared::cluster.b64 _, [%0];" ::"r"(bar) : "memory"); }
DEVINL void mbar_arrive_tx(uint32_t bar, uint32_t tx) { asm volatile("mbarrier.arrive.expect_tx.shared::cta.b64 _, [%0], %1;" ::"r"(bar), "r"(tx) : "memory"); }
DEVINL void mbar_wait(uint32_t bar, uint32_t ph) {
  asm volatile("{.reg .pred p; .reg .b32 c,q; shl.b32 c, %1, 20;\n"
               "W0: bfe.u32 q, c, 20, 1; mbarrier.try_wait.parity.shared::cta.b64 p, [%0], q; add.u32 c,c,1; @!p bra.uni W0;}" ::"r"(bar), "r"(ph) : "memory");
}
DEVINL void bar_sync(int id, int n) { asm volatile("bar.sync %0, %1;" ::"r"(id), "r"(n) : "memory"); }
DEVINL void bar_arrive(int id, int n) { asm volatile("bar.arrive %0, %1;" ::"r"(id), "r"(n) : "memory"); }
DEVINL void cluster_sync() { asm volatile("barrier.cluster.arrive.release.aligned; barrier.cluster.wait.acquire.aligned;" ::: "memory"); }
DEVINL void tma_2d(uint32_t dst, const CUtensorMap* tm, int c0, int c1, uint32_t bar) {
  asm volatile("cp.async.bulk.tensor.2d.shared::cluster.global.mbarrier::complete_tx::bytes [%0], [%1, {%2, %3}], [%4];" ::"r"(dst), "l"(tm), "r"(c0), "r"(c1), "r"(bar) : "memory");
}
DEVINL void tma_2d_mc(uint32_t dst, const CUtensorMap* tm, int c0, int c1, uint32_t bar) {
  asm volatile("cp.async.bulk.tensor.2d.shared::cluster.global.mbarrier::complete_tx::bytes.multicast::cluster [%0], [%1, {%2, %3}], [%4], %5;" ::"r"(dst), "l"(tm), "r"(c0), "r"(c1), "r"(bar), "h"((uint16_t)3) : "memory");
}
DEVINL void bulk_g2s(uint32_t dst, const void* src, uint32_t bytes, uint32_t bar) {
  asm volatile("cp.async.bulk.shared::cluster.global.mbarrier::complete_tx::bytes [%0], [%1], %2, [%3];" ::"r"(dst), "l"(src), "r"(bytes), "r"(bar) : "memory");
}
DEVINL void l2_prefetch(const void* p, uint32_t bytes) { asm volatile("cp.async.bulk.prefetch.L2.global [%0], %1;" ::"l"(p), "r"(bytes) : "memory"); }
DEVINL void fence_proxy_async() { asm volatile("fence.proxy.async.global;" ::: "memory"); }
DEVINL void ldsm4t(uint32_t* r, uint32_t a) { asm volatile("ldmatrix.sync.aligned.m8n8.x4.trans.shared.b16 {%0,%1,%2,%3}, [%4];" : "=r"(r[0]), "=r"(r[1]), "=r"(r[2]), "=r"(r[3]) : "r"(a) : "memory"); }
DEVINL void stsm4(uint32_t a, uint32_t r0, uint32_t r1, uint32_t r2, uint32_t r3) { asm volatile("stmatrix.sync.aligned.m8n8.x4.shared.b16 [%0], {%1,%2,%3,%4};" ::"r"(a), "r"(r0), "r"(r1), "r"(r2), "r"(r3) : "memory"); }
DEVINL void mma16816(float* d, const uint32_t* a, uint32_t b0, uint32_t b1) {
  asm volatile("mma.sync.aligned.m16n8k16.row.col.f32.bf16.bf16.f32 {%0,%1,%2,%3}, {%4,%5,%6,%7}, {%8,%9}, {%0,%1,%2,%3};"
               : "+f"(d[0]), "+f"(d[1]), "+f"(d[2]), "+f"(d[3]) : "r"(a[0]), "r"(a[1]), "r"(a[2]), "r"(a[3]), "r"(b0), "r"(b1));
}
DEVINL void mma16816z(float* d, const uint32_t* a, uint32_t b0, uint32_t b1) {
  asm volatile("mma.sync.aligned.m16n8k16.row.col.f32.bf16.bf16.f32 {%0,%1,%2,%3}, {%4,%5,%6,%7}, {%8,%9}, {%10,%10,%10,%10};"
               : "=f"(d[0]), "=f"(d[1]), "=f"(d[2]), "=f"(d[3]) : "r"(a[0]), "r"(a[1]), "r"(a[2]), "r"(a[3]), "r"(b0), "r"(b1), "f"(0.f));
}
DEVINL void mma1688z(float* d, uint32_t a0, uint32_t a1, uint32_t b0) {
  asm volatile("mma.sync.aligned.m16n8k8.row.col.f32.bf16.bf16.f32 {%0,%1,%2,%3}, {%4,%5}, {%6}, {%7,%7,%7,%7};"
               : "=f"(d[0]), "=f"(d[1]), "=f"(d[2]), "=f"(d[3]) : "r"(a0), "r"(a1), "r"(b0), "f"(0.f));
}
DEVINL uint32_t movm(uint32_t a) { uint32_t r; asm volatile("movmatrix.sync.aligned.m8n8.trans.b16 %0, %1;" : "=r"(r) : "r"(a)); return r; }
DEVINL uint32_t pack_bf16(float lo, float hi) { uint32_t r; asm("cvt.rn.bf16x2.f32 %0, %1, %2;" : "=r"(r) : "f"(hi), "f"(lo)); return r; }
DEVINL uint32_t pack_f16(float lo, float hi) { uint32_t r; asm("cvt.rn.f16x2.f32 %0, %1, %2;" : "=r"(r) : "f"(hi), "f"(lo)); return r; }
DEVINL float bf_lo(uint32_t w) { return __uint_as_float(w << 16); }
DEVINL float bf_hi(uint32_t w) { return __uint_as_float(w & 0xffff0000u); }
DEVINL uint32_t hadd2bf(uint32_t a, uint32_t b) { uint32_t r; asm("add.rn.bf16x2 %0, %1, %2;" : "=r"(r) : "r"(a), "r"(b)); return r; }
DEVINL uint32_t hmax2bf(uint32_t a, uint32_t b) { uint32_t r; asm("max.bf16x2 %0, %1, %2;" : "=r"(r) : "r"(a), "r"(b)); return r; }
DEVINL uint32_t lds32(uint32_t a) { uint32_t v; asm volatile("ld.shared.u32 %0, [%1];" : "=r"(v) : "r"(a) : "memory"); return v; }
DEVINL uint2 lds64(uint32_t a) { uint2 v; asm volatile("ld.shared.v2.u32 {%0,%1}, [%2];" : "=r"(v.x), "=r"(v.y) : "r"(a) : "memory"); return v; }
DEVINL uint4 lds128(uint32_t a) { uint4 v; asm volatile("ld.shared.v4.u32 {%0,%1,%2,%3}, [%4];" : "=r"(v.x), "=r"(v.y), "=r"(v.z), "=r"(v.w) : "r"(a) : "memory"); return v; }
DEVINL void sts32(uint32_t a, uint32_t v) { asm volatile("st.shared.u32 [%0], %1;" ::"r"(a), "r"(v) : "memory"); }
DEVINL void sts64(uint32_t a, uint32_t x, uint32_t y) { asm volatile("st.shared.v2.u32 [%0], {%1,%2};" ::"r"(a), "r"(x), "r"(y) : "memory"); }
DEVINL void sts128(uint32_t a, uint4 v) { asm volatile("st.shared.v4.u32 [%0], {%1,%2,%3,%4};" ::"r"(a), "r"(v.x), "r"(v.y), "r"(v.z), "r"(v.w) : "memory"); }
DEVINL void stasync64(uint32_t a, uint32_t x, uint32_t y, uint32_t bar) { asm volatile("st.async.weak.shared::cluster.mbarrier::complete_tx::bytes.v2.b32 [%0], {%1,%2}, [%3];" ::"r"(a), "r"(x), "r"(y), "r"(bar) : "memory"); }
DEVINL uint4 ldg_rlx128(const void* p) { uint4 v; asm volatile("{.reg .b64 a,b; ld.relaxed.gpu.global.v2.b64 {a,b}, [%4]; mov.b64 {%0,%1}, a; mov.b64 {%2,%3}, b;}" : "=r"(v.x), "=r"(v.y), "=r"(v.z), "=r"(v.w) : "l"(p) : "memory"); return v; }
DEVINL uint2 ldg_rlx64(const void* p) { uint2 v; asm volatile("ld.relaxed.gpu.global.v2.u32 {%0,%1}, [%2];" : "=r"(v.x), "=r"(v.y) : "l"(p) : "memory"); return v; }
DEVINL void stg_rlx64(void* p, uint32_t x, uint32_t y) { asm volatile("{.reg .b64 a; mov.b64 a, {%1,%2}; st.relaxed.gpu.global.b64 [%0], a;}" ::"l"(p), "r"(x), "r"(y) : "memory"); }
DEVINL void stg_rlx128(void* p, uint32_t x, uint32_t y, uint32_t z, uint32_t w) { asm volatile("{.reg .b64 a,b; mov.b64 a, {%1,%2}; mov.b64 b, {%3,%4}; st.relaxed.gpu.global.v2.b64 [%0], {a,b};}" ::"l"(p), "r"(x), "r"(y), "r"(z), "r"(w) : "memory"); }
DEVINL void stg_rlx32(void* p, uint32_t x) { asm volatile("st.relaxed.gpu.global.u32 [%0], %1;" ::"l"(p), "r"(x) : "memory"); }
DEVINL uint4 ldg_cg128(const void* p) { uint4 v; asm volatile("ld.global.cg.v4.u32 {%0,%1,%2,%3}, [%4];" : "=r"(v.x), "=r"(v.y), "=r"(v.z), "=r"(v.w) : "l"(p) : "memory"); return v; }
DEVINL uint32_t ldg_cg32(const void* p) { uint32_t v; asm volatile("ld.global.cg.u32 %0, [%1];" : "=r"(v) : "l"(p) : "memory"); return v; }
DEVINL uint32_t ldg32_if(const void* p, int on) { uint32_t v; asm volatile("{.reg .pred q; setp.ne.s32 q, %2, 0; mov.u32 %0, 0; @q ld.global.cg.u32 %0, [%1];}" : "=r"(v) : "l"(p), "r"(on) : "memory"); return v; }
DEVINL uint4 ldg128_if(const void* p, int on) { uint4 v; asm volatile("{.reg .pred q; setp.ne.s32 q, %5, 0; mov.u32 %0, 0; mov.u32 %1, 0; mov.u32 %2, 0; mov.u32 %3, 0; @q ld.global.cg.v4.u32 {%0,%1,%2,%3}, [%4];}" : "=r"(v.x), "=r"(v.y), "=r"(v.z), "=r"(v.w) : "l"(p), "r"(on) : "memory"); return v; }
DEVINL void stg32_if(void* p, uint32_t v, int on) { asm volatile("{.reg .pred q; setp.ne.s32 q, %2, 0; @q st.global.u32 [%0], %1;}" ::"l"(p), "r"(v), "r"(on) : "memory"); }
DEVINL void stg128_if(void* p, uint4 v, int on) { asm volatile("{.reg .pred q; setp.ne.s32 q, %5, 0; @q st.global.v4.u32 [%0], {%1,%2,%3,%4};}" ::"l"(p), "r"(v.x), "r"(v.y), "r"(v.z), "r"(v.w), "r"(on) : "memory"); }
DEVINL uint4 ldg_na128(const void* p) { uint4 v; asm volatile("ld.global.L1::no_allocate.v4.u32 {%0,%1,%2,%3}, [%4];" : "=r"(v.x), "=r"(v.y), "=r"(v.z), "=r"(v.w) : "l"(p) : "memory"); return v; }
DEVINL uint4 ldg_ef128(const void* p) { uint4 v; asm volatile("ld.global.L1::evict_first.v4.u32 {%0,%1,%2,%3}, [%4];" : "=r"(v.x), "=r"(v.y), "=r"(v.z), "=r"(v.w) : "l"(p) : "memory"); return v; }
DEVINL uint4 ldg_ca128(const void* p) { uint4 v; asm volatile("ld.global.ca.v4.u32 {%0,%1,%2,%3}, [%4];" : "=r"(v.x), "=r"(v.y), "=r"(v.z), "=r"(v.w) : "l"(p) : "memory"); return v; }
DEVINL uint32_t ldg_ca32(const void* p) { uint32_t v; asm volatile("ld.global.ca.u32 %0, [%1];" : "=r"(v) : "l"(p) : "memory"); return v; }
DEVINL void flag_wait(const uint32_t* p, uint32_t want) {
  uint32_t v;
#pragma unroll 1
  for (int n = 0; n < POLL_LIMIT; n++) { asm volatile("ld.acquire.gpu.global.u32 %0, [%1];" : "=r"(v) : "l"(p) : "memory"); if (v >= want) break; __nanosleep(40); }
}
DEVINL void flag_wait_warp(const uint32_t* p, uint32_t want) {
  uint32_t v; int n = 0;
  do { asm volatile("ld.acquire.gpu.global.u32 %0, [%1];" : "=r"(v) : "l"(p) : "memory"); } while (__any_sync(~0u, v < want && ++n < POLL_LIMIT));
}
DEVINL void flag_add(uint32_t* p) { asm volatile("red.release.gpu.global.add.u32 [%0], 1;" ::"l"(p) : "memory"); }
DEVINL void flag_set(uint32_t* p, uint32_t v) { asm volatile("fence.acq_rel.gpu; st.relaxed.gpu.global.u32 [%0], %1;" ::"l"(p), "r"(v) : "memory"); }
DEVINL uint32_t ldg_rlx32(const void* p) { uint32_t v; asm volatile("ld.relaxed.gpu.global.u32 %0, [%1];" : "=r"(v) : "l"(p) : "memory"); return v; }
DEVINL float ex2(float x) { float y; asm("ex2.approx.ftz.f32 %0, %1;" : "=f"(y) : "f"(x)); return y; }
DEVINL float rcp(float x) { float y; asm("rcp.approx.ftz.f32 %0, %1;" : "=f"(y) : "f"(x)); return y; }
DEVINL uint32_t opaque(uint32_t x) { return __shfl_sync(~0u, x, threadIdx.x & 31); }
DEVINL uint32_t launder(uint32_t x) { asm volatile("" : "+r"(x)); return x; }
DEVINL void pdl_wait() { asm volatile("griddepcontrol.wait;" ::: "memory"); }
DEVINL void pdl_launch() { asm volatile("griddepcontrol.launch_dependents;" ::: "memory"); }
#define LOGS(cta, i)
#define LOGK(k, i)
#define LOG(cta, i)
#define LOGV(cta, i, v)
#define EV(i, v)
constexpr float SM_SCALE = 0.08838834764831845f * 1.4426950408889634f;

DEVINL void unpack8(uint4 v, float* f) { f[0] = bf_lo(v.x); f[1] = bf_hi(v.x); f[2] = bf_lo(v.y); f[3] = bf_hi(v.y); f[4] = bf_lo(v.z); f[5] = bf_hi(v.z); f[6] = bf_lo(v.w); f[7] = bf_hi(v.w); }
DEVINL uint4 pack8(const float* f) { return make_uint4(pack_bf16(f[0], f[1]), pack_bf16(f[2], f[3]), pack_bf16(f[4], f[5]), pack_bf16(f[6], f[7])); }
DEVINL void ln_row(float* f) {
  float s = 0.f;
#pragma unroll
  for (int i = 0; i < 40; i++) s += f[i];
#pragma unroll
  for (int o = 1; o < 16; o <<= 1) s += __shfl_xor_sync(~0u, s, o);
  const float mean = s * (1.f / 640.f); float q = 0.f;
#pragma unroll
  for (int i = 0; i < 40; i++) { f[i] -= mean; q = fmaf(f[i], f[i], q); }
#pragma unroll
  for (int o = 1; o < 16; o <<= 1) q += __shfl_xor_sync(~0u, q, o);
  const float rs = rsqrtf(q * (1.f / 640.f) + 1e-5f);
#pragma unroll
  for (int i = 0; i < 40; i++) f[i] *= rs;
}

struct Wts { const char* w[4]; };
template <int CH> DEVINL void weight_warm(const Wts& w, uint32_t buf, uint32_t bar, uint32_t stop) {
  uint32_t smid; asm volatile("mov.u32 %0, %%smid;" : "=r"(smid));
  const uint32_t c = g_role[smid & 255];
  if (c >= 128) return;
  mbar_init(bar, 1); asm volatile("fence.mbarrier_init.release.cluster; fence.proxy.async.shared::cta;" ::: "memory");
  constexpr int N = 81920 / CH;
#pragma unroll 1
  for (int i = 0; i < (c < 64 ? 4 : 2) * N; i++) {
    uint32_t v; asm volatile("ld.volatile.shared.u32 %0, [%1];" : "=r"(v) : "r"(stop) : "memory");
    if (v) break;
    mbar_arrive_tx(bar, CH);
    bulk_g2s(buf, w.w[c < 64 ? i / N : i / N * 2] + (c & 63) * 81920 + (i % N) * CH, CH, bar);
    mbar_wait(bar, i & 1);
  }
}
struct ArgsA {
  const bf16* x; const bf16* mem0; char* comm; uint32_t* flags; const bf16* wr; const bf16* wi; const char* wq; const char* wo;
  int layer; int ta[4], tb[4], tc[2];
};

#define VP 4
#define HELD 0x2557
#define PRE 4
#define VPRE0 2
#define VPRE1 4
#define R0 2
#define TRK 30
#define TEXP 200
#define TRD 0
#define TKV 300
#define KB1 5
#define W2D 0
#define WD 4
#define VPW 2
#define P1F 1
#define W0D 0
#define XD 0
#define TSF 1
#define XP 0
#define PW 1
#define VXE 0
#define LA 0
#define KB2 9
#define KB3 13
#define TSE 7
#define PRP 0
#define R1 2
#define OBF 0
#define W1D 0
constexpr int C_WV = 0;
constexpr int C_WO = 81920;
constexpr int C_KV = 163840;
constexpr int C_M  = C_KV + 24576;
constexpr int C_QK = C_M + 10240;
constexpr int C_VP = C_QK + 4096;
constexpr int C_S  = C_VP + 4096;
constexpr int C_O  = C_S + 2048;
constexpr int C_R  = C_O + 2048;
constexpr int C_T  = C_R + 256;
constexpr int S_BAR = 229376;
constexpr int S_END = S_BAR + 256;
enum { BAR_QK = 2, BAR_O = 3, BAR_H = 4, BAR_X = 5, BAR_W = 7  , BAR_E = 9, BAR_M1 = 10  , BAR_M3 = 12, BAR_M2 = 13   };
constexpr int B_W = 0, B_S = 8, B_W2 = 16, B_KV = 24, B_WV = 40, B_WO = 48;
constexpr int G2_OFF = 0x130000, TS_OFF = 0x11000;

#define FEN() asm volatile("pmevent 0;" ::: "memory")
#define SCHED(x, c) asm volatile("{.reg .pred p; setp.eq.u32 p, %0, %1; @p exit;}" ::"r"(x), "r"(0x7fff0001u + 2 * (c)) : "memory")
DEVINL uint32_t g1page(uint32_t L) { L = ((L & 7) | ((L & 24) << 2)) << 1; return (L | (__popc(L & 0xb2) & 1)) << 12; }
DEVINL void spin_until(uint32_t t) {
  asm volatile("{.reg .pred p; .reg .b32 c; .reg .b64 w;\nS0: mov.u64 w, %%clock64; cvt.u32.u64 c, w; sub.u32 c, %0, c; setp.lt.u32 p, c, 16384; @p bra.uni S0;}" ::"r"(t) : "memory");
}
DEVINL uint32_t wait_until(uint32_t t, uint32_t z) { uint32_t r;
  asm volatile("{.reg .pred p; .reg .b32 c,x,y; .reg .b64 w;\nT0: .branchtargets L0, L1, L2, L3, L4, L5, L6, L7, L8, L9, L10;\n mov.u32 x, %2;\n"
               "mov.u64 w, %%clock64; cvt.u32.u64 c, w; sub.u32 c, %1, c; setp.ge.u32 p, c, 16384; @p bra.uni L0;\n"
               "S0: mov.u64 w, %%clock64; cvt.u32.u64 c, w; sub.u32 c, %1, c; setp.gt.s32 p, c, 40; @p bra.uni S0;\n"
               "mad.lo.s32 c, c, 37, 1200; shr.s32 c, c, 8; max.s32 c, c, 0;\nbrx.idx.uni c, T0;\n"
               "L10: mul.lo.u32 x, x, x; L9: mul.lo.u32 x, x, x; L8: mul.lo.u32 x, x, x; L7: mul.lo.u32 x, x, x; L6: mul.lo.u32 x, x, x; L5: mul.lo.u32 x, x, x; L4: mul.lo.u32 x, x, x; L3: mul.lo.u32 x, x, x; L2: mul.lo.u32 x, x, x; L1: mul.lo.u32 x, x, x; L0: mov.u32 %0, x;}" : "=r"(r) : "r"(t), "r"(z) : "memory"); return r;
}
DEVINL void gtime(uint32_t& G16, uint32_t& C) {
  asm volatile("{.reg .b64 w; .reg .b32 g,g0,a;\n mov.u64 w, %%clock64; cvt.u32.u64 %1, w; mov.u64 w, %%globaltimer; cvt.u32.u64 g0, w; mul.lo.u32 a, g0, -11;\n"
               "mov.u64 w, %%globaltimer; cvt.u32.u64 g, w; add.u32 a, a, g; mov.u64 w, %%globaltimer; cvt.u32.u64 g, w; add.u32 a, a, g; mov.u64 w, %%globaltimer; cvt.u32.u64 g, w; add.u32 a, a, g; mov.u64 w, %%globaltimer; cvt.u32.u64 g, w; add.u32 a, a, g; mov.u64 w, %%globaltimer; cvt.u32.u64 g, w; add.u32 a, a, g; mov.u64 w, %%globaltimer; cvt.u32.u64 g, w; add.u32 a, a, g; mov.u64 w, %%globaltimer; cvt.u32.u64 g, w; add.u32 a, a, g; mov.u64 w, %%globaltimer; cvt.u32.u64 g, w; add.u32 a, a, g; mov.u64 w, %%globaltimer; cvt.u32.u64 g, w; add.u32 a, a, g; mov.u64 w, %%globaltimer; cvt.u32.u64 g, w; add.u32 a, a, g; mov.u64 w, %%globaltimer; cvt.u32.u64 g, w; add.u32 a, a, g; \n mul.lo.u32 a, a, 341; shr.u32 a, a, 8; mad.lo.u32 %0, g0, 16, a;}" : "=r"(G16), "=r"(C)::"memory");
}
DEVINL uint32_t pack_tag(float lo, float hi, uint32_t tg) {
  const uint32_t w = pack_bf16(lo, __uint_as_float(tg | 0x3F800000u)), a = __float_as_uint(hi) + (tg ^ 0x10000u); uint32_t r;
  asm("lop3.b32 %0, %1, %2, 0xFFFE0000, 0xE4;" : "=r"(r) : "r"(a), "r"(w)); return r;
}
DEVINL float ex2v(float x) { float y; asm volatile("ex2.approx.ftz.f32 %0, %1;" : "=f"(y) : "f"(x)); return y; }
DEVINL void load_kv(uint32_t sb, int h, int j, int s) {
  asm volatile("{.reg .pred p; elect.sync _|p, 0xffffffff;\n fence.proxy.async.global;\n @p mbarrier.arrive.expect_tx.shared::cta.b64 _, [%2], 12288;\n"
               " @p cp.async.bulk.shared::cluster.global.mbarrier::complete_tx::bytes [%0], [%1], 12288, [%2];}"
               ::"r"(sb + C_KV + (s & 1) * 12288), "l"(g_kv + (size_t)(s * 32 + h) * 16384 + j * 4096), "r"(sb + S_BAR + B_KV + (s & 1) * 8) : "memory");
}

template <int KH>
DEVINL void chain_mma(uint32_t sb0, const ArgsA& args) {
  const int lane = threadIdx.x & 31, mg = (threadIdx.x >> 5) & 3, mi = lane >> 3, r = lane & 7;
  const uint32_t aW = opaque(sb0 + (uint32_t)(((mi >> 1) * 8 + r) * 128 + (((mg + 4 * (mi & 1)) ^ r) << 4)));
  const uint32_t aL = opaque(sb0 + lane * 16);
  const uint32_t aLm = opaque(sb0 + mg * 512 + lane * 16);
#define sb (launder(aL) & ~511u)
  constexpr int OV = C_WV + KH * 40960, OM = C_M + KH * 5120, NF = KH ? 16 : 24;
  auto owo = [](int f) { return C_WO + (KH + 2 * (f >> 3)) * 16384 + (f & 7) * 2048; };
  auto held = [](int k) { return (HELD >> k) & 1; };
  auto rank = [](int k) { return __popc(HELD & ((1 << k) - 1)); };
  uint32_t wq[20][4], wk[20][4];
  mbar_wait(sb + S_BAR + B_W, 0);
#pragma unroll
  for (int k = 0; k < 12; k++) { ldsm4t(wq[k], aW + OV + k * 2048); ldsm4t(wk[k], aW + C_WO + KH * 40960 + k * 2048); }
  bar_arrive(BAR_H, 288);
  mbar_wait(sb + S_BAR + B_W2, 0);
#pragma unroll
  for (int k = 12; k < 20; k++) { ldsm4t(wq[k], aW + OV + k * 2048); ldsm4t(wk[k], aW + C_WO + KH * 40960 + k * 2048); }
  bar_sync(BAR_E, 384);
  mbar_wait(sb + S_BAR + B_WV, 0);
  uint32_t sx = args.layer << 16;
#pragma unroll 1
  while (true) {
    uint32_t v[20][4], b[10][4];
    {
      const uint32_t o = launder(aLm) - sb, on = (sx >> 16) != (uint32_t)args.layer;
      const char* p = args.comm + lds32(sb + C_T + KH * 1024 + 4 + (o >> 1));
      constexpr int NB = KH ? VPRE1 : VPRE0;
      const uint32_t zero = (uint32_t)(uintptr_t)p & 1, tt = lds32(sb + C_R + 48) + args.tb[0]; uint32_t av = aW;
#pragma unroll
      for (int k = 0; k < 20; k++) if (held(k) && rank(k) < NB) { ldsm4t(v[k], av + OV + k * 2048); if (rank(k) % VPW == VPW - 1 && rank(k) < NB - 1) av = aW + (v[k][0] & zero); }
      p += wait_until(tt, zero);
      uint4 a = ldg_rlx128(p);
      __syncwarp();
#pragma unroll
      for (int k = 0; k < 20; k++) if (held(k) && rank(k) >= NB) { ldsm4t(v[k], av + OV + k * 2048); if ((rank(k) - NB) % VPW == VPW - 1) av = aW + (v[k][0] & zero); }
      SCHED(o ^ on, 29);
      if (on) sts128(aLm + OM, a);
      if (__builtin_expect(__any_sync(~0u, on && (((a.x ^ sx) | (a.z ^ sx)) & 0x10000u)), 0)) {
        int lim = 0;
        do a = ldg_rlx128(p); while (__any_sync(~0u, (((a.x ^ sx) | (a.z ^ sx)) & 0x10000u) && ++lim < POLL_LIMIT));
        sts128(aLm + OM, a);
      }
      bar_sync(BAR_W + KH, 128);
      ldsm4t(b[0], aL + OM); ldsm4t(b[1], aL + OM + 512);
    }
    float cq[4], ck[4], cv[4];
    static_for<0, 20>([&](auto I) {
      constexpr int k = I.value, p = k >> 1;
      const uint32_t b0 = b[p][(k & 1) * 2], b1 = b[p][(k & 1) * 2 + 1];
      if (k == 0) { mma16816z(cv, v[0], b0, b1); mma16816z(cq, wq[k], b0, b1); mma16816z(ck, wk[k], b0, b1); }
      else { if (k < 20 - VP) mma16816(cv, v[k], b0, b1); mma16816(cq, wq[k], b0, b1); mma16816(ck, wk[k], b0, b1); }
      if (k == KB1) bar_sync(BAR_M1 + KH, 160);
      if (k == KB2) bar_sync(BAR_M2 + KH, 160);
      if (k == KB3) bar_sync(BAR_M3, 320);
      static_for<2, 10>([&](auto J) {
        constexpr int q = J.value, st = q < 4 ? 0 : q < 6 ? KB1 : q < 8 ? KB2 : KB3;
        if constexpr (k == (2 * q - 3 > st ? 2 * q - 3 : st)) ldsm4t(b[q], aL + OM + q * 512); });
      if constexpr (k + 3 < 20 - VP && !((HELD >> (k + 3)) & 1)) ldsm4t(v[k + 3], aW + OV + (k + 3) * 2048);
      if (k >= 20 - VP && k < 20 - VP + PRE && !held(k)) ldsm4t(v[k], aW + OV + k * 2048);
      if (P1F && (k & 1) && k >= P1F && k < 19) FEN();
    });
    stsm4(aLm + C_QK + KH * 2048, pack_bf16(cq[0], cq[1]), pack_bf16(cq[2], cq[3]), pack_bf16(ck[0], ck[1]), pack_bf16(ck[2], ck[3]));
    bar_arrive(BAR_QK, 384);
    FEN();
    const uint32_t l8 = (launder(aL) & 511) >> 1, px = lds32(sb + C_R + 80);
#pragma unroll
    for (int k = 20 - VP + PRE; k < 20; k++) if (!held(k)) ldsm4t(v[k], aW + OV + k * 2048);
#pragma unroll
    for (int k = 20 - VP; k < 20; k++) {
      const int p = k >> 1, q = k - 20 + VP; const uint32_t b0 = b[p][(k & 1) * 2], b1 = b[p][(k & 1) * 2 + 1];
      if (q % 3 == 0) mma16816(cv, v[k], b0, b1); else if (q == 1) mma16816z(cq, v[k], b0, b1); else if (q == 2) mma16816z(ck, v[k], b0, b1);
      else if (q % 3 == 1) mma16816(cq, v[k], b0, b1); else mma16816(ck, v[k], b0, b1);
    }
    if (VP >= 3) {
#pragma unroll
      for (int i = 0; i < 4; i++) cv[i] += cq[i] + ck[i];
    }
    { const uint32_t vx = pack_bf16(cv[0], cv[1]), vy = pack_bf16(cv[2], cv[3]);
      const uint32_t av = aLm - l8 + C_VP + KH * 256;
      stasync64(av + 2048 + px, vx, vy, sb + S_BAR + B_S + px);
      sts64(av, vx, vy);
      __syncwarp();
      if (l8 == 0) mbar_arrive(sb + S_BAR + B_S); }
    sx += 0x10000;
    if ((sx >> 16) == args.layer + 64u) break;
    uint32_t w[NF][4];
    {
      const uint32_t zero = px & 1; uint32_t a = aW;
      const bool tsw = KH == 1 && __any_sync(~0u, launder(aLm) == aL); uint2 ts = make_uint2(0, 0); uint4 cal = make_uint4(0, 0, 0, 0);
      if ((sx >> 16) == args.layer + 1u) mbar_wait(sb + S_BAR + B_WO, 0);
#pragma unroll
      for (int f = 0; f < 8 + XP; f++) { ldsm4t(w[f], a + owo(f));
        if (KH == 1 && f == TSF && tsw) { ts = ldg_rlx64(args.comm + TS_OFF + l8); cal = lds128(sb + C_R + 64); }
      if (KH == 1 && f == TSE && tsw) {
        const uint32_t d0 = ts.x - cal.x, d1 = ts.y - cal.x;
        const int dt = (int)__reduce_max_sync(~0u, max(d0 < 32768u ? d0 : 0u, d1 < 32768u ? d1 : 0u));
        sts32(sb + C_R + 48, cal.y + min((dt * cal.z) >> 16, 8192u));
      }
        uint32_t d = w[f][0] & zero;
#pragma unroll
        for (int q = 0; q < TRD; q++) d = __popc(d);
        if (f % PW == PW - 1) a = aW + d; }
    }
    const uint32_t go = lds32(sb + C_T + KH * 1024 + ((launder(aLm) - sb) >> 1));
    SCHED(go, 30);
    bar_sync(BAR_O, 384);
    uint32_t ob[16];
#pragma unroll
    for (int p = 0; p < 4; p++) ldsm4t(ob + 4 * p, aL + C_O + p * 512);
    __syncwarp();
    float r0, r1; uint32_t y0, y1;
    { const uint2 rr = lds64(sb + C_R + 128 + ((launder(aL) >> 1) & 24)); r0 = rcp(__uint_as_float(rr.x)); r1 = rcp(__uint_as_float(rr.y)); }
    constexpr int RA = KH ? R1 : R0;
    static_for<0, NF>([&](auto I) {
      constexpr int f = I.value, k = f & 7, nx = (f & ~7) + 8, x0 = f < 8 ? XP : 0; const uint32_t* A = w[f];
      if (k == 0) mma16816z(cq, A, ob[0], ob[1]); else if (k == 1) mma16816z(ck, A, ob[2], ob[3]);
      else if (k & 1) mma16816(ck, A, ob[2 * k], ob[2 * k + 1]); else mma16816(cq, A, ob[2 * k], ob[2 * k + 1]);
      if constexpr (f >= 8 && (f & 1) && k + WD < 8) { const uint32_t a = aW + (A[0] & go & 1); ldsm4t(w[f + WD - 1], a + owo(f + WD - 1)); ldsm4t(w[f + WD], a + owo(f + WD)); }
      if constexpr (k == 5 && nx < NF && RA > 0) { const uint32_t a = f < 8 ? aW : aW + (A[0] & go & 1);
#pragma unroll
        for (int q = x0; q < x0 + RA; q++) ldsm4t(w[nx + q], a + owo(nx + q)); }
      if (k == 7) { y0 = pack_tag((cq[0] + ck[0]) * r0, (cq[1] + ck[1]) * r1, sx & 0x10000u); y1 = pack_bf16((cq[2] + ck[2]) * r0, (cq[3] + ck[3]) * r1);
        stg_rlx64(args.comm + go + (f < 8 ? 0 : f < 16 ? 0x30000 : 0x100000), y0, y1); }
      if constexpr (k == 7 && nx < NF) {
        if constexpr (KH == 1 && W1D != 0) spin_until(clk() + W1D); else FEN();
#pragma unroll
        for (int q = x0 + RA; q < WD; q++) ldsm4t(w[nx + q], aW + owo(nx + q));
      }
      if (f >= 8 && k == 3) SCHED(y0 & y1 & go, 40 + f);
      else if ((f >= 7 && (f & 1)) || (f == 5 && RA > 0) || (f == 1 && OBF)) FEN();
    });
  }
}

#undef sb
DEVINL void chain_helper(uint32_t sb, uint32_t px, int h, int j, const ArgsA& args, const CUtensorMap* tq, const CUtensorMap* tk, const CUtensorMap* tv, const CUtensorMap* to) {
  const int c = 2 * h + j;
  const uint32_t bW = sb + S_BAR + B_W, bS = sb + S_BAR + B_S, bKV = sb + S_BAR + B_KV;
  const uint32_t lane0 = opaque(threadIdx.x & 31);
  const uint32_t warp = __reduce_max_sync(~0u, (threadIdx.x >> 5) & 3);
  { const int tid = threadIdx.x - 256;
    if (tid == 0) { mbar_arrive_tx(bW, 98304); mbar_arrive_tx(bW + B_W2, 65536); mbar_arrive_tx(bW + B_WV, 81920); mbar_arrive_tx(bW + B_WO, 81920);
#pragma unroll 1
      for (int q = 0; q < 10; q++) { const int i = (q & 1) * 5 + (q >> 1); const uint32_t bar = q < 6 ? bW : bW + B_W2;
        tma_2d(sb + C_WV + i * 8192, tq, h * 128 + j * 64, i * 64, bar); tma_2d(sb + C_WO + i * 8192, tk, h * 128 + j * 64, i * 64, bar); } }
    uint32_t G0, C0; gtime(G0, C0);
    if (warp == 0) sts64(sb + C_R + 96, G0, C0);
    { const uint32_t g = lane0 >> 2, t = lane0 & 3;
      sts128(sb + C_T + 2048 + tid * 16, make_uint4(g1page(c >> 1) + (c & 1) * 2048 + (warp == 0 ? 0 : warp == 1 ? 0x30000 : 0x100000) + ((g >> 2) * 4 + t) * 64 + (g & 3) * 16,
                                                    g1page(((t >> 1) + (g >> 2) * 2) * 4 + warp) + G2_OFF + (c >> 4) * 1024 + (t & 1) * 512 + (c & 15) * 32 + (g & 3) * 8,
                                                    g1page((h & 3) * 4 + (warp == 2 ? 2 : 1)) + G2_OFF + (warp == 1 ? 1024 : warp == 3 ? 2048 : 0) + lane0 * 16, (g & 1) ? 0x3F800000u : 0x00003F80u)); }
    sts32(sb + C_R + 80, px); sts32(sb + C_R + 48, C0 - 65536);
#pragma unroll
    for (int kh = 0; kh < 2; kh++)
      sts64(sb + C_T + kh * 1024 + tid * 8, g1page(j * 16 + kh * 8 + (tid >> 4)) + (tid & 8) * 256 + h * 64 + (tid & 7) * 8, g1page((h & 3) * 4) + G2_OFF + kh * 2048 + tid * 16);
#pragma unroll
    for (int i = 0; i < 5; i++) { const int q = tid + i * 128, n = q & 7, d0 = (q >> 3) * 8; const uint4 v = *(const uint4*)(args.mem0 + n * 640 + d0); const uint32_t w[4] = {v.x, v.y, v.z, v.w};
#pragma unroll
      for (int e = 0; e < 8; e++) asm volatile("st.shared.u16 [%0], %1;" ::"r"(sb + C_M + (d0 + e) * 16 + n * 2), "h"((unsigned short)(w[e >> 1] >> ((e & 1) * 16))) : "memory"); }
    auto round2 = [&](int q0, int q1) {
#pragma unroll 1
      for (int q = q0; q < q1; q++) { const int i = (q & 1) * 5 + (q >> 1); tma_2d(sb + C_WV + i * 8192, tv, h * 128 + j * 64, i * 64, bW + B_WV); }
#pragma unroll 1
      for (int q = q0; q < q1; q++) { const int i = (q & 1) * 5 + (q >> 1); tma_2d(sb + C_WO + i * 8192, to, j * 320 + (i >> 1) * 64, h * 128 + ((i & 1) ^ j) * 64, bW + B_WO); } };
    if (warp == 0) { bar_sync(BAR_H, 288); if (tid == 0) round2(0, 6); __syncwarp(); }
    bar_sync(BAR_E, 384);
    if (tid == 0) round2(6, 10);
    if (warp == 3) {
      if (tid == 96) LOG(c, 250);
      flag_wait_warp(args.flags + F_KV + h * 32, 2);
      load_kv(sb, h, j, 0); load_kv(sb, h, j, 1); if (tid == 96) LOG(c, 251);
    }
  }
  auto calib = [&]() { uint32_t G, C; gtime(G, C);
    const uint2 o = lds64(sb + C_R + 96); const float rt = (float)(C - o.y) * rcp((float)(G - o.x));
    sts128(sb + C_R + 32, make_uint4(G, C, __float2uint_rn(rt * 65536.f) & 0xffffu, __float_as_uint(rcp(rt)))); __syncwarp(); };
  auto do_export = [&](int s, uint32_t lane) {
    uint32_t k0[2][4], k1[2][4]; uint2 a[4], b[4];
    const uint32_t ak = sb + C_QK + 256 + (lane >> 4) * 512 + (lane & 15) * 16, av = sb + C_VP + (lane >> 3) * 512 + (lane & 7) * 8;
#pragma unroll
    for (int i = 0; i < 2; i++) { ldsm4t(k0[i], ak + i * 1024); ldsm4t(k1[i], ak + i * 1024 + 2048); }
#pragma unroll
    for (int i = 0; i < 4; i++) { a[i] = lds64(av + i * 64); b[i] = lds64(av + i * 64 + 256); }
    char* dst = g_kvm + ((s * 32 + h) * 4096 + j * 1024 + lane * 16);
    const uint32_t tg = (args.layer ^ 1) << 16;
    auto put = [&](char* q, uint32_t x, uint32_t y, uint32_t z, uint32_t w) { stg_rlx128(q, (x & ~0x10000u) | tg, y, (z & ~0x10000u) | tg, w); };
#pragma unroll
    for (int i = 0; i < 2; i++) put(dst + i * 512, hadd2bf(k0[i][0], k1[i][0]), hadd2bf(k0[i][1], k1[i][1]), hadd2bf(k0[i][2], k1[i][2]), hadd2bf(k0[i][3], k1[i][3]));
    put(dst + 2048, hadd2bf(a[0].x, b[0].x), hadd2bf(a[1].x, b[1].x), hadd2bf(a[2].x, b[2].x), hadd2bf(a[3].x, b[3].x));
    put(dst + 2560, hadd2bf(a[0].y, b[0].y), hadd2bf(a[1].y, b[1].y), hadd2bf(a[2].y, b[2].y), hadd2bf(a[3].y, b[3].y));
    stg_rlx32(args.flags + F_KM + h * 32 + j, s + 1);
  };
  auto staged = [&]() { if (warp == 2) bar_arrive(BAR_M3, 320); else if (warp == 1) { bar_arrive(BAR_M2, 160); bar_arrive(BAR_M2 + 1, 160); } else bar_arrive(BAR_M1 + (warp >> 1), 160); };
  if (warp == 0) calib();
  staged();
  int kv_ok = 1;
  uint32_t vx[4][4];
  auto load_vx = [&](int s, uint32_t lane) {
    const uint32_t aVx = sb + C_KV + (s & 1) * 12288 + 4096 + (warp >> 1) * (j ? -4096 : 4096) + (warp & 1) * 1024 + lane * 16, zero = lane >> 5;
#pragma unroll
    for (int i = 0; i < 4; i++) { const uint4 q = lds128(aVx + (i & 1) * 2048 + (i >> 1) * 512); vx[i][0] = q.x ^ zero; vx[i][1] = q.z ^ zero; vx[i][2] = q.y ^ zero; vx[i][3] = q.w ^ zero; }
  };
  uint2 kb[4];
  auto prep = [&](int s, uint32_t lane) {
    if (s < 63) mbar_wait(bKV + (s & 1) * 8, (s >> 1) & 1);
    const uint32_t aK = sb + C_KV + (s & 1) * 12288 + j * 8192 + warp * 1024 + lane * 16;
#pragma unroll
    for (int i = 0; i < 4; i++) kb[i] = lds64(aK + ((warp ^ i) >> 1) * 512 + ((warp ^ i) & 1) * 8);
    if (VXE) load_vx(s, lane);
    asm volatile("{.reg .pred p; setp.eq.u32 p, %2, 32; @p mbarrier.arrive.expect_tx.shared::cta.b64 _, [%0], %1;}" ::"r"(bS), "r"(s < 63 ? 3072 : 2048), "r"(warp * 32 + lane) : "memory");
  };
  prep(0, lane0);
#pragma unroll 1
  for (int s = 0;; s++) {
    const uint32_t ph = s & 1;
    const uint32_t lane = __shfl_sync(~0u, lane0, lane0);
    const uint32_t mi = lane >> 3, r = lane & 7;
    const uint32_t aQ = sb + C_QK + (mi & 1) * 2048 + ((mi >> 1) * 8 + r) * 16;
    const uint32_t aKm = sb + C_QK + 256 + warp * 512 + (lane >> 4) * 2048 + (lane & 15) * 16;
    const uint32_t aH = sb + C_S + warp * 256 + lane * 8, aR = aH + 1024 + px;
    SCHED(aQ ^ aR ^ aKm, 60);
    if (warp == 0) {
      const uint4 cal = lds128(sb + C_R + 32);
      bar_sync(BAR_M3, 320);
      sts32(sb + C_R + 52, 0);
      const uint32_t E = clk(), e16 = cal.x + (uint32_t)__float2int_rn((float)(int)(E - cal.y) * __uint_as_float(cal.w));
      stg_rlx32(args.comm + TS_OFF + c * 4, e16); sts128(sb + C_R + 64, make_uint4(e16, E, cal.z, 0));
    }
    if (s == 63) { bar_sync(BAR_QK, 384); mbar_wait(bS, 1); if (warp == 3) do_export(63, lane); break; }
    {
      uint32_t qa[4][4], km[4]; float s0[4], s1[4], s2[4];
      bar_sync(BAR_QK, 384);
      ldsm4t(qa[0], aQ + warp * 512); ldsm4t(km, aKm); ldsm4t(qa[1], aQ + (warp ^ 1) * 512); ldsm4t(qa[2], aQ + (warp ^ 2) * 512); ldsm4t(qa[3], aQ + (warp ^ 3) * 512);
      mma16816z(s0, qa[0], kb[0].x, kb[0].y); mma16816z(s2, qa[0], km[0], km[1]); mma16816z(s1, qa[1], kb[1].x, kb[1].y);
      FEN();
      mma16816(s2, qa[0], km[2], km[3]); mma16816(s0, qa[2], kb[2].x, kb[2].y); mma16816(s1, qa[3], kb[3].x, kb[3].y);
      const uint32_t w0 = pack_bf16((s0[0] + s0[2]) + (s1[0] + s1[2]), (s0[1] + s0[3]) + (s1[1] + s1[3]));
      const uint32_t w1 = pack_bf16(s2[0] + s2[2], s2[1] + s2[3]);
      stasync64(aR, w0, w1, bS + px);
      sts64(aH, w0, w1);
    }
    {
      uint32_t sl[5];
      const uint32_t a8 = sb + lane * 8, av = a8 + C_VP + warp * 1024;
      const uint32_t aO = sb + C_O + ((warp >> 1) * 64 + (warp & 1) * 16 + (mi & 1) * 32 + (mi >> 1) * 8 + r) * 16, aU = sb + C_R + (lane & 28);
      bar_sync(BAR_X, 128);
      { uint2 t[4];
#pragma unroll
        for (int u = 0; u < 4; u++) t[u] = lds64(a8 + C_S + u * 256);
        if (!VXE) load_vx(s, lane);
#pragma unroll
        for (int u = 0; u < 4; u++) sl[u] = t[u].x;
        sl[4] = pack_bf16((bf_lo(t[0].y) + bf_lo(t[1].y)) + (bf_lo(t[2].y) + bf_lo(t[3].y)), (bf_hi(t[0].y) + bf_hi(t[1].y)) + (bf_hi(t[2].y) + bf_hi(t[3].y))); }
      mbar_wait(bS, ph);
      uint32_t vm[2][4];
      { uint2 t[4];
#pragma unroll
        for (int u = 0; u < 4; u++) t[u] = lds64(a8 + C_S + 1024 + u * 256);
#pragma unroll
        for (int u = 0; u < 4; u++) sl[u] = hadd2bf(sl[u], t[u].x);
        sl[4] = hadd2bf(hadd2bf(hadd2bf(sl[4], t[0].y), t[1].y), hadd2bf(t[2].y, t[3].y)); }
      uint32_t m2 = hmax2bf(hmax2bf(hmax2bf(sl[0], sl[1]), hmax2bf(sl[2], sl[3])), sl[4]);
      const uint32_t x1 = __shfl_xor_sync(~0u, m2, 1), x2 = __shfl_xor_sync(~0u, m2, 2), x3 = __shfl_xor_sync(~0u, m2, 3);
#pragma unroll
      for (int i = 0; i < 4; i++) { const uint2 q = lds64(av + i * 256); vm[i >> 1][(i & 1) * 2] = q.x; vm[i >> 1][(i & 1) * 2 + 1] = q.y; }
      float sv[10];
#pragma unroll
      for (int u = 0; u < 5; u++) { sv[2 * u] = bf_lo(sl[u]) * SM_SCALE; sv[2 * u + 1] = bf_hi(sl[u]) * SM_SCALE; }
      FEN();
      m2 = hmax2bf(hmax2bf(m2, x1), hmax2bf(x2, x3));
      const float mx = fmaxf(bf_lo(m2), bf_hi(m2));
      float o0[4], o1[4];
#pragma unroll
      for (int i = 0; i < 10; i++) sv[i] = fmaf(mx, -SM_SCALE, sv[i]);
      sv[8] = ex2v(sv[8]); sv[9] = ex2v(sv[9]);
#pragma unroll
      for (int i = 0; i < 8; i++) sv[i] = ex2v(sv[i]);
      { const uint32_t p = pack_bf16(sv[8], sv[9]); mma16816z(o0, vm[0], p, p); mma16816z(o1, vm[1], p, p); }
      { const uint32_t p0 = pack_bf16(sv[0], sv[1]), p1 = pack_bf16(sv[2], sv[3]); mma16816(o0, vx[0], p0, p1); mma16816(o1, vx[2], p0, p1); }
      { const uint32_t p0 = pack_bf16(sv[4], sv[5]), p1 = pack_bf16(sv[6], sv[7]); mma16816(o0, vx[1], p0, p1); mma16816(o1, vx[3], p0, p1); }
      float su = (((sv[8] + sv[9]) + ((sv[0] + sv[1]) + (sv[2] + sv[3]))) + (sv[4] + sv[5])) + (sv[6] + sv[7]);
      { const float a1 = __shfl_xor_sync(~0u, su, 1), a2 = __shfl_xor_sync(~0u, su, 2), a3 = __shfl_xor_sync(~0u, su, 3); su = (su + a1) + (a2 + a3); }
      sts32(aU + 128, __float_as_uint(su));
      stsm4(aO, pack_bf16(o0[0], o0[1]), pack_bf16(o0[2], o0[3]), pack_bf16(o1[0], o1[1]), pack_bf16(o1[2], o1[3]));
      bar_sync(BAR_O, 384);
    }
    const uint32_t t0 = lds32(sb + C_R + 48);
    const uint4 xo = lds128(sb + C_T + 2048 + warp * 512 + lane * 16);
    uint32_t rdy = 0;
    const uint32_t tag = (s + args.layer + 1) & 1, tm = 0u - tag;
    if (warp == 3) {
      if (lane == 0) { LOGS(c, s); LOGV(c, 192 + (s >> 1), clk()); }
      if (((s + 2) >> 1) >= kv_ok) rdy = ldg_rlx32(args.flags + F_KV + h * 32 + lane);
      spin_until(t0 + args.tc[0]);
      do_export(s, lane);
      if (lane == 0) LOG(c, 64 + s);
    }
    if (warp == 2) calib();
    if (warp < 2 || (warp == 2 && !(c & 16))) {
      const char* p = args.comm + xo.x; char* g2w = args.comm + xo.y;
      const uint32_t s0 = (lane & 8) ? 0u : xo.w, s1 = (lane & 8) ? xo.w : 0u;
      int lim = 0; bool bad;
      p += wait_until(t0 + args.ta[warp == 0 ? 0 : warp == 2 ? 3 : 1 + ((c >> 4) & 1)], lane >> 5);
      do {
        uint4 a[4]; float z0[4], z1[4], y[4];
#pragma unroll
        for (int i = 0; i < 4; i++) a[i] = ldg_rlx128(p + i * 512);
        ++lim;
        { const uint32_t A[4] = {a[0].x, a[0].y, a[0].z, a[0].w}; mma16816z(z0, A, s0, s1); }
        { const uint32_t A[4] = {a[1].x, a[1].y, a[1].z, a[1].w}; mma16816z(z1, A, s0, s1); }
        { const uint32_t A[4] = {a[2].x, a[2].y, a[2].z, a[2].w}; mma16816(z0, A, s0, s1); }
        { const uint32_t A[4] = {a[3].x, a[3].y, a[3].z, a[3].w}; mma16816(z1, A, s0, s1); }
        const uint32_t m0 = launder((a[0].x ^ tm) | (a[0].z ^ tm)), m1 = launder((a[1].x ^ tm) | (a[1].z ^ tm)), m2 = launder((a[2].x ^ tm) | (a[2].z ^ tm)), m3 = launder((a[3].x ^ tm) | (a[3].z ^ tm));
        bad = __any_sync(~0u, ((launder(m0 | m1 | m2) | m3) & 0x10000u) && lim < POLL_LIMIT);
#pragma unroll
        for (int i = 0; i < 4; i++) y[i] = z0[i] + z1[i];
        const bool odd = lane & 1; const float k0 = odd ? y[2] : y[0], k1 = odd ? y[3] : y[1], e0 = odd ? y[0] : y[2], e1 = odd ? y[1] : y[3];
        const float o0 = __shfl_xor_sync(~0u, e0, 1) + __shfl_xor_sync(~0u, e0, 17), o1 = __shfl_xor_sync(~0u, e1, 1) + __shfl_xor_sync(~0u, e1, 17);
        const float q0 = k0 + __shfl_xor_sync(~0u, k0, 16), q1 = k1 + __shfl_xor_sync(~0u, k1, 16);
        const uint32_t w0 = pack_tag(odd ? o0 : q0, odd ? o1 : q1, tag << 16), w1 = pack_bf16(odd ? q0 : o0, odd ? q1 : o1);
        if (!bad) stg_rlx64(g2w, w0, w1);
      } while (bad);
      if (lane == 0 && warp == 0) LOGV(c, 128 + s, lim);
      if (lane == 0) { EV(warp, clk() - t0); EV(3 + warp, lim); }
    }
    if (!PRP || warp != 1) prep(s + 1, lane); else kb[0] = kb[1] = kb[2] = kb[3] = make_uint2(0, 0);
    {
      const char* p = args.comm + xo.z;
      const uint32_t aMw = sb + C_M + 2048 + (warp == 3 ? 5120 : warp * 1024) + lane * 16;
      int lim = 0; bool bad;
      p += wait_until(t0 + args.tb[warp == 3 ? 1 : warp + 1], lane >> 5);
      if (warp == 0 || warp == 3) {
        do { const uint4 a = ldg_rlx128(p), b = ldg_rlx128(p + 512); ++lim;
          sts128(aMw, a); sts128(aMw + 512, b);
          bad = __any_sync(~0u, ((launder((a.x ^ tm) | (a.z ^ tm)) | launder((b.x ^ tm) | (b.z ^ tm))) & 0x10000u) && lim < POLL_LIMIT);
        } while (bad);
      } else {
        do { uint4 a[4]; uint32_t m[4]; ++lim;
#pragma unroll
          for (int i = 0; i < 4; i++) a[i] = ldg_rlx128(p + (i & 1) * 512 + (i >> 1) * 2048);
#pragma unroll
          for (int i = 0; i < 4; i++) { sts128(aMw + (i & 1) * 512 + (i >> 1) * 5120, a[i]); m[i] = launder((a[i].x ^ tm) | (a[i].z ^ tm)); }
          bad = __any_sync(~0u, ((launder(m[0] | m[1] | m[2]) | m[3]) & 0x10000u) && lim < POLL_LIMIT);
        } while (bad);
      }
      staged();
      if (lane == 0 && warp < 3) { EV(6 + warp, clk() - t0); EV(9 + warp, lim); }
    }
    if (PRP && warp == 1) prep(s + 1, lane);
    if (warp == 3 && s < 61) {
      spin_until(t0 + args.tc[1]);
      if (((s + 2) >> 1) >= kv_ok) {
        for (int n = 0; (kv_ok = __clz(__brev(~__ballot_sync(~0u, rdy >= 2)))) <= ((s + 2) >> 1) && n < POLL_LIMIT; n++) rdy = ldg_rlx32(args.flags + F_KV + h * 32 + lane);
        asm volatile("fence.acquire.gpu;" ::: "memory");
      }
      load_kv(sb, h, j, s + 2);
    }
  }
}

#define PF0 14
#define QORD 0
#define LDA ldg_ef128
#define LDB ldg_na128
#define PFD 2
#define PFR 1
#define NPROBE 3
#define OPACE 400
constexpr int G_ST = 163840;
constexpr int B_FULL = 64, B_EMPTY = 96, B_RB = 128, B_WD = 136, B_ROLE = 144, B_PROG = 152, B_WF = 160  , B_DUM = 200;
enum { BAR_T = 1  , BAR_G = 3  , BAR_V = 5   };
DEVINL uint64_t mkdesc(uint32_t a, uint32_t lbo, uint32_t sbo, uint32_t sw) { return (uint64_t)((a & 0x3FFFF) >> 4) | ((uint64_t)(lbo >> 4) << 16) | ((uint64_t)(sbo >> 4) << 32) | ((uint64_t)sw << 62); }
DEVINL void wgmma_n128(float* d, uint64_t a, uint64_t b, int acc) {
  asm volatile("{.reg .pred p; setp.ne.b32 p, %66, 0; wgmma.mma_async.sync.aligned.m64n128k16.f32.bf16.bf16 {%0,%1,%2,%3,%4,%5,%6,%7,%8,%9,%10,%11,%12,%13,%14,%15,%16,%17,%18,%19,%20,%21,%22,%23,%24,%25,%26,%27,%28,%29,%30,%31,%32,%33,%34,%35,%36,%37,%38,%39,%40,%41,%42,%43,%44,%45,%46,%47,%48,%49,%50,%51,%52,%53,%54,%55,%56,%57,%58,%59,%60,%61,%62,%63}, %64, %65, p, 1, 1, 0, 1;}"
               : "+f"(d[0]),"+f"(d[1]),"+f"(d[2]),"+f"(d[3]),"+f"(d[4]),"+f"(d[5]),"+f"(d[6]),"+f"(d[7]),"+f"(d[8]),"+f"(d[9]),"+f"(d[10]),"+f"(d[11]),"+f"(d[12]),"+f"(d[13]),"+f"(d[14]),"+f"(d[15]),"+f"(d[16]),"+f"(d[17]),"+f"(d[18]),"+f"(d[19]),"+f"(d[20]),"+f"(d[21]),"+f"(d[22]),"+f"(d[23]),"+f"(d[24]),"+f"(d[25]),"+f"(d[26]),"+f"(d[27]),"+f"(d[28]),"+f"(d[29]),"+f"(d[30]),"+f"(d[31]),"+f"(d[32]),"+f"(d[33]),"+f"(d[34]),"+f"(d[35]),"+f"(d[36]),"+f"(d[37]),"+f"(d[38]),"+f"(d[39]),"+f"(d[40]),"+f"(d[41]),"+f"(d[42]),"+f"(d[43]),"+f"(d[44]),"+f"(d[45]),"+f"(d[46]),"+f"(d[47]),"+f"(d[48]),"+f"(d[49]),"+f"(d[50]),"+f"(d[51]),"+f"(d[52]),"+f"(d[53]),"+f"(d[54]),"+f"(d[55]),"+f"(d[56]),"+f"(d[57]),"+f"(d[58]),"+f"(d[59]),"+f"(d[60]),"+f"(d[61]),"+f"(d[62]),"+f"(d[63]) : "l"(a), "l"(b), "r"(acc));
}
DEVINL void wgmma_n80(float* d, uint64_t a, uint64_t b, int acc) {
  asm volatile("{.reg .pred p; setp.ne.b32 p, %42, 0; wgmma.mma_async.sync.aligned.m64n80k16.f32.bf16.bf16 {%0,%1,%2,%3,%4,%5,%6,%7,%8,%9,%10,%11,%12,%13,%14,%15,%16,%17,%18,%19,%20,%21,%22,%23,%24,%25,%26,%27,%28,%29,%30,%31,%32,%33,%34,%35,%36,%37,%38,%39}, %40, %41, p, 1, 1, 0, 1;}"
               : "+f"(d[0]),"+f"(d[1]),"+f"(d[2]),"+f"(d[3]),"+f"(d[4]),"+f"(d[5]),"+f"(d[6]),"+f"(d[7]),"+f"(d[8]),"+f"(d[9]),"+f"(d[10]),"+f"(d[11]),"+f"(d[12]),"+f"(d[13]),"+f"(d[14]),"+f"(d[15]),"+f"(d[16]),"+f"(d[17]),"+f"(d[18]),"+f"(d[19]),"+f"(d[20]),"+f"(d[21]),"+f"(d[22]),"+f"(d[23]),"+f"(d[24]),"+f"(d[25]),"+f"(d[26]),"+f"(d[27]),"+f"(d[28]),"+f"(d[29]),"+f"(d[30]),"+f"(d[31]),"+f"(d[32]),"+f"(d[33]),"+f"(d[34]),"+f"(d[35]),"+f"(d[36]),"+f"(d[37]),"+f"(d[38]),"+f"(d[39]) : "l"(a), "l"(b), "r"(acc));
}

template <int N, int NST, bool HAND>
DEVINL void gemm_tile(float* acc, uint32_t sb, uint32_t px, int wg, uint32_t u0, int rot, bool lead, int wph) {
  const uint64_t db = N == 128 ? mkdesc(sb, 81920, 1024, 1) : mkdesc(sb, 32768, 256, 3);
#pragma unroll
  for (int i = 0; i < N / 2; i++) acc[i] = 0.f;
  bar_sync(BAR_T + wg, 256);
#pragma unroll 1
  for (int st = 0; st < NST; st++) {
    const uint32_t u = u0 + st, slot = u & 3, ks = (st + rot >= NST ? st + rot - NST : st + rot) * 8;
    if (wph >= 0) mbar_wait(sb + S_BAR + B_WF + (N == 128 ? st * 8 : 0), wph);
    mbar_wait(sb + S_BAR + B_FULL + slot * 8, (u >> 2) & 1);
    const uint64_t da = mkdesc(sb + G_ST + slot * 16384, 16, 1024, 1);
    asm volatile("wgmma.fence.sync.aligned;" ::: "memory");
#pragma unroll
    for (int k = 0; k < 8; k++) {
      const uint64_t a = da + (k >> 2) * 512 + (k & 3) * 2;
      if (N == 128) wgmma_n128(acc, a, db + (ks + k) * 128, 1); else wgmma_n80(acc, a, db + (ks + k) * 32, 1);
    }
    asm volatile("wgmma.commit_group.sync.aligned;" ::: "memory");
    if (HAND && st == NST - 1) bar_arrive(BAR_T + (wg ^ 1), 256);
    if (st > 0) {
      asm volatile("wgmma.wait_group.sync.aligned 1;" ::: "memory");
      if (lead) { const uint32_t e = sb + S_BAR + B_EMPTY + ((u - 1) & 3) * 8; mbar_arrive(e); mbar_arrive_remote(e + px); }
    }
  }
  asm volatile("wgmma.wait_group.sync.aligned 0;" ::: "memory");
  if (lead) { const uint32_t e = sb + S_BAR + B_EMPTY + ((u0 + NST - 1) & 3) * 8; mbar_arrive(e); mbar_arrive_remote(e + px); }
}
DEVINL void wg_publish(int wg) { bar_sync(BAR_G + wg, 160); }
DEVINL uint32_t km_known(uint32_t sb) { uint32_t v; asm volatile("ld.volatile.shared.u32 %0, [%1];" : "=r"(v) : "r"(sb + S_BAR + B_PROG) : "memory"); return __reduce_min_sync(~0u, v); }
DEVINL void km_load(uint4* f, const char* p) {
#pragma unroll
  for (int G = 0; G < 4; G++) f[G] = ldg_rlx128(p + G * 512);
}
DEVINL void km_check(uint4* f, const char* p, uint32_t tg) {
  int n = 0;
  while (__any_sync(~0u, (((f[0].x ^ tg) | (f[0].z ^ tg) | (f[1].x ^ tg) | (f[1].z ^ tg) | (f[2].x ^ tg) | (f[2].z ^ tg) | (f[3].x ^ tg) | (f[3].z ^ tg)) & 0x10000u) && ++n < POLL_LIMIT)) km_load(f, p);
}
DEVINL void km_watcher(uint32_t sb, const uint32_t* p) {
  uint32_t v = 0;
#pragma unroll 1
  for (int n = 0; n < 16 * POLL_LIMIT && v < 64; n++) {
    const uint2 q = ldg_rlx64(p);
    if (min(q.x, q.y) != v) { v = min(q.x, q.y); asm volatile("st.volatile.shared.u32 [%0], %1;" ::"r"(sb + S_BAR + B_PROG), "r"(v) : "memory"); }
    __nanosleep(v < 61 ? 300 : 20);
  }
}

template <int HF>
DEVINL void attend(const float* acc, uint4 (*kf)[4], uint4* kmf, uint4* op, const char* kvp, const char* mp, bf16* orow, int lane, int wg, uint32_t sb, int tile, bool& pend, uint32_t tg) {
  constexpr int NT = HF ? 4 : 2;
  const int g = lane >> 2, t = lane & 3;
  float sc[NT + 1][4];
#pragma unroll
  for (int k = 0; k < 8; k++) {
    uint32_t qa[4];
#pragma unroll
    for (int i = 0; i < 4; i++) { const float* a = acc + 32 * (k >> 2) + 4 * (k & 3) + 16 * (i >> 1) + 2 * (i & 1); qa[i] = pack_bf16(a[0], a[1]); }
#pragma unroll
    for (int kt = 0; kt <= NT; kt++) {
      const uint4 b = kt < NT ? kf[kt][k >> 1] : kmf[k >> 1];
      if (k == 0) mma16816z(sc[kt], qa, b.x, b.y); else if (k & 1) mma16816(sc[kt], qa, b.z, b.w); else mma16816(sc[kt], qa, b.x, b.y);
    }
  }
  FEN();
  bar_arrive(BAR_T + (wg ^ 1), 256);
  FEN();
  uint32_t go; asm volatile("{.reg .pred p,q; setp.ne.u32 q, %1, 0; bar.red.and.pred p, %2, 128, q; selp.u32 %0, 1, 0, p;}" : "=r"(go) : "r"((uint32_t)(tile < 30 && lds32(sb + S_BAR + B_PROG) > tile * 2 + 5)), "r"(BAR_V + wg) : "memory");
  uint4 vf[HF + 1][8], vm[4];
  auto traffic = [&]() {
    if (pend) {
#pragma unroll
      for (int q = 0; q < 4; q++) { *(uint4*)(orow - 128 * 4096 + q * 32) = op[2 * q]; *(uint4*)(orow - 120 * 4096 + q * 32) = op[2 * q + 1]; }
      wg_publish(wg);
    }
    pend = __any_sync(~0u, go);
    const char* vp = kvp + 4096 + (g >> 1) * 512 + ((g & 1) * 4 + t) * 16; const char* kp = kvp + 4 * 32 * 16384 + lane * 16;
    km_load(vm, mp + 2048 + lane * 16);
    if (pend) km_load(kmf, mp + 4 * 32 * 4096 + lane * 16);
#pragma unroll
    for (int hh = 0; hh <= HF; hh++) {
#pragma unroll
      for (int i = 0; i < 8; i++) { const char* q = vp + hh * 2048 + (i >> 2) * 4096 + (i & 3) * 128; vf[hh][i] = hh ? LDB(q) : LDA(q); }
      if (tile < 30) {
#pragma unroll
        for (int i = 8 * hh; i < 8 * hh + 8; i++) { const char* q = kp + ((i >> 1) & 1) * 12288 + (i >> 2) * 1024 + (i & 1) * 512; kf[i >> 2][i & 3] = hh ? LDB(q) : LDA(q); }
      }
    } };
  if (QORD == 0) traffic();
  const float NINF = __int_as_float(0xff800000);
  if (2 * t > g) { sc[NT - 2][0] = NINF; sc[NT - 1][2] = NINF; }
  if (2 * t + 1 > g) { sc[NT - 2][1] = NINF; sc[NT - 1][3] = NINF; }
  sc[NT - 1][0] = NINF; sc[NT - 1][1] = NINF;
  float m0 = fmaxf(sc[NT][0], sc[NT][1]), m1 = fmaxf(sc[NT][2], sc[NT][3]);
#pragma unroll
  for (int kt = 0; kt < NT; kt++) { m0 = fmaxf(m0, fmaxf(sc[kt][0], sc[kt][1])); m1 = fmaxf(m1, fmaxf(sc[kt][2], sc[kt][3])); }
  m0 = fmaxf(fmaxf(m0, __shfl_xor_sync(~0u, m0, 1)), fmaxf(__shfl_xor_sync(~0u, m0, 2), __shfl_xor_sync(~0u, m0, 3)));
  m1 = fmaxf(fmaxf(m1, __shfl_xor_sync(~0u, m1, 1)), fmaxf(__shfl_xor_sync(~0u, m1, 2), __shfl_xor_sync(~0u, m1, 3)));
  m0 *= -SM_SCALE; m1 *= -SM_SCALE;
  float s0 = 0.f, s1 = 0.f; uint32_t p[NT + 1][2];
#pragma unroll
  for (int kt = 0; kt <= NT; kt++) {
    const float a = ex2(fmaf(sc[kt][0], SM_SCALE, m0)), b = ex2(fmaf(sc[kt][1], SM_SCALE, m0)), c = ex2(fmaf(sc[kt][2], SM_SCALE, m1)), d = ex2(fmaf(sc[kt][3], SM_SCALE, m1));
    s0 += a + b; s1 += c + d; p[kt][0] = pack_bf16(a, b); p[kt][1] = pack_bf16(c, d);
  }
  s0 = (s0 + __shfl_xor_sync(~0u, s0, 1)) + (__shfl_xor_sync(~0u, s0, 2) + __shfl_xor_sync(~0u, s0, 3));
  s1 = (s1 + __shfl_xor_sync(~0u, s1, 1)) + (__shfl_xor_sync(~0u, s1, 2) + __shfl_xor_sync(~0u, s1, 3));
  s0 = rcp(s0); s1 = rcp(s1);
  if (QORD == 1) { FEN(); traffic(); }
  km_check(vm, mp + 2048 + lane * 16, tg);
  if (pend) km_check(kmf, mp + 4 * 32 * 4096 + lane * 16, tg);
#pragma unroll
  for (int grp = 0; grp < 4; grp++) {
    float o[4][4];
#pragma unroll
    for (int L = 0; L < 4; L++) {
      mma1688z(o[L], p[NT][0], p[NT][1], L == 0 ? vm[grp].x : L == 1 ? vm[grp].y : L == 2 ? vm[grp].z : vm[grp].w);
#pragma unroll
      for (int kh = 0; kh <= HF; kh++) {
        const uint4 w = vf[kh][(grp >> 1) * 4 + L]; const uint32_t A[4] = {p[2 * kh][0], p[2 * kh][1], p[2 * kh + 1][0], p[2 * kh + 1][1]};
        if (grp & 1) mma16816(o[L], A, w.z, w.w); else mma16816(o[L], A, w.x, w.y);
      }
    }
    op[2 * grp] = make_uint4(pack_bf16(o[0][0] * s0, o[0][1] * s0), pack_bf16(o[1][0] * s0, o[1][1] * s0), pack_bf16(o[2][0] * s0, o[2][1] * s0), pack_bf16(o[3][0] * s0, o[3][1] * s0));
    op[2 * grp + 1] = make_uint4(pack_bf16(o[0][2] * s1, o[0][3] * s1), pack_bf16(o[1][2] * s1, o[1][3] * s1), pack_bf16(o[2][2] * s1, o[2][3] * s1), pack_bf16(o[3][2] * s1, o[3][3] * s1));
  }
}

DEVINL void gemm_consumer(uint32_t sb, uint32_t px, int wg, int pr, int rank, const ArgsA& args) {
  const int lane = opaque(threadIdx.x & 31), w = __reduce_max_sync(~0u, (threadIdx.x >> 5) & 3);
  const bool lead = lane == 0 && w == 0;
  const int rot5 = pr % 5;
  if (wg == 1) bar_arrive(BAR_T, 256);
  if (threadIdx.x == 0) LOG(64 + pr * 2 + rank, 250);
#pragma unroll 1
  for (int tile = wg; tile < 32; tile += 2) {
    float acc[64];
    gemm_tile<128, 5, true>(acc, sb, px, wg, tile * 5, rot5, lead, tile < 2 ? 0 : -1);
    if (tile >= 30 && lead) mbar_arrive(sb + S_BAR + B_WD);
    char* dst = g_kv + (size_t)((tile * 2 + (w >> 1)) * 32 + pr) * 16384 + (w & 1) * 2048 + lane * 16;
    if (rank == 0) {
#pragma unroll
      for (int G = 0; G < 4; G++)
#pragma unroll
        for (int hh = 0; hh < 2; hh++) {
          const float* a = acc + 32 * (G >> 1) + 8 * (G & 1) + 2 * hh;
          *(uint4*)(dst + (G >> 1) * 12288 + hh * 1024 + (G & 1) * 512) = make_uint4(pack_bf16(a[0], a[1]), pack_bf16(a[16], a[17]), pack_bf16(a[4], a[5]), pack_bf16(a[20], a[21]));
        }
    } else {
#pragma unroll
      for (int i = 0; i < 8; i++) {
        const float* a = acc + (i >> 2) * 32 + (i & 3) * 4;
        *(uint4*)(dst + 4096 + (i >> 2) * 4096 + (i & 3) * 512) = make_uint4(movm(pack_bf16(a[0], a[1])), movm(pack_bf16(a[2], a[3])), movm(pack_bf16(a[16], a[17])), movm(pack_bf16(a[18], a[19])));
      }
    }
    wg_publish(wg);
    if ((threadIdx.x & 127) == 0) LOG(64 + pr * 2 + rank, tile);
  }
  if (threadIdx.x == 0) LOG(64 + pr * 2 + rank, 251);
  if (pr < 16) {
    const int h = 2 * pr + rank;
    flag_wait_warp(args.flags + F_KV + h * 32 + 16 + (lane & 1), 2);
    bool pend = false; uint4 op[8], kf[4][4], kmf[4];
#pragma unroll
    for (int i = 0; i < 16; i++) kf[i >> 2][i & 3] = ldg_cg128(g_kv + (size_t)((wg * 2 + (w >> 1)) * 32 + h) * 16384 + ((i >> 1) & 1) * 12288 + (i >> 2) * 1024 + (i & 1) * 512 + lane * 16);
#pragma unroll
    for (int i = 0; i < 8; i++) op[i] = kmf[i & 3] = make_uint4(0, 0, 0, 0);
#pragma unroll 1
    for (int tile = wg; tile < 32; tile += 2) {
      const uint32_t seg = tile * 2 + (w >> 1);
      const char* kvp = g_kv + (size_t)(seg * 32 + h) * 16384;
      const char* mp = g_kvm + (size_t)(seg * 32 + h) * 4096;
      bf16* orow = g_o + (size_t)(tile * 64 + w * 16 + (lane >> 2)) * 4096 + h * 128 + (lane & 3) * 8;
      if ((tile >> 1) == 6) flag_wait_warp(args.flags + F_KV + h * 32 + 30 + (lane & 1), 2);
      float acc[64];
      gemm_tile<128, 5, false>(acc, sb, px, wg, 160 + tile * 5, rot5, lead, tile < 2 ? 1 : -1);
      if ((threadIdx.x & 127) == 96) LOG(64 + pr * 2 + rank, 64 + tile);
      if (!pend) {
        int n = 0;
        while (km_known(sb) <= seg && ++n < 16 * POLL_LIMIT) {}
        km_load(kmf, mp + lane * 16);
        km_check(kmf, mp + lane * 16, (args.layer ^ 1) << 16);
      }
      if ((threadIdx.x & 127) == 96) LOG(64 + pr * 2 + rank, 96 + tile);
      if (w & 1) attend<1>(acc, kf, kmf, op, kvp, mp, orow, lane, wg, sb, tile, pend, (args.layer ^ 1) << 16); else attend<0>(acc, kf, kmf, op, kvp, mp, orow, lane, wg, sb, tile, pend, (args.layer ^ 1) << 16);
      if (!pend) {
#pragma unroll
        for (int q = 0; q < 4; q++) { *(uint4*)(orow + q * 32) = op[2 * q]; *(uint4*)(orow + 8 * 4096 + q * 32) = op[2 * q + 1]; }
        wg_publish(wg);
      }
      if ((threadIdx.x & 127) == 0) LOG(64 + pr * 2 + rank, 32 + tile);
    }
  } else {
    const int kq = (pr - 16) >> 2, cg = 2 * (pr & 3) + rank;
#pragma unroll 1
    for (int tile = wg; tile < 32; tile += 2) {
      float acc[40];
      gemm_tile<80, 8, true>(acc, sb, px, wg, 160 + tile * 8, (pr & 3) * 2, lead, tile < 2 ? 1 : -1);
      const bool odd = lane & 1;
      bf16* dst = g_part + (size_t)(kq * 2048 + tile * 64 + w * 16 + (lane >> 2)) * 640 + cg * 80 + (lane & 1) * 8 + (lane & 2) * 2;
#pragma unroll
      for (int q = 0; q < 5; q++)
#pragma unroll
        for (int hh = 0; hh < 2; hh++) {
          const uint32_t A = pack_bf16(acc[8 * q + 2 * hh], acc[8 * q + 2 * hh + 1]), B = pack_bf16(acc[8 * q + 4 + 2 * hh], acc[8 * q + 5 + 2 * hh]);
          const uint32_t x = __shfl_xor_sync(~0u, odd ? A : B, 1);
          *(uint2*)(dst + hh * 8 * 640 + q * 16) = odd ? make_uint2(x, B) : make_uint2(A, x);
        }
      wg_publish(wg);
      if ((threadIdx.x & 127) == 0) LOG(64 + pr * 2 + rank, 32 + tile);
    }
  }
  if (wg == 0) bar_sync(BAR_T, 256);
}

DEVINL void gemm_producer(uint32_t sb, int pr, int rank, const ArgsA& args, const CUtensorMap* tq, const CUtensorMap* tk, const CUtensorMap* tv,
                          const CUtensorMap* to32, const CUtensorMap* tx, const CUtensorMap* tao) {
  const uint32_t bWF = sb + S_BAR + B_WF;
  auto load_w = [&](const CUtensorMap* tm, int col, int st) {
    const int r = ((st + pr) % 5) * 2; mbar_arrive_tx(bWF + st * 8, 32768);
#pragma unroll 1
    for (int i = 0; i < 4; i++) tma_2d(sb + (i & 1) * 81920 + (r + (i >> 1)) * 8192, tm, col + (i & 1) * 64, (r + (i >> 1)) * 64, bWF + st * 8); };
  auto att_pf = [&](int tile, int st) {
    if (tile >= 32) return;
    const int q = tile * 64 + 2 * pr + rank;
    if (st < 4) l2_prefetch(g_kv + (size_t)(q + (st >> 1) * 32) * 16384 + (st & 1) * 8192, 8192);
    else if (lds32(sb + S_BAR + B_PROG) > tile * 2 + 1) { l2_prefetch(g_kvm + (size_t)q * 4096, 4096); l2_prefetch(g_kvm + (size_t)(q + 32) * 4096, 4096); } };
  uint32_t u = 0;
  auto push = [&](const CUtensorMap* tm, int c0, int c1) {
    const uint32_t slot = u & 3, full = sb + S_BAR + B_FULL + slot * 8;
    mbar_wait(sb + S_BAR + B_EMPTY + slot * 8, ((u >> 2) & 1) ^ 1);
    mbar_arrive_tx(full, 16384);
    tma_2d_mc(sb + G_ST + slot * 16384 + rank * 8192, tm, c0 + rank * 64, c1, full);
    u++; };
#pragma unroll 1
  for (int st = 0; st < 5; st++) load_w(rank ? tv : tk, pr * 128, st);
  if (args.layer == 0) { flag_wait(args.flags + F_X, 128); fence_proxy_async(); } else pdl_wait();
#pragma unroll 1
  for (int tile = 0; tile < 32; tile++) {
    l2_prefetch((const char*)g_xn + ((tile + 2) & 31) * 81920 + (pr * 2 + rank) * 1280, 1280);
#pragma unroll 1
    for (int st = 0; st < 5; st++) {
      push(tx, ((st + pr) % 5) * 128, tile * 64);
      if (tile >= PF0 && tile < PF0 + 16) {
        const int q = (tile - PF0) * 5 + st; const char* src = (rank ? args.wo : args.wq) + (pr * 80 + q) * 2048;
        if (PFR) { if (q == 0) mbar_arrive_tx(sb + S_BAR + B_DUM, 163840); bulk_g2s(sb + S_END, src, 1024, sb + S_BAR + B_DUM); bulk_g2s(sb + S_END, src + 1024, 1024, sb + S_BAR + B_DUM); }
        else l2_prefetch(src, 2048);
      }
      if (pr < 16 && tile >= 32 - PFD) att_pf(tile + PFD - 32, st);
    }
  }
  pdl_launch();
  if (pr < 16) {
    load_w(tq, (2 * pr + rank) * 128, 0);
#pragma unroll 1
    for (int tile = 0; tile < 32; tile++) {
      if (tile < 30) l2_prefetch((const char*)g_xn + (tile + 2) * 81920 + (pr * 2 + rank) * 2560, 2560);
#pragma unroll 1
      for (int st = 0; st < 5; st++) { push(tx, ((st + pr) % 5) * 128, tile * 64); if (tile == 0 && st < 4) load_w(tq, (2 * pr + rank) * 128, st + 1); att_pf(tile + PFD, st); }
    }
  } else {
    const int kq = (pr - 16) >> 2, cg = 2 * (pr & 3) + rank;
    mbar_wait(sb + S_BAR + B_WD, 0);
    mbar_arrive_tx(bWF, 163840);
#pragma unroll 1
    for (int i = 0; i < 20; i++) { tma_2d(sb + (i % 5) * 32768 + (i / 5) * 8192, to32, cg * 80 + (i % 5) * 16, kq * 1024 + (i / 5) * 256, bWF); __nanosleep(OPACE); }
#pragma unroll 1
    for (int tile = 0; tile < 32; tile++) {
      flag_wait(args.flags + F_O + tile * 4 + kq, 8);
      fence_proxy_async();
#pragma unroll 1
      for (int st = 0; st < 8; st++) push(tao, kq * 1024 + ((st + (pr & 3) * 2) & 7) * 128, tile * 64);
    }
  }
  if (PFR) mbar_wait(sb + S_BAR + B_DUM, 0);
#pragma unroll 1
  for (int i = 0; i < 4; i++, u++) mbar_wait(sb + S_BAR + B_EMPTY + (u & 3) * 8, ((u >> 2) & 1) ^ 1);
}

DEVINL void gemm_publisher(int wg, int pr, int rank, const ArgsA& args) {
#pragma unroll 1
  for (int i = 0; i < 32; i++) {
    const int tile = (i & 15) * 2 + wg;
    bar_sync(BAR_G + wg, 160);
    if ((threadIdx.x & 31) == 0) {
      flag_add(args.flags + (i < 16 ? F_KV + pr * 32 + tile : pr < 16 ? F_O + tile * 4 + (pr >> 2) : F_P + tile * 32));
    }
    __syncwarp();
  }
}

DEVINL void filter_prep(uint32_t* sm, int part, const ArgsA& args) {
  const int tid = threadIdx.x, lane = tid & 31, w = tid >> 5;
  const unsigned short* wr = (const unsigned short*)args.wr; const unsigned short* wi = (const unsigned short*)args.wi;
#pragma unroll 1
  for (int it = part; it < 32; it += 4) {
#pragma unroll 1
    for (int rr = 0; rr < 8; rr += 2) {
      uint32_t a[2][11], b[2][11];
#pragma unroll
      for (int r = 0; r < 2; r++) {
        const int pos = it * 64 + w * 8 + rr + r, th = (pos >> 2) & 127, v = (pos >> 9) * 4 + (pos & 3);
        const int o = ((th >> 3) + 16 * ((th & 7) + (v & 8)) + 256 * (v & 7)) * 321 + lane;
#pragma unroll
        for (int c = 0; c < 11; c++) if (c < 10 || lane == 0) { a[r][c] = wr[o + c * 32]; b[r][c] = wi[o + c * 32]; }
      }
#pragma unroll
      for (int r = 0; r < 2; r++)
#pragma unroll
        for (int c = 0; c < 11; c++) if (c < 10 || lane == 0) sm[(c * 32 + lane) * 65 + w * 8 + rr + r] = a[r][c] | (b[r][c] << 16);
    }
    bar_sync(1, 256);
#pragma unroll 2
    for (int i = tid; i < 64 * 321; i += 256) g_wt[(i >> 6) * 2048 + it * 64 + (i & 63)] = sm[(i >> 6) * 65 + (i & 63)];
    bar_sync(1, 256);
  }
}

__global__ void __cluster_dims__(2, 1, 1) __launch_bounds__(384, 1)
layer_a_kernel(const __grid_constant__ CUtensorMap tq, const __grid_constant__ CUtensorMap tk, const __grid_constant__ CUtensorMap tv,
               const __grid_constant__ CUtensorMap to, const __grid_constant__ CUtensorMap to32, const __grid_constant__ CUtensorMap tx,
               const __grid_constant__ CUtensorMap tao, const __grid_constant__ ArgsA args) {
  extern __shared__ __align__(1024) char smraw[];
  const uint32_t sb = (smem_u32(smraw) + 1023) & ~1023u;
  uint32_t rank; asm volatile("mov.u32 %0, %%cluster_ctarank;" : "=r"(rank));
  rank = __reduce_max_sync(~0u, rank);
  const uint32_t px = __reduce_max_sync(~0u, mapa(sb, rank ^ 1) - sb);
  if (args.layer == 0) LOGK(0, 0);
  uint32_t smid; asm volatile("mov.u32 %0, %%smid;" : "=r"(smid));
  const uint32_t b = sb + S_BAR;
  if (threadIdx.x == 320) {
    mbar_init(b + B_W, 1); mbar_init(b + B_W2, 1); mbar_init(b + B_WV, 1); mbar_init(b + B_WO, 1); mbar_init(b + B_S, 9); mbar_init(b + B_KV, 1); mbar_init(b + B_KV + 8, 1);
    for (int i = 0; i < 4; i++) { mbar_init(b + B_FULL + i * 8, 1); mbar_init(b + B_EMPTY + i * 8, 2); }
    for (int i = 0; i < 5; i++) mbar_init(b + B_WF + i * 8, 1);
    mbar_init(b + B_WD, 2); mbar_init(b + B_RB, 1); mbar_init(b + B_DUM, 1); sts32(b + B_PROG, 0);
    mbar_arrive_tx(b + B_RB, 8);
    asm volatile("fence.mbarrier_init.release.cluster;" ::: "memory");
  }
  __syncwarp();
  asm volatile("barrier.cluster.arrive.relaxed.aligned;" ::: "memory");
  uint32_t role = 0; uint4 xr[5];
  const bool ln = args.layer == 0 && blockIdx.x < 128 && threadIdx.x < 256;
  const size_t off = (size_t)(blockIdx.x * 16 + (threadIdx.x >> 4)) * 640 + (threadIdx.x & 15) * 8;
#pragma unroll
  for (int i = 0; i < 5; i++) xr[i] = ldg128_if(args.x + off + i * 128, ln);
  if (rank == 0 && threadIdx.x >= 256 && threadIdx.x < 320) {
    if (args.layer == 0) {
      uint32_t* p = (uint32_t*)(args.comm + 0x20000 + (threadIdx.x < 288 ? 0x1000 : 0) + (blockIdx.x >> 1) * 32);
      if ((threadIdx.x & 31) < 8) p[threadIdx.x & 31] = 0;
      __syncwarp();
      if ((threadIdx.x & 31) == 0) {
        uint32_t v, best = ~0u;
#pragma unroll 1
        for (int i = 0; i < NPROBE; i++) { const uint32_t t0 = clk(); asm volatile("atom.relaxed.gpu.global.add.u32 %0, [%1], 1;" : "=r"(v) : "l"(p) : "memory"); asm volatile("st.volatile.shared.u32 [%0], %1;" ::"r"(b + 216), "r"(v) : "memory"); best = min(best, clk() - t0); }
        sts32(b + 208 + ((threadIdx.x >> 5) & 1) * 4, best);
      }
      bar_sync(1, 64);
    }
    if (threadIdx.x == 256) {
      int d;
      if (args.layer == 0) { d = (int)(lds32(b + 208) - lds32(b + 212)); g_side[smid & 254] = d; g_side[(smid & 254) + 1] = d; } else d = g_side[smid & 255];
      uint32_t* cnt = args.flags + F_ROLE;
      if (d < 0) { role = atomicAdd(cnt, 1); if (role >= 32) role = 32 + atomicAdd(cnt + 1, 1); }
      else { role = 32 + atomicAdd(cnt + 1, 1); if (role >= 66) role = atomicAdd(cnt, 1); }
    }
    __syncwarp();
  }
  asm volatile("barrier.cluster.wait.aligned;" ::: "memory");
  if (rank == 0 && threadIdx.x == 256) { stasync64(b + B_ROLE, role, 0, b + B_RB); stasync64(b + B_ROLE + px, role, 0, b + B_RB + px); }
  if (ln) {
    float f[40];
#pragma unroll
    for (int i = 0; i < 5; i++) unpack8(xr[i], f + 8 * i);
    ln_row(f);
#pragma unroll
    for (int i = 0; i < 5; i++) *(uint4*)(g_xn + off + i * 128) = pack8(f + 8 * i);
    bar_sync(2, 256);
    if (threadIdx.x == 0) flag_add(args.flags + F_X);
  }
  __syncwarp();
  mbar_wait(b + B_RB, 0);
  role = __reduce_max_sync(~0u, lds32(b + B_ROLE));
  if (threadIdx.x == 352 && args.layer == 0) g_role[smid & 255] = role * 2 + rank;
  if (role != 32) pdl_launch();
  const int wg = __reduce_max_sync(~0u, threadIdx.x >> 7);
  auto U = [](uint32_t x) { return __reduce_max_sync(~0u, opaque(x)); };
  if (wg < 2) {
    asm volatile("setmaxnreg.inc.sync.aligned.u32 224;");
    if (role >= 32) {
      if (role >= 64) { if (args.layer == 0) { filter_prep((uint32_t*)smraw, (role - 64) * 2 + rank, args); if (threadIdx.x == 0) LOG(role * 2 + rank, 0); } }
      else gemm_consumer(U(sb), U(px), U(wg), U(role - 32), U(rank), args);
    } else { if (wg == 0) chain_mma<0>(sb, args); else chain_mma<1>(sb, args); }
  } else {
    asm volatile("setmaxnreg.dec.sync.aligned.u32 56;");
    if (role >= 32) {
      if (role < 64) {
        if (threadIdx.x == 256) gemm_producer(sb, role - 32, rank, args, &tq, &tk, &tv, &to32, &tx, &tao);
        else if (threadIdx.x >= 288 && threadIdx.x < 352) gemm_publisher((threadIdx.x >> 5) - 9, role - 32, rank, args);
        else if (threadIdx.x == 352 && role < 48) km_watcher(sb, args.flags + F_KM + (2 * (role - 32) + rank) * 32);
      }
    } else chain_helper(U(sb), U(px), U(role), U(rank), args, &tq, &tk, &tv, &to);
  }
}

DEVINL float2 cadd(float2 a, float2 b) { return make_float2(a.x + b.x, a.y + b.y); }
DEVINL float2 csub(float2 a, float2 b) { return make_float2(a.x - b.x, a.y - b.y); }
DEVINL float2 cmul(float2 a, float2 b) { return make_float2(fmaf(a.x, b.x, -a.y * b.y), fmaf(a.x, b.y, a.y * b.x)); }
DEVINL float2 cmulc(float2 a, float2 b) { return make_float2(fmaf(a.x, b.x, a.y * b.y), fmaf(a.y, b.x, -a.x * b.y)); }
template <int INV> DEVINL float2 ctw(float2 a, float2 w) { return INV ? cmulc(a, w) : cmul(a, w); }
template <int INV> DEVINL float2 rot(float2 a) { return INV ? make_float2(-a.y, a.x) : make_float2(a.y, -a.x); }
template <int INV> DEVINL void fft4(float2& a, float2& b, float2& c, float2& d) {
  const float2 s0 = cadd(a, c), d0 = csub(a, c), s1 = cadd(b, d), d1 = rot<INV>(csub(b, d));
  a = cadd(s0, s1); b = cadd(d0, d1); c = csub(s0, s1); d = csub(d0, d1);
}
template <int INV> DEVINL float2 w8(float2 a) { const float h = 0.70710678118654752f; const float2 r = rot<INV>(a); return make_float2((a.x + r.x) * h, (a.y + r.y) * h); }
template <int INV> DEVINL void fft8(float2* x) {
  fft4<INV>(x[0], x[2], x[4], x[6]); fft4<INV>(x[1], x[3], x[5], x[7]);
  const float2 e0 = x[0], e1 = x[2], e2 = x[4], e3 = x[6], o0 = x[1], o1 = w8<INV>(x[3]), o2 = rot<INV>(x[5]), o3 = rot<INV>(w8<INV>(x[7]));
  x[0] = cadd(e0, o0); x[1] = cadd(e1, o1); x[2] = cadd(e2, o2); x[3] = cadd(e3, o3);
  x[4] = csub(e0, o0); x[5] = csub(e1, o1); x[6] = csub(e2, o2); x[7] = csub(e3, o3);
}
template <int INV> DEVINL void fft16(float2* x) {
  const float c = 0.92387953251128674f, s = 0.38268343236508977f;
  const float2 w1 = make_float2(c, -s), w3 = make_float2(s, -c);
#pragma unroll
  for (int i = 0; i < 4; i++) fft4<INV>(x[i], x[i + 4], x[i + 8], x[i + 12]);
  x[5] = ctw<INV>(x[5], w1); x[9] = w8<INV>(x[9]); x[13] = ctw<INV>(x[13], w3);
  x[6] = w8<INV>(x[6]); x[10] = rot<INV>(x[10]); x[14] = rot<INV>(w8<INV>(x[14]));
  x[7] = ctw<INV>(x[7], w3); x[11] = rot<INV>(w8<INV>(x[11])); x[15] = ctw<INV>(x[15], make_float2(-c, s));
#pragma unroll
  for (int k = 0; k < 4; k++) fft4<INV>(x[4 * k], x[4 * k + 1], x[4 * k + 2], x[4 * k + 3]);
#pragma unroll
  for (int k = 0; k < 4; k++)
#pragma unroll
    for (int m = k + 1; m < 4; m++) { const float2 t = x[4 * k + m]; x[4 * k + m] = x[4 * m + k]; x[4 * m + k] = t; }
}
template <int INV> DEVINL void fft5(float2& x0, float2& x1, float2& x2, float2& x3, float2& x4) {
  const float c1 = 0.30901699437494742f, c2 = -0.80901699437494742f, s1 = 0.95105651629515357f, s2 = 0.58778525229247313f;
  const float2 a1 = cadd(x1, x4), a2 = cadd(x2, x3), b1 = rot<INV>(csub(x1, x4)), b2 = rot<INV>(csub(x2, x3));
  const float2 p1 = make_float2(fmaf(c1, a1.x, fmaf(c2, a2.x, x0.x)), fmaf(c1, a1.y, fmaf(c2, a2.y, x0.y)));
  const float2 p2 = make_float2(fmaf(c2, a1.x, fmaf(c1, a2.x, x0.x)), fmaf(c2, a1.y, fmaf(c1, a2.y, x0.y)));
  const float2 q1 = make_float2(fmaf(s1, b1.x, s2 * b2.x), fmaf(s1, b1.y, s2 * b2.y));
  const float2 q2 = make_float2(fmaf(s2, b1.x, -s1 * b2.x), fmaf(s2, b1.y, -s1 * b2.y));
  x0 = cadd(x0, cadd(a1, a2)); x1 = cadd(p1, q1); x4 = csub(p1, q1); x2 = cadd(p2, q2); x3 = csub(p2, q2);
}
template <int INV> DEVINL void fft20(const float2* in, float2* out) {
  float2 t[4][5];
#pragma unroll
  for (int a = 0; a < 4; a++) {
#pragma unroll
    for (int b = 0; b < 5; b++) t[a][b] = in[(5 * a + 4 * b) % 20];
    fft5<INV>(t[a][0], t[a][1], t[a][2], t[a][3], t[a][4]);
  }
#pragma unroll
  for (int d = 0; d < 5; d++) {
    fft4<INV>(t[0][d], t[1][d], t[2][d], t[3][d]);
#pragma unroll
    for (int c = 0; c < 4; c++) out[(5 * c + 16 * d) % 20] = t[c][d];
  }
}
constexpr int ZP = 336;
struct RowSmem { float2 T[320 * 17]; uint32_t Z[16 * ZP]; float2 tw[320]; float2 tp[160]; };
DEVINL float2 cis(int k, int n) {
  float sn, cs; __sincosf((float)(2 * k > n ? k - n : k) * (-6.283185307179586f / (float)n), &sn, &cs); return make_float2(cs, sn);
}
DEVINL void row_tables(RowSmem& sm) {
  const int t = threadIdx.x;
  sm.tw[t] = cis((t >> 4) * (t & 15), 320);
  if (t < 160) sm.tp[t] = cis(t, 640);
}

#define WCH 16384
#define WST 2
#define CUNR 1
#define CDRY 0
#define RDRY 1

__global__ void __launch_bounds__(320, 1) rows_fwd_kernel(const bf16* __restrict__ xin, const uint32_t* flags) {
  extern __shared__ __align__(1024) char smraw[]; RowSmem& sm = *(RowSmem*)smraw;
  const int tid = threadIdx.x, s0 = blockIdx.x * 16, wp = __reduce_max_sync(~0u, tid >> 5);
  const uint32_t* flag = flags + F_P + (blockIdx.x >> 2) * 32;
  LOGK(1 + 3 * (xin == g_x), 0);
  if (tid == 0) l2_prefetch(xin + s0 * 640, 20480);
  row_tables(sm);
#pragma unroll 1
  for (int live = !RDRY || wp != 1 || __any_sync(~0u, ldg_rlx32(flag) >= 32); live < 2; live++) {
    if (live) {
      if (wp == 0) { uint32_t v; int n = 0;
        while (true) { asm volatile("ld.acquire.gpu.global.u32 %0, [%1];" : "=r"(v) : "l"(flag) : "memory"); if (__all_sync(~0u, v >= 32 || ++n >= 8 * POLL_LIMIT)) break; __nanosleep(v ? 20 : 200); } }
      __syncthreads();
      pdl_launch();
      LOGK(1 + 3 * (xin == g_x), 1);
    }
    if (wp < 8) {
      const int row = tid >> 4, j = tid & 15; const size_t off = (size_t)(s0 + row) * 640 + j * 8;
      float f[40]; uint4 in[5][5];
#pragma unroll
      for (int i = 0; i < 5; i++) {
#pragma unroll
        for (int q = 0; q < 4; q++) in[i][q] = ldg128_if(g_part + q * 2048 * 640 + off + i * 128, live);
        in[i][4] = ldg128_if(xin + off + i * 128, live);
      }
#pragma unroll
      for (int i = 0; i < 5; i++) {
        float a[8], b[8], c[8], d[8];
        unpack8(in[i][0], a); unpack8(in[i][1], b); unpack8(in[i][2], c); unpack8(in[i][3], d);
#pragma unroll
        for (int e = 0; e < 8; e++) a[e] = (a[e] + b[e]) + (c[e] + d[e]);
        const uint4 o = pack8(a), x = in[i][4];
        const uint4 r = make_uint4(hadd2bf(o.x, x.x), hadd2bf(o.y, x.y), hadd2bf(o.z, x.z), hadd2bf(o.w, x.w));
        stg128_if(g_x + off + i * 128, r, live); unpack8(r, f + 8 * i);
      }
      ln_row(f);
#pragma unroll
      for (int i = 0; i < 5; i++) *(uint4*)(sm.Z + row * ZP + i * 64 + j * 4) = pack8(f + 8 * i);
      __syncwarp();
      float2 z[20], y[20];
#pragma unroll
      for (int n1 = 0; n1 < 20; n1++) { const uint32_t w = sm.Z[row * ZP + n1 * 16 + j]; z[n1] = make_float2(bf_lo(w), bf_hi(w)); }
      fft20<0>(z, y);
#pragma unroll
      for (int k1 = 0; k1 < 20; k1++) sm.T[(k1 * 16 + j) * 17 + row] = k1 ? cmul(y[k1], sm.tw[k1 * 16 + j]) : y[0];
    }
    if (live) __syncthreads();
    const int up = (tid >> 4) & 1, row = tid & 15, k1 = wp ? (up ? 20 - wp : wp) : up * 10;
    float2 x[16];
#pragma unroll
    for (int n2 = 0; n2 < 16; n2++) x[n2] = sm.T[(k1 * 16 + n2) * 17 + row];
    fft16<0>(x);
    uint32_t* ya = g_y + s0 + row + k1 * 2048; uint32_t* yb = g_y + s0 + row + (320 - k1) * 2048;
    stg32_if(g_y + s0 + row + 160 * 2048, pack_f16(2.f * x[8].x, -2.f * x[8].y), live && k1 == 0);
    const int src = (tid & 31) ^ (wp ? 16 : 0);
#pragma unroll
    for (int k2 = 0; k2 < 8; k2++) {
      const float2 c = k1 ? x[15 - k2] : x[(16 - k2) & 15], b = make_float2(__shfl_sync(~0u, c.x, src), __shfl_sync(~0u, c.y, src)), a = x[k2];
      const float2 E = make_float2(a.x + b.x, a.y - b.y), O = cmul(make_float2(a.y + b.y, b.x - a.x), sm.tp[k1 + 20 * k2]);
      stg32_if(ya + k2 * 20 * 2048, pack_f16(E.x + O.x, E.y + O.y), live); stg32_if(yb - k2 * 20 * 2048, pack_f16(E.x - O.x, O.y - E.y), live);
    }
  }
  LOGK(1 + 3 * (xin == g_x), 2);
  if (blockIdx.x == gridDim.x - 1) pdl_wait();
}

__global__ void __launch_bounds__(384) cols_kernel(int layer) {
  extern __shared__ __align__(1024) char smraw[];
  const int sub = threadIdx.x >> 7, tid = threadIdx.x & 127, col = blockIdx.x * 3 + sub, k1 = tid >> 3, j0 = tid & 7;
  float2* sm = (float2*)smraw + sub * (16 * 152);
  float2* tw = (float2*)smraw + 3 * 16 * 152;
  LOGK(2 + 3 * layer, 0);
  pdl_launch();
  uint32_t* y = g_y + col * 2048 + tid;
  if (tid < 2) l2_prefetch((tid ? g_wt : g_y) + col * 2048, 8192);
#pragma unroll 1
  for (int i = threadIdx.x; i < 2176; i += 384) {
    const int a = i < 2048 ? i >> 7 : (i - 2048) >> 3, b = i < 2048 ? i & 127 : i & 7;
    tw[i < 2048 ? a * 136 + b : 2176 + a * 9 + b] = cis(i < 2048 ? a * b : a * b * 16, 2048);
  }
  float2* reg = sm + k1 * 152;
  uint4 wf[4];
#pragma unroll
  for (int q = 0; q < 4; q++) {
    const int live = q >= 0, it = live ? q : q == -3 ? 0 : q == -2 ? 1 : 3;
    float2 x[16];
    if (it == 0) {
      if (live) { __syncthreads(); pdl_wait(); LOGK(2 + 3 * layer, 1); }
#pragma unroll
      for (int i = 0; i < 16; i++) { const uint32_t w = ldg32_if(y + i * 128, live); x[i] = __half22float2(*(const __half2*)&w); }
#pragma unroll
      for (int i = 0; i < 4; i++) wf[i] = ldg128_if(g_wt + col * 2048 + i * 512 + tid * 4, live);
    } else {
      const float2* in = it == 3 ? sm + tid : reg + j0; const int is = it == 1 ? 8 : it == 2 ? 9 : 152;
#pragma unroll
      for (int i = 0; i < 16; i++) x[i] = in[i * is];
    }
    fft16<0>(x);
    if (it == 3) {
      const float sc = 1.f / 4096.f;
#pragma unroll
      for (int i = 0; i < 16; i++) stg32_if(y + i * 128, pack_bf16(x[i].y * sc, x[i].x * sc), live);
    } else {
      const float2* t = it == 0 ? tw + tid : it == 1 ? tw + 2176 + j0 : tw + k1 * 136 + j0; const int ts = it == 0 ? 136 : it == 1 ? 9 : 8;
      float2* o = it == 0 ? sm + tid : reg + j0; const int os = it == 0 ? 152 : it == 1 ? 9 : 8;
      __syncwarp();
#pragma unroll
      for (int k = 0; k < 16; k++) o[k * os] = (CUNR && k == 0 && it < 2) ? x[0] : cmul(x[k], t[k * ts]);
      if (it == 1) {
        __syncwarp();
        float2* r9 = reg + j0 * 9;
#pragma unroll
        for (int i = 0; i < 16; i++) x[i] = r9[(i & 8) * 9 + (i & 7)];
#pragma unroll
        for (int h = 0; h < 2; h++) {
          fft8<0>(x); fft8<0>(x + 8);
          if (h == 0) {
#pragma unroll
            for (int i = 0; i < 16; i++) {
              const uint32_t w = (i & 3) == 0 ? wf[i >> 2].x : (i & 3) == 1 ? wf[i >> 2].y : (i & 3) == 2 ? wf[i >> 2].z : wf[i >> 2].w;
              const float2 v = cmul(x[i], make_float2(bf_lo(w), bf_hi(w))); x[i] = make_float2(v.y, v.x);
            }
          }
        }
        const float2* t9 = tw + 2176 + j0 * 9;
#pragma unroll
        for (int i = 0; i < 16; i++) r9[(i & 8) * 9 + (i & 7)] = (i & 7) ? cmul(x[i], t9[(i & 8) * 9 + (i & 7)]) : x[i];
        __syncwarp();
      } else if (live) bar_sync(sub + 1, 128);
    }
  }
  LOGK(2 + 3 * layer, 2);
}

__global__ void __launch_bounds__(352) rows_inv_kernel(bf16* __restrict__ xout, int do_ln, const __grid_constant__ Wts w) {
  extern __shared__ __align__(1024) char smraw[]; RowSmem& sm = *(RowSmem*)smraw;
  const int tid = threadIdx.x, s0 = blockIdx.x * 16, wp = __reduce_max_sync(~0u, tid >> 5);
  LOGK(3 + 3 * !do_ln, 0);
  const uint32_t ctl = smem_u32(smraw) + 72 * 1024;
  if (tid == 0) sts32(ctl + 8, 0);
  __syncthreads();
  if (wp == 10) { if (WCH && do_ln && tid == 320) weight_warm<WCH ? WCH : 16>(w, ctl + 1024, ctl, ctl + 8); return; }
  if (tid == 0) l2_prefetch(g_x + s0 * 640, 20480);
  row_tables(sm);
  const size_t off = (size_t)(s0 + ((tid >> 4) & 15)) * 640 + (tid & 15) * 8;
#pragma unroll 1
  for (int live = !RDRY || wp != 1; live < 2; live++) {
    if (live) {
      bar_sync(1, 320);
      pdl_wait();
      pdl_launch();
      if (WST == 0 && tid == 0) sts32(ctl + 8, 1);
      LOGK(3 + 3 * !do_ln, 1);
    }
    uint4 xr[5];
    {
      const int up = (tid >> 4) & 1, row = tid & 15, k1 = wp ? (up ? 20 - wp : wp) : up * 10;
      const uint32_t* ya = g_y + s0 + row + k1 * 2048; const uint32_t* yb = g_y + s0 + row + (320 - k1) * 2048;
      uint32_t wa[8], wb[8];
#pragma unroll
      for (int k2 = 0; k2 < 8; k2++) { wa[k2] = ldg32_if(ya + k2 * 20 * 2048, live); wb[k2] = ldg32_if(yb - k2 * 20 * 2048, live); }
      const uint32_t wm = ldg32_if(g_y + s0 + row + 160 * 2048, live && k1 == 0);
#pragma unroll
      for (int i = 0; i < 5; i++) xr[i] = ldg128_if(g_x + off + i * 128, live && wp < 8);
      stg32_if(g_flags + blockIdx.x * 320 + tid, 0, live && !do_ln && blockIdx.x * 320 + tid < 2 * F_LAYER);
      if (k1 == 0) { wa[0] &= 0xffffu; wb[0] &= 0xffffu; }
      float2 x[16], r[8];
#pragma unroll
      for (int k2 = 0; k2 < 8; k2++) {
        const float2 a = make_float2(bf_lo(wa[k2]), bf_hi(wa[k2])), b = make_float2(bf_lo(wb[k2]), bf_hi(wb[k2]));
        const float2 E = make_float2(a.x + b.x, a.y - b.y), O = cmulc(make_float2(a.x - b.x, a.y + b.y), sm.tp[k1 + 20 * k2]);
        x[k2] = make_float2(E.x - O.y, E.y + O.x); r[k2] = make_float2(E.x + O.y, O.x - E.y);
      }
      if (k1 == 0) r[0] = make_float2(2.f * bf_lo(wm), -2.f * bf_hi(wm));
      const int src = (tid & 31) ^ (wp ? 16 : 0);
#pragma unroll
      for (int i = 8; i < 16; i++) { const float2 c = k1 ? r[15 - i] : r[(16 - i) & 7]; x[i] = make_float2(__shfl_sync(~0u, c.x, src), __shfl_sync(~0u, c.y, src)); }
      fft16<1>(x);
#pragma unroll
      for (int n2 = 0; n2 < 16; n2++) sm.T[(k1 * 16 + n2) * 17 + row] = x[n2];
    }
    if (live) { bar_sync(1, 320); if (WST == 1 && tid == 0) sts32(ctl + 8, 1); }
    if (wp < 8) {
      const int row = tid >> 4, n2 = tid & 15;
      float2 z[20], y[20];
#pragma unroll
      for (int k1 = 0; k1 < 20; k1++) { const float2 t = sm.T[(k1 * 16 + n2) * 17 + row]; z[k1] = k1 ? cmulc(t, sm.tw[k1 * 16 + n2]) : t; }
      fft20<1>(z, y);
      const float sc = 1.f / 640.f;
#pragma unroll
      for (int n1 = 0; n1 < 20; n1++) sm.Z[row * ZP + n1 * 16 + n2] = pack_bf16(y[n1].x * sc, y[n1].y * sc);
      __syncwarp();
      if (WST == 2 && live && tid == 0) sts32(ctl + 8, 1);
      float f[40];
#pragma unroll
      for (int i = 0; i < 5; i++) {
        const uint4 o = *(const uint4*)(sm.Z + row * ZP + i * 64 + n2 * 4), x = xr[i];
        const uint4 r = make_uint4(hadd2bf(o.x, x.x), hadd2bf(o.y, x.y), hadd2bf(o.z, x.z), hadd2bf(o.w, x.w));
        stg128_if(xout + off + i * 128, r, live); unpack8(r, f + 8 * i);
      }
      if (do_ln) {
        ln_row(f);
#pragma unroll
        for (int i = 0; i < 5; i++) stg128_if(g_xn + off + i * 128, pack8(f + 8 * i), live);
      }
    }
  }
  LOGK(3 + 3 * !do_ln, 2);
}

typedef CUresult (*EncFn)(CUtensorMap*, CUtensorMapDataType, cuuint32_t, void*, const cuuint64_t*, const cuuint64_t*, const cuuint32_t*, const cuuint32_t*,
                          CUtensorMapInterleave, CUtensorMapSwizzle, CUtensorMapL2promotion, CUtensorMapFloatOOBfill);
static void make_map(EncFn fn, CUtensorMap* m, const void* p, uint64_t cols, uint64_t rows, uint32_t bc, uint32_t br, CUtensorMapSwizzle sw) {
  cuuint64_t gd[2] = {cols, rows}, gs[1] = {cols * 2}; cuuint32_t bd[2] = {bc, br}, es[2] = {1, 1};
  fn(m, CU_TENSOR_MAP_DATA_TYPE_BFLOAT16, 2, (void*)p, gd, gs, bd, es, CU_TENSOR_MAP_INTERLEAVE_NONE, sw, CU_TENSOR_MAP_L2_PROMOTION_L2_128B, CU_TENSOR_MAP_FLOAT_OOB_FILL_NONE);
}
template <class... P, class... A>
static void launch(void (*k)(P...), int grid, int block, int smem, bool pdl, A... a) {
  cudaLaunchConfig_t cfg = {}; cfg.gridDim = dim3(grid); cfg.blockDim = dim3(block); cfg.dynamicSmemBytes = smem; cfg.stream = cudaStreamPerThread;
  cudaLaunchAttribute at[1]; at[0].id = cudaLaunchAttributeProgrammaticStreamSerialization; at[0].val.programmaticStreamSerializationAllowed = 1;
  cfg.attrs = at; cfg.numAttrs = pdl ? 1 : 0;
  cudaLaunchKernelEx(&cfg, k, a...);
}
static const int tune_t[10] = {1480, 1765, 1795, 2070, 2230, 2505, 2570, 2815, 1950, 2619}; constexpr int dev_stop = 100, dev_pdl = 1;

extern "C" void kernel_launch(void* const* d_in, const int* in_sizes, int n_in, void* d_out, int out_size) {
  const bf16 *x = (const bf16*)d_in[0], *mem0 = (const bf16*)d_in[1], *Wq = (const bf16*)d_in[2], *Wk = (const bf16*)d_in[3], *Wv = (const bf16*)d_in[4], *Wo = (const bf16*)d_in[5];
  const bf16 *wr = (const bf16*)d_in[8], *wi = (const bf16*)d_in[9];
  constexpr int SM_A = S_END + 2048, SM_R = sizeof(RowSmem), SM_C = 76 * 1024, SM_I = 116 * 1024;
  void *p_xn, *p_o, *p_x, *p_comm, *p_flags, *fn; cudaDriverEntryPointQueryResult qr;
  cudaGetSymbolAddress(&p_xn, g_xn); cudaGetSymbolAddress(&p_o, g_o); cudaGetSymbolAddress(&p_x, g_x); cudaGetSymbolAddress(&p_comm, g_comm); cudaGetSymbolAddress(&p_flags, g_flags);
  cudaGetDriverEntryPoint("cuTensorMapEncodeTiled", &fn, cudaEnableDefault, &qr);
  cudaFuncSetAttribute(layer_a_kernel, cudaFuncAttributeMaxDynamicSharedMemorySize, SM_A);
  cudaFuncSetAttribute(rows_fwd_kernel, cudaFuncAttributeMaxDynamicSharedMemorySize, SM_R);
  cudaFuncSetAttribute(rows_inv_kernel, cudaFuncAttributeMaxDynamicSharedMemorySize, SM_I);
  cudaFuncSetAttribute(cols_kernel, cudaFuncAttributeMaxDynamicSharedMemorySize, SM_C);
  cudaFuncSetAttribute(rows_fwd_kernel, cudaFuncAttributePreferredSharedMemoryCarveout, 100);
  cudaFuncSetAttribute(cols_kernel, cudaFuncAttributePreferredSharedMemoryCarveout, 100);
  cudaFuncSetAttribute(rows_inv_kernel, cudaFuncAttributePreferredSharedMemoryCarveout, 100);
  CUtensorMap tq, tk, tv, to, to32, tx, tao; EncFn enc = (EncFn)fn;
  make_map(enc, &tq, Wq, 4096, 640, 64, 64, CU_TENSOR_MAP_SWIZZLE_128B); make_map(enc, &tk, Wk, 4096, 640, 64, 64, CU_TENSOR_MAP_SWIZZLE_128B);
  make_map(enc, &tv, Wv, 4096, 640, 64, 64, CU_TENSOR_MAP_SWIZZLE_128B); make_map(enc, &to, Wo, 640, 4096, 64, 64, CU_TENSOR_MAP_SWIZZLE_128B);
  make_map(enc, &to32, Wo, 640, 4096, 16, 256, CU_TENSOR_MAP_SWIZZLE_32B);
  make_map(enc, &tx, p_xn, 640, 2048, 64, 64, CU_TENSOR_MAP_SWIZZLE_128B); make_map(enc, &tao, p_o, 4096, 2048, 64, 64, CU_TENSOR_MAP_SWIZZLE_128B);
  char* comm = (char*)(((uintptr_t)p_comm + (2 << 20) - 1) & ~(uintptr_t)((2 << 20) - 1));
  const bool pdl = dev_pdl;
#define L0PDL 0
  for (int l = 0; l < 2; l++) {
    ArgsA a{x, mem0, comm, (uint32_t*)p_flags + l * F_LAYER, wr, wi, (const char*)Wq, (const char*)Wo, l, {tune_t[0], tune_t[1], tune_t[2], tune_t[3]}, {tune_t[4], tune_t[5], tune_t[6], tune_t[7]}, {tune_t[8], tune_t[9]}};
    const Wts w = {{(const char*)Wk, (const char*)Wq, (const char*)Wv, (const char*)Wo}};
    if (dev_stop > 4 * l + 0) launch(layer_a_kernel, 132, 384, SM_A, pdl && (l || L0PDL), tq, tk, tv, to, to32, tx, tao, a);
    if (dev_stop > 4 * l + 1) launch(rows_fwd_kernel, 128, 320, SM_R, pdl, l ? (const bf16*)p_x : x, (const uint32_t*)a.flags);
    if (dev_stop > 4 * l + 2) launch(cols_kernel, 107, 384, SM_C, pdl, l);
    if (dev_stop > 4 * l + 3) launch(rows_inv_kernel, 128, 352, SM_I, pdl, l ? (bf16*)d_out : (bf16*)p_x, l == 0, w);
  }
}
```

```cpp
#include <cuda_runtime.h>
#include <cuda_bf16.h>
#include <cuda_fp16.h>
#include <cuda.h>
#include <stdint.h>

typedef __nv_bfloat16 bf16;
#define DEVINL __device__ __forceinline__

__device__ __align__(1024) bf16 g_xn[2048 * 640];
__device__ __align__(1024) bf16 g_x[2048 * 640];
__device__ __align__(1024) char g_kv[64 * 32 * 16384];
__device__ __align__(1024) char g_kvm[64 * 32 * 4096];
__device__ __align__(1024) bf16 g_o[2048 * 4096];
__device__ __align__(1024) bf16 g_part[4 * 2048 * 640];
__device__ __align__(1024) uint32_t g_y[321 * 2048];
__device__ __align__(1024) uint32_t g_wt[321 * 2048];
__device__ __align__(4096) char g_comm[4 << 20];
constexpr int F_KV = 0, F_KM = 1024, F_O = F_KM + 1024, F_P = F_O + 128, F_ROLE = F_P + 32 * 32, F_X = F_ROLE + 64, F_W = F_X + 32, F_LAYER = F_W + 32;
__device__ __align__(1024) uint32_t g_flags[2 * F_LAYER];
__device__ int g_side[256];
__device__ uint32_t g_role[256];

template <int V> struct IC { static constexpr int value = V; };
template <int B, int E, class F> DEVINL void static_for(F&& f) { if constexpr (B < E) { f(IC<B>{}); static_for<B + 1, E>(f); } }

#define POLL_LIMIT (1 << 17)
DEVINL uint32_t smem_u32(const void* p) { return (uint32_t)__cvta_generic_to_shared(p); }
DEVINL uint32_t mapa(uint32_t a, uint32_t r) { uint32_t o; asm volatile("mapa.shared::cluster.u32 %0, %1, %2;" : "=r"(o) : "r"(a), "r"(r)); return o; }
DEVINL uint32_t clk() { uint32_t v; asm volatile("{.reg .b64 w; mov.u64 w, %%clock64; cvt.u32.u64 %0, w;}" : "=r"(v)::"memory"); return v; }
DEVINL void mbar_init(uint32_t bar, uint32_t cnt) { asm volatile("mbarrier.init.shared::cta.b64 [%0], %1;" ::"r"(bar), "r"(cnt) : "memory"); }
DEVINL void mbar_arrive(uint32_t bar) { asm volatile("mbarrier.arrive.shared::cta.b64 _, [%0];" ::"r"(bar) : "memory"); }
DEVINL void mbar_arrive_remote(uint32_t bar) { asm volatile("mbarrier.arrive.shared::cluster.b64 _, [%0];" ::"r"(bar) : "memory"); }
DEVINL void mbar_arrive_tx(uint32_t bar, uint32_t tx) { asm volatile("mbarrier.arrive.expect_tx.shared::cta.b64 _, [%0], %1;" ::"r"(bar), "r"(tx) : "memory"); }
DEVINL void mbar_wait(uint32_t bar, uint32_t ph) {
  asm volatile("{.reg .pred p; .reg .b32 c,q; shl.b32 c, %1, 20;\n"
               "W0: bfe.u32 q, c, 20, 1; mbarrier.try_wait.parity.shared::cta.b64 p, [%0], q; add.u32 c,c,1; @!p bra.uni W0;}" ::"r"(bar), "r"(ph) : "memory");
}
DEVINL void bar_sync(int id, int n) { asm volatile("bar.sync %0, %1;" ::"r"(id), "r"(n) : "memory"); }
DEVINL void bar_arrive(int id, int n) { asm volatile("bar.arrive %0, %1;" ::"r"(id), "r"(n) : "memory"); }
DEVINL void cluster_sync() { asm volatile("barrier.cluster.arrive.release.aligned; barrier.cluster.wait.acquire.aligned;" ::: "memory"); }
DEVINL void tma_2d(uint32_t dst, const CUtensorMap* tm, int c0, int c1, uint32_t bar) {
  asm volatile("cp.async.bulk.tensor.2d.shared::cluster.global.mbarrier::complete_tx::bytes [%0], [%1, {%2, %3}], [%4];" ::"r"(dst), "l"(tm), "r"(c0), "r"(c1), "r"(bar) : "memory");
}
DEVINL void tma_2d_mc(uint32_t dst, const CUtensorMap* tm, int c0, int c1, uint32_t bar) {
  asm volatile("cp.async.bulk.tensor.2d.shared::cluster.global.mbarrier::complete_tx::bytes.multicast::cluster [%0], [%1, {%2, %3}], [%4], %5;" ::"r"(dst), "l"(tm), "r"(c0), "r"(c1), "r"(bar), "h"((uint16_t)3) : "memory");
}
DEVINL void bulk_g2s(uint32_t dst, const void* src, uint32_t bytes, uint32_t bar) {
  asm volatile("cp.async.bulk.shared::cluster.global.mbarrier::complete_tx::bytes [%0], [%1], %2, [%3];" ::"r"(dst), "l"(src), "r"(bytes), "r"(bar) : "memory");
}
DEVINL void l2_prefetch(const void* p, uint32_t bytes) { asm volatile("cp.async.bulk.prefetch.L2.global [%0], %1;" ::"l"(p), "r"(bytes) : "memory"); }
DEVINL void fence_proxy_async() { asm volatile("fence.proxy.async.global;" ::: "memory"); }
DEVINL void ldsm4t(uint32_t* r, uint32_t a) { asm volatile("ldmatrix.sync.aligned.m8n8.x4.trans.shared.b16 {%0,%1,%2,%3}, [%4];" : "=r"(r[0]), "=r"(r[1]), "=r"(r[2]), "=r"(r[3]) : "r"(a) : "memory"); }
DEVINL void stsm4(uint32_t a, uint32_t r0, uint32_t r1, uint32_t r2, uint32_t r3) { asm volatile("stmatrix.sync.aligned.m8n8.x4.shared.b16 [%0], {%1,%2,%3,%4};" ::"r"(a), "r"(r0), "r"(r1), "r"(r2), "r"(r3) : "memory"); }
DEVINL void mma16816(float* d, const uint32_t* a, uint32_t b0, uint32_t b1) {
  asm volatile("mma.sync.aligned.m16n8k16.row.col.f32.bf16.bf16.f32 {%0,%1,%2,%3}, {%4,%5,%6,%7}, {%8,%9}, {%0,%1,%2,%3};"
               : "+f"(d[0]), "+f"(d[1]), "+f"(d[2]), "+f"(d[3]) : "r"(a[0]), "r"(a[1]), "r"(a[2]), "r"(a[3]), "r"(b0), "r"(b1));
}
DEVINL void mma16816z(float* d, const uint32_t* a, uint32_t b0, uint32_t b1) {
  asm volatile("mma.sync.aligned.m16n8k16.row.col.f32.bf16.bf16.f32 {%0,%1,%2,%3}, {%4,%5,%6,%7}, {%8,%9}, {%10,%10,%10,%10};"
               : "=f"(d[0]), "=f"(d[1]), "=f"(d[2]), "=f"(d[3]) : "r"(a[0]), "r"(a[1]), "r"(a[2]), "r"(a[3]), "r"(b0), "r"(b1), "f"(0.f));
}
DEVINL void mma1688z(float* d, uint32_t a0, uint32_t a1, uint32_t b0) {
  asm volatile("mma.sync.aligned.m16n8k8.row.col.f32.bf16.bf16.f32 {%0,%1,%2,%3}, {%4,%5}, {%6}, {%7,%7,%7,%7};"
               : "=f"(d[0]), "=f"(d[1]), "=f"(d[2]), "=f"(d[3]) : "r"(a0), "r"(a1), "r"(b0), "f"(0.f));
}
DEVINL uint32_t movm(uint32_t a) { uint32_t r; asm volatile("movmatrix.sync.aligned.m8n8.trans.b16 %0, %1;" : "=r"(r) : "r"(a)); return r; }
DEVINL uint32_t pack_bf16(float lo, float hi) { uint32_t r; asm("cvt.rn.bf16x2.f32 %0, %1, %2;" : "=r"(r) : "f"(hi), "f"(lo)); return r; }
DEVINL uint32_t pack_f16(float lo, float hi) { uint32_t r; asm("cvt.rn.f16x2.f32 %0, %1, %2;" : "=r"(r) : "f"(hi), "f"(lo)); return r; }
DEVINL float bf_lo(uint32_t w) { return __uint_as_float(w << 16); }
DEVINL float bf_hi(uint32_t w) { return __uint_as_float(w & 0xffff0000u); }
DEVINL uint32_t hadd2bf(uint32_t a, uint32_t b) { uint32_t r; asm("add.rn.bf16x2 %0, %1, %2;" : "=r"(r) : "r"(a), "r"(b)); return r; }
DEVINL uint32_t hmax2bf(uint32_t a, uint32_t b) { uint32_t r; asm("max.bf16x2 %0, %1, %2;" : "=r"(r) : "r"(a), "r"(b)); return r; }
DEVINL uint32_t lds32(uint32_t a) { uint32_t v; asm volatile("ld.shared.u32 %0, [%1];" : "=r"(v) : "r"(a) : "memory"); return v; }
DEVINL uint2 lds64(uint32_t a) { uint2 v; asm volatile("ld.shared.v2.u32 {%0,%1}, [%2];" : "=r"(v.x), "=r"(v.y) : "r"(a) : "memory"); return v; }
DEVINL uint4 lds128(uint32_t a) { uint4 v; asm volatile("ld.shared.v4.u32 {%0,%1,%2,%3}, [%4];" : "=r"(v.x), "=r"(v.y), "=r"(v.z), "=r"(v.w) : "r"(a) : "memory"); return v; }
DEVINL void sts32(uint32_t a, uint32_t v) { asm volatile("st.shared.u32 [%0], %1;" ::"r"(a), "r"(v) : "memory"); }
DEVINL void sts64(uint32_t a, uint32_t x, uint32_t y) { asm volatile("st.shared.v2.u32 [%0], {%1,%2};" ::"r"(a), "r"(x), "r"(y) : "memory"); }
DEVINL void sts128(uint32_t a, uint4 v) { asm volatile("st.shared.v4.u32 [%0], {%1,%2,%3,%4};" ::"r"(a), "r"(v.x), "r"(v.y), "r"(v.z), "r"(v.w) : "memory"); }
DEVINL void stasync64(uint32_t a, uint32_t x, uint32_t y, uint32_t bar) { asm volatile("st.async.weak.shared::cluster.mbarrier::complete_tx::bytes.v2.b32 [%0], {%1,%2}, [%3];" ::"r"(a), "r"(x), "r"(y), "r"(bar) : "memory"); }
DEVINL uint4 ldg_rlx128(const void* p) { uint4 v; asm volatile("{.reg .b64 a,b; ld.relaxed.gpu.global.v2.b64 {a,b}, [%4]; mov.b64 {%0,%1}, a; mov.b64 {%2,%3}, b;}" : "=r"(v.x), "=r"(v.y), "=r"(v.z), "=r"(v.w) : "l"(p) : "memory"); return v; }
DEVINL uint2 ldg_rlx64(const void* p) { uint2 v; asm volatile("ld.relaxed.gpu.global.v2.u32 {%0,%1}, [%2];" : "=r"(v.x), "=r"(v.y) : "l"(p) : "memory"); return v; }
DEVINL void stg_rlx64(void* p, uint32_t x, uint32_t y) { asm volatile("{.reg .b64 a; mov.b64 a, {%1,%2}; st.relaxed.gpu.global.b64 [%0], a;}" ::"l"(p), "r"(x), "r"(y) : "memory"); }
DEVINL void stg_rlx128(void* p, uint32_t x, uint32_t y, uint32_t z, uint32_t w) { asm volatile("{.reg .b64 a,b; mov.b64 a, {%1,%2}; mov.b64 b, {%3,%4}; st.relaxed.gpu.global.v2.b64 [%0], {a,b};}" ::"l"(p), "r"(x), "r"(y), "r"(z), "r"(w) : "memory"); }
DEVINL void stg_rlx32(void* p, uint32_t x) { asm volatile("st.relaxed.gpu.global.u32 [%0], %1;" ::"l"(p), "r"(x) : "memory"); }
DEVINL uint4 ldg_cg128(const void* p) { uint4 v; asm volatile("ld.global.cg.v4.u32 {%0,%1,%2,%3}, [%4];" : "=r"(v.x), "=r"(v.y), "=r"(v.z), "=r"(v.w) : "l"(p) : "memory"); return v; }
DEVINL uint32_t ldg_cg32(const void* p) { uint32_t v; asm volatile("ld.global.cg.u32 %0, [%1];" : "=r"(v) : "l"(p) : "memory"); return v; }
DEVINL uint32_t ldg32_if(const void* p, int on) { uint32_t v; asm volatile("{.reg .pred q; setp.ne.s32 q, %2, 0; mov.u32 %0, 0; @q ld.global.cg.u32 %0, [%1];}" : "=r"(v) : "l"(p), "r"(on) : "memory"); return v; }
DEVINL uint4 ldg128_if(const void* p, int on) { uint4 v; asm volatile("{.reg .pred q; setp.ne.s32 q, %5, 0; mov.u32 %0, 0; mov.u32 %1, 0; mov.u32 %2, 0; mov.u32 %3, 0; @q ld.global.cg.v4.u32 {%0,%1,%2,%3}, [%4];}" : "=r"(v.x), "=r"(v.y), "=r"(v.z), "=r"(v.w) : "l"(p), "r"(on) : "memory"); return v; }
DEVINL void stg32_if(void* p, uint32_t v, int on) { asm volatile("{.reg .pred q; setp.ne.s32 q, %2, 0; @q st.global.u32 [%0], %1;}" ::"l"(p), "r"(v), "r"(on) : "memory"); }
DEVINL void stg128_if(void* p, uint4 v, int on) { asm volatile("{.reg .pred q; setp.ne.s32 q, %5, 0; @q st.global.v4.u32 [%0], {%1,%2,%3,%4};}" ::"l"(p), "r"(v.x), "r"(v.y), "r"(v.z), "r"(v.w), "r"(on) : "memory"); }
DEVINL uint4 ldg_na128(const void* p) { uint4 v; asm volatile("ld.global.L1::no_allocate.v4.u32 {%0,%1,%2,%3}, [%4];" : "=r"(v.x), "=r"(v.y), "=r"(v.z), "=r"(v.w) : "l"(p) : "memory"); return v; }
DEVINL uint4 ldg_ef128(const void* p) { uint4 v; asm volatile("ld.global.L1::evict_first.v4.u32 {%0,%1,%2,%3}, [%4];" : "=r"(v.x), "=r"(v.y), "=r"(v.z), "=r"(v.w) : "l"(p) : "memory"); return v; }
DEVINL uint4 ldg_ca128(const void* p) { uint4 v; asm volatile("ld.global.ca.v4.u32 {%0,%1,%2,%3}, [%4];" : "=r"(v.x), "=r"(v.y), "=r"(v.z), "=r"(v.w) : "l"(p) : "memory"); return v; }
DEVINL uint32_t ldg_ca32(const void* p) { uint32_t v; asm volatile("ld.global.ca.u32 %0, [%1];" : "=r"(v) : "l"(p) : "memory"); return v; }
DEVINL void flag_wait(const uint32_t* p, uint32_t want) {
  uint32_t v;
#pragma unroll 1
  for (int n = 0; n < POLL_LIMIT; n++) { asm volatile("ld.acquire.gpu.global.u32 %0, [%1];" : "=r"(v) : "l"(p) : "memory"); if (v >= want) break; __nanosleep(40); }
}
DEVINL void flag_wait_warp(const uint32_t* p, uint32_t want) {
  uint32_t v; int n = 0;
  do { asm volatile("ld.acquire.gpu.global.u32 %0, [%1];" : "=r"(v) : "l"(p) : "memory"); } while (__any_sync(~0u, v < want && ++n < POLL_LIMIT));
}
DEVINL void flag_add(uint32_t* p) { asm volatile("red.release.gpu.global.add.u32 [%0], 1;" ::"l"(p) : "memory"); }
DEVINL void flag_set(uint32_t* p, uint32_t v) { asm volatile("fence.acq_rel.gpu; st.relaxed.gpu.global.u32 [%0], %1;" ::"l"(p), "r"(v) : "memory"); }
DEVINL uint32_t ldg_rlx32(const void* p) { uint32_t v; asm volatile("ld.relaxed.gpu.global.u32 %0, [%1];" : "=r"(v) : "l"(p) : "memory"); return v; }
DEVINL float ex2(float x) { float y; asm("ex2.approx.ftz.f32 %0, %1;" : "=f"(y) : "f"(x)); return y; }
DEVINL float rcp(float x) { float y; asm("rcp.approx.ftz.f32 %0, %1;" : "=f"(y) : "f"(x)); return y; }
DEVINL uint32_t opaque(uint32_t x) { return __shfl_sync(~0u, x, threadIdx.x & 31); }
DEVINL uint32_t launder(uint32_t x) { asm volatile("" : "+r"(x)); return x; }
DEVINL void pdl_wait() { asm volatile("griddepcontrol.wait;" ::: "memory"); }
DEVINL void pdl_launch() { asm volatile("griddepcontrol.launch_dependents;" ::: "memory"); }
#define LOGS(cta, i)
#define LOGK(k, i)
#define LOG(cta, i)
#define LOGV(cta, i, v)
#define EV(i, v)
constexpr float SM_SCALE = 0.08838834764831845f * 1.4426950408889634f;

DEVINL void unpack8(uint4 v, float* f) { f[0] = bf_lo(v.x); f[1] = bf_hi(v.x); f[2] = bf_lo(v.y); f[3] = bf_hi(v.y); f[4] = bf_lo(v.z); f[5] = bf_hi(v.z); f[6] = bf_lo(v.w); f[7] = bf_hi(v.w); }
DEVINL uint4 pack8(const float* f) { return make_uint4(pack_bf16(f[0], f[1]), pack_bf16(f[2], f[3]), pack_bf16(f[4], f[5]), pack_bf16(f[6], f[7])); }
DEVINL void ln_row(float* f) {
  float s = 0.f;
#pragma unroll
  for (int i = 0; i < 40; i++) s += f[i];
#pragma unroll
  for (int o = 1; o < 16; o <<= 1) s += __shfl_xor_sync(~0u, s, o);
  const float mean = s * (1.f / 640.f); float q = 0.f;
#pragma unroll
  for (int i = 0; i < 40; i++) { f[i] -= mean; q = fmaf(f[i], f[i], q); }
#pragma unroll
  for (int o = 1; o < 16; o <<= 1) q += __shfl_xor_sync(~0u, q, o);
  const float rs = rsqrtf(q * (1.f / 640.f) + 1e-5f);
#pragma unroll
  for (int i = 0; i < 40; i++) f[i] *= rs;
}

#define WAH 2
struct Wts { const char* w[4]; };
template <int CH> DEVINL void weight_warm(const Wts& w, uint32_t buf, uint32_t bar, uint32_t stop) {
  uint32_t smid; asm volatile("mov.u32 %0, %%smid;" : "=r"(smid));
  const uint32_t c = g_role[smid & 255];
  if (c >= 128) return;
  mbar_init(bar, 1); asm volatile("fence.mbarrier_init.release.cluster; fence.proxy.async.shared::cta;" ::: "memory");
  constexpr int N = 81920 / CH;
#pragma unroll 1
  for (int i = 0; i < (c < 64 ? 4 : 2) * N; i++) {
    uint32_t v; asm volatile("ld.volatile.shared.u32 %0, [%1];" : "=r"(v) : "r"(stop) : "memory");
    if (v) break;
    mbar_arrive_tx(bar, CH);
    auto src = [&](int i) { return w.w[c < 64 ? i / N : i / N * 2] + (c & 63) * 81920 + (i % N) * CH; };
    bulk_g2s(buf, src(i), CH, bar);
    if (WAH && i + WAH < (c < 64 ? 4 : 2) * N) l2_prefetch(src(i + WAH), CH);
    mbar_wait(bar, i & 1);
  }
}
struct ArgsA {
  const bf16* x; const bf16* mem0; char* comm; uint32_t* flags; const bf16* wr; const bf16* wi; const char* wq; const char* wo;
  int layer; int ta[4], tb[4], tc[2];
};

#define VP 4
#define HELD 0x2557
#define PRE 4
#define VPRE0 2
#define VPRE1 4
#define R0 2
#define TRK 30
#define TEXP 200
#define TRD 0
#define TKV 300
#define KB1 5
#define W2D 0
#define WD 4
#define VPW 2
#define P1F 1
#define W0D 0
#define XD 0
#define TSF 1
#define XP 0
#define PW 1
#define VXE 0
#define LA 0
#define KB2 9
#define KB3 13
#define TSE 7
#define PRP 0
#define R1 2
#define OBF 0
#define W1D 0
constexpr int C_WV = 0;
constexpr int C_WO = 81920;
constexpr int C_KV = 163840;
constexpr int C_M  = C_KV + 24576;
constexpr int C_QK = C_M + 10240;
constexpr int C_VP = C_QK + 4096;
constexpr int C_S  = C_VP + 4096;
constexpr int C_O  = C_S + 2048;
constexpr int C_R  = C_O + 2048;
constexpr int C_T  = C_R + 256;
constexpr int S_BAR = 229376;
constexpr int S_END = S_BAR + 256;
enum { BAR_QK = 2, BAR_O = 3, BAR_H = 4, BAR_X = 5, BAR_W = 7  , BAR_E = 9, BAR_M1 = 10  , BAR_M3 = 12, BAR_M2 = 13   };
constexpr int B_W = 0, B_S = 8, B_W2 = 16, B_KV = 24, B_WV = 40, B_WO = 48;
constexpr int G2_OFF = 0x130000, TS_OFF = 0x11000;

#define FEN() asm volatile("pmevent 0;" ::: "memory")
#define SCHED(x, c) asm volatile("{.reg .pred p; setp.eq.u32 p, %0, %1; @p exit;}" ::"r"(x), "r"(0x7fff0001u + 2 * (c)) : "memory")
DEVINL uint32_t g1page(uint32_t L) { L = ((L & 7) | ((L & 24) << 2)) << 1; return (L | (__popc(L & 0xb2) & 1)) << 12; }
DEVINL void spin_until(uint32_t t) {
  asm volatile("{.reg .pred p; .reg .b32 c; .reg .b64 w;\nS0: mov.u64 w, %%clock64; cvt.u32.u64 c, w; sub.u32 c, %0, c; setp.lt.u32 p, c, 16384; @p bra.uni S0;}" ::"r"(t) : "memory");
}
DEVINL uint32_t wait_until(uint32_t t, uint32_t z) { uint32_t r;
  asm volatile("{.reg .pred p; .reg .b32 c,x,y; .reg .b64 w;\nT0: .branchtargets L0, L1, L2, L3, L4, L5, L6, L7, L8, L9, L10;\n mov.u32 x, %2;\n"
               "mov.u64 w, %%clock64; cvt.u32.u64 c, w; sub.u32 c, %1, c; setp.ge.u32 p, c, 16384; @p bra.uni L0;\n"
               "S0: mov.u64 w, %%clock64; cvt.u32.u64 c, w; sub.u32 c, %1, c; setp.gt.s32 p, c, 40; @p bra.uni S0;\n"
               "mad.lo.s32 c, c, 37, 1200; shr.s32 c, c, 8; max.s32 c, c, 0;\nbrx.idx.uni c, T0;\n"
               "L10: mul.lo.u32 x, x, x; L9: mul.lo.u32 x, x, x; L8: mul.lo.u32 x, x, x; L7: mul.lo.u32 x, x, x; L6: mul.lo.u32 x, x, x; L5: mul.lo.u32 x, x, x; L4: mul.lo.u32 x, x, x; L3: mul.lo.u32 x, x, x; L2: mul.lo.u32 x, x, x; L1: mul.lo.u32 x, x, x; L0: mov.u32 %0, x;}" : "=r"(r) : "r"(t), "r"(z) : "memory"); return r;
}
DEVINL void gtime(uint32_t& G16, uint32_t& C) {
  asm volatile("{.reg .b64 w; .reg .b32 g,g0,a;\n mov.u64 w, %%clock64; cvt.u32.u64 %1, w; mov.u64 w, %%globaltimer; cvt.u32.u64 g0, w; mul.lo.u32 a, g0, -11;\n"
               "mov.u64 w, %%globaltimer; cvt.u32.u64 g, w; add.u32 a, a, g; mov.u64 w, %%globaltimer; cvt.u32.u64 g, w; add.u32 a, a, g; mov.u64 w, %%globaltimer; cvt.u32.u64 g, w; add.u32 a, a, g; mov.u64 w, %%globaltimer; cvt.u32.u64 g, w; add.u32 a, a, g; mov.u64 w, %%globaltimer; cvt.u32.u64 g, w; add.u32 a, a, g; mov.u64 w, %%globaltimer; cvt.u32.u64 g, w; add.u32 a, a, g; mov.u64 w, %%globaltimer; cvt.u32.u64 g, w; add.u32 a, a, g; mov.u64 w, %%globaltimer; cvt.u32.u64 g, w; add.u32 a, a, g; mov.u64 w, %%globaltimer; cvt.u32.u64 g, w; add.u32 a, a, g; mov.u64 w, %%globaltimer; cvt.u32.u64 g, w; add.u32 a, a, g; mov.u64 w, %%globaltimer; cvt.u32.u64 g, w; add.u32 a, a, g; \n mul.lo.u32 a, a, 341; shr.u32 a, a, 8; mad.lo.u32 %0, g0, 16, a;}" : "=r"(G16), "=r"(C)::"memory");
}
DEVINL uint32_t pack_tag(float lo, float hi, uint32_t tg) {
  const uint32_t w = pack_bf16(lo, __uint_as_float(tg | 0x3F800000u)), a = __float_as_uint(hi) + (tg ^ 0x10000u); uint32_t r;
  asm("lop3.b32 %0, %1, %2, 0xFFFE0000, 0xE4;" : "=r"(r) : "r"(a), "r"(w)); return r;
}
DEVINL float ex2v(float x) { float y; asm volatile("ex2.approx.ftz.f32 %0, %1;" : "=f"(y) : "f"(x)); return y; }
DEVINL void load_kv(uint32_t sb, int h, int j, int s) {
  asm volatile("{.reg .pred p; elect.sync _|p, 0xffffffff;\n fence.proxy.async.global;\n @p mbarrier.arrive.expect_tx.shared::cta.b64 _, [%2], 12288;\n"
               " @p cp.async.bulk.shared::cluster.global.mbarrier::complete_tx::bytes [%0], [%1], 12288, [%2];}"
               ::"r"(sb + C_KV + (s & 1) * 12288), "l"(g_kv + (size_t)(s * 32 + h) * 16384 + j * 4096), "r"(sb + S_BAR + B_KV + (s & 1) * 8) : "memory");
}

template <int KH>
DEVINL void chain_mma(uint32_t sb0, const ArgsA& args) {
  const int lane = threadIdx.x & 31, mg = (threadIdx.x >> 5) & 3, mi = lane >> 3, r = lane & 7;
  const uint32_t aW = opaque(sb0 + (uint32_t)(((mi >> 1) * 8 + r) * 128 + (((mg + 4 * (mi & 1)) ^ r) << 4)));
  const uint32_t aL = opaque(sb0 + lane * 16);
  const uint32_t aLm = opaque(sb0 + mg * 512 + lane * 16);
#define sb (launder(aL) & ~511u)
  constexpr int OV = C_WV + KH * 40960, OM = C_M + KH * 5120, NF = KH ? 16 : 24;
  auto owo = [](int f) { return C_WO + (KH + 2 * (f >> 3)) * 16384 + (f & 7) * 2048; };
  auto held = [](int k) { return (HELD >> k) & 1; };
  auto rank = [](int k) { return __popc(HELD & ((1 << k) - 1)); };
  uint32_t wq[20][4], wk[20][4];
  mbar_wait(sb + S_BAR + B_W, 0);
#pragma unroll
  for (int k = 0; k < 12; k++) { ldsm4t(wq[k], aW + OV + k * 2048); ldsm4t(wk[k], aW + C_WO + KH * 40960 + k * 2048); }
  bar_arrive(BAR_H, 288);
  mbar_wait(sb + S_BAR + B_W2, 0);
#pragma unroll
  for (int k = 12; k < 20; k++) { ldsm4t(wq[k], aW + OV + k * 2048); ldsm4t(wk[k], aW + C_WO + KH * 40960 + k * 2048); }
  bar_sync(BAR_E, 384);
  mbar_wait(sb + S_BAR + B_WV, 0);
  uint32_t sx = args.layer << 16;
#pragma unroll 1
  while (true) {
    uint32_t v[20][4], b[10][4];
    {
      const uint32_t o = launder(aLm) - sb, on = (sx >> 16) != (uint32_t)args.layer;
      const char* p = args.comm + lds32(sb + C_T + KH * 1024 + 4 + (o >> 1));
      constexpr int NB = KH ? VPRE1 : VPRE0;
      const uint32_t zero = (uint32_t)(uintptr_t)p & 1, tt = lds32(sb + C_R + 48) + args.tb[0]; uint32_t av = aW;
#pragma unroll
      for (int k = 0; k < 20; k++) if (held(k) && rank(k) < NB) { ldsm4t(v[k], av + OV + k * 2048); if (rank(k) % VPW == VPW - 1 && rank(k) < NB - 1) av = aW + (v[k][0] & zero); }
      p += wait_until(tt, zero);
      uint4 a = ldg_rlx128(p);
      __syncwarp();
#pragma unroll
      for (int k = 0; k < 20; k++) if (held(k) && rank(k) >= NB) { ldsm4t(v[k], av + OV + k * 2048); if ((rank(k) - NB) % VPW == VPW - 1) av = aW + (v[k][0] & zero); }
      SCHED(o ^ on, 29);
      if (on) sts128(aLm + OM, a);
      if (__builtin_expect(__any_sync(~0u, on && (((a.x ^ sx) | (a.z ^ sx)) & 0x10000u)), 0)) {
        int lim = 0;
        do a = ldg_rlx128(p); while (__any_sync(~0u, (((a.x ^ sx) | (a.z ^ sx)) & 0x10000u) && ++lim < POLL_LIMIT));
        sts128(aLm + OM, a);
      }
      bar_sync(BAR_W + KH, 128);
      ldsm4t(b[0], aL + OM); ldsm4t(b[1], aL + OM + 512);
    }
    float cq[4], ck[4], cv[4];
    static_for<0, 20>([&](auto I) {
      constexpr int k = I.value, p = k >> 1;
      const uint32_t b0 = b[p][(k & 1) * 2], b1 = b[p][(k & 1) * 2 + 1];
      if (k == 0) { mma16816z(cv, v[0], b0, b1); mma16816z(cq, wq[k], b0, b1); mma16816z(ck, wk[k], b0, b1); }
      else { if (k < 20 - VP) mma16816(cv, v[k], b0, b1); mma16816(cq, wq[k], b0, b1); mma16816(ck, wk[k], b0, b1); }
      if (k == KB1) bar_sync(BAR_M1 + KH, 160);
      if (k == KB2) bar_sync(BAR_M2 + KH, 160);
      if (k == KB3) bar_sync(BAR_M3, 320);
      static_for<2, 10>([&](auto J) {
        constexpr int q = J.value, st = q < 4 ? 0 : q < 6 ? KB1 : q < 8 ? KB2 : KB3;
        if constexpr (k == (2 * q - 3 > st ? 2 * q - 3 : st)) ldsm4t(b[q], aL + OM + q * 512); });
      if constexpr (k + 3 < 20 - VP && !((HELD >> (k + 3)) & 1)) ldsm4t(v[k + 3], aW + OV + (k + 3) * 2048);
      if (k >= 20 - VP && k < 20 - VP + PRE && !held(k)) ldsm4t(v[k], aW + OV + k * 2048);
      if (P1F && (k & 1) && k >= P1F && k < 19) FEN();
    });
    stsm4(aLm + C_QK + KH * 2048, pack_bf16(cq[0], cq[1]), pack_bf16(cq[2], cq[3]), pack_bf16(ck[0], ck[1]), pack_bf16(ck[2], ck[3]));
    bar_arrive(BAR_QK, 384);
    FEN();
    const uint32_t l8 = (launder(aL) & 511) >> 1, px = lds32(sb + C_R + 80);
#pragma unroll
    for (int k = 20 - VP + PRE; k < 20; k++) if (!held(k)) ldsm4t(v[k], aW + OV + k * 2048);
#pragma unroll
    for (int k = 20 - VP; k < 20; k++) {
      const int p = k >> 1, q = k - 20 + VP; const uint32_t b0 = b[p][(k & 1) * 2], b1 = b[p][(k & 1) * 2 + 1];
      if (q % 3 == 0) mma16816(cv, v[k], b0, b1); else if (q == 1) mma16816z(cq, v[k], b0, b1); else if (q == 2) mma16816z(ck, v[k], b0, b1);
      else if (q % 3 == 1) mma16816(cq, v[k], b0, b1); else mma16816(ck, v[k], b0, b1);
    }
    if (VP >= 3) {
#pragma unroll
      for (int i = 0; i < 4; i++) cv[i] += cq[i] + ck[i];
    }
    { const uint32_t vx = pack_bf16(cv[0], cv[1]), vy = pack_bf16(cv[2], cv[3]);
      const uint32_t av = aLm - l8 + C_VP + KH * 256;
      stasync64(av + 2048 + px, vx, vy, sb + S_BAR + B_S + px);
      sts64(av, vx, vy);
      __syncwarp();
      if (l8 == 0) mbar_arrive(sb + S_BAR + B_S); }
    sx += 0x10000;
    if ((sx >> 16) == args.layer + 64u) break;
    uint32_t w[NF][4];
    {
      const uint32_t zero = px & 1; uint32_t a = aW;
      const bool tsw = KH == 1 && __any_sync(~0u, launder(aLm) == aL); uint2 ts = make_uint2(0, 0); uint4 cal = make_uint4(0, 0, 0, 0);
      if ((sx >> 16) == args.layer + 1u) mbar_wait(sb + S_BAR + B_WO, 0);
#pragma unroll
      for (int f = 0; f < 8 + XP; f++) { ldsm4t(w[f], a + owo(f));
        if (KH == 1 && f == TSF && tsw) { ts = ldg_rlx64(args.comm + TS_OFF + l8); cal = lds128(sb + C_R + 64); }
      if (KH == 1 && f == TSE && tsw) {
        const uint32_t d0 = ts.x - cal.x, d1 = ts.y - cal.x;
        const int dt = (int)__reduce_max_sync(~0u, max(d0 < 32768u ? d0 : 0u, d1 < 32768u ? d1 : 0u));
        sts32(sb + C_R + 48, cal.y + min((dt * cal.z) >> 16, 8192u));
      }
        uint32_t d = w[f][0] & zero;
#pragma unroll
        for (int q = 0; q < TRD; q++) d = __popc(d);
        if (f % PW == PW - 1) a = aW + d; }
    }
    const uint32_t go = lds32(sb + C_T + KH * 1024 + ((launder(aLm) - sb) >> 1));
    SCHED(go, 30);
    bar_sync(BAR_O, 384);
    uint32_t ob[16];
#pragma unroll
    for (int p = 0; p < 4; p++) ldsm4t(ob + 4 * p, aL + C_O + p * 512);
    __syncwarp();
    float r0, r1; uint32_t y0, y1;
    { const uint2 rr = lds64(sb + C_R + 128 + ((launder(aL) >> 1) & 24)); r0 = rcp(__uint_as_float(rr.x)); r1 = rcp(__uint_as_float(rr.y)); }
    constexpr int RA = KH ? R1 : R0;
    static_for<0, NF>([&](auto I) {
      constexpr int f = I.value, k = f & 7, nx = (f & ~7) + 8, x0 = f < 8 ? XP : 0; const uint32_t* A = w[f];
      if (k == 0) mma16816z(cq, A, ob[0], ob[1]); else if (k == 1) mma16816z(ck, A, ob[2], ob[3]);
      else if (k & 1) mma16816(ck, A, ob[2 * k], ob[2 * k + 1]); else mma16816(cq, A, ob[2 * k], ob[2 * k + 1]);
      if constexpr (f >= 8 && (f & 1) && k + WD < 8) { const uint32_t a = aW + (A[0] & go & 1); ldsm4t(w[f + WD - 1], a + owo(f + WD - 1)); ldsm4t(w[f + WD], a + owo(f + WD)); }
      if constexpr (k == 5 && nx < NF && RA > 0) { const uint32_t a = f < 8 ? aW : aW + (A[0] & go & 1);
#pragma unroll
        for (int q = x0; q < x0 + RA; q++) ldsm4t(w[nx + q], a + owo(nx + q)); }
      if (k == 7) { y0 = pack_tag((cq[0] + ck[0]) * r0, (cq[1] + ck[1]) * r1, sx & 0x10000u); y1 = pack_bf16((cq[2] + ck[2]) * r0, (cq[3] + ck[3]) * r1);
        stg_rlx64(args.comm + go + (f < 8 ? 0 : f < 16 ? 0x30000 : 0x100000), y0, y1); }
      if constexpr (k == 7 && nx < NF) {
        if constexpr (KH == 1 && W1D != 0) spin_until(clk() + W1D); else FEN();
#pragma unroll
        for (int q = x0 + RA; q < WD; q++) ldsm4t(w[nx + q], aW + owo(nx + q));
      }
      if (f >= 8 && k == 3) SCHED(y0 & y1 & go, 40 + f);
      else if ((f >= 7 && (f & 1)) || (f == 5 && RA > 0) || (f == 1 && OBF)) FEN();
    });
  }
}

#undef sb
DEVINL void chain_helper(uint32_t sb, uint32_t px, int h, int j, const ArgsA& args, const CUtensorMap* tq, const CUtensorMap* tk, const CUtensorMap* tv, const CUtensorMap* to) {
  const int c = 2 * h + j;
  const uint32_t bW = sb + S_BAR + B_W, bS = sb + S_BAR + B_S, bKV = sb + S_BAR + B_KV;
  const uint32_t lane0 = opaque(threadIdx.x & 31);
  const uint32_t warp = __reduce_max_sync(~0u, (threadIdx.x >> 5) & 3);
  { const int tid = threadIdx.x - 256;
    if (tid == 0) { mbar_arrive_tx(bW, 98304); mbar_arrive_tx(bW + B_W2, 65536); mbar_arrive_tx(bW + B_WV, 81920); mbar_arrive_tx(bW + B_WO, 81920);
#pragma unroll 1
      for (int q = 0; q < 10; q++) { const int i = (q & 1) * 5 + (q >> 1); const uint32_t bar = q < 6 ? bW : bW + B_W2;
        tma_2d(sb + C_WV + i * 8192, tq, h * 128 + j * 64, i * 64, bar); tma_2d(sb + C_WO + i * 8192, tk, h * 128 + j * 64, i * 64, bar); } }
    uint32_t G0, C0; gtime(G0, C0);
    if (warp == 0) sts64(sb + C_R + 96, G0, C0);
    { const uint32_t g = lane0 >> 2, t = lane0 & 3;
      sts128(sb + C_T + 2048 + tid * 16, make_uint4(g1page(c >> 1) + (c & 1) * 2048 + (warp == 0 ? 0 : warp == 1 ? 0x30000 : 0x100000) + ((g >> 2) * 4 + t) * 64 + (g & 3) * 16,
                                                    g1page(((t >> 1) + (g >> 2) * 2) * 4 + warp) + G2_OFF + (c >> 4) * 1024 + (t & 1) * 512 + (c & 15) * 32 + (g & 3) * 8,
                                                    g1page((h & 3) * 4 + (warp == 2 ? 2 : 1)) + G2_OFF + (warp == 1 ? 1024 : warp == 3 ? 2048 : 0) + lane0 * 16, (g & 1) ? 0x3F800000u : 0x00003F80u)); }
    sts32(sb + C_R + 80, px); sts32(sb + C_R + 48, C0 - 65536);
#pragma unroll
    for (int kh = 0; kh < 2; kh++)
      sts64(sb + C_T + kh * 1024 + tid * 8, g1page(j * 16 + kh * 8 + (tid >> 4)) + (tid & 8) * 256 + h * 64 + (tid & 7) * 8, g1page((h & 3) * 4) + G2_OFF + kh * 2048 + tid * 16);
#pragma unroll
    for (int i = 0; i < 5; i++) { const int q = tid + i * 128, n = q & 7, d0 = (q >> 3) * 8; const uint4 v = *(const uint4*)(args.mem0 + n * 640 + d0); const uint32_t w[4] = {v.x, v.y, v.z, v.w};
#pragma unroll
      for (int e = 0; e < 8; e++) asm volatile("st.shared.u16 [%0], %1;" ::"r"(sb + C_M + (d0 + e) * 16 + n * 2), "h"((unsigned short)(w[e >> 1] >> ((e & 1) * 16))) : "memory"); }
    auto round2 = [&](int q0, int q1) {
#pragma unroll 1
      for (int q = q0; q < q1; q++) { const int i = (q & 1) * 5 + (q >> 1); tma_2d(sb + C_WV + i * 8192, tv, h * 128 + j * 64, i * 64, bW + B_WV); }
#pragma unroll 1
      for (int q = q0; q < q1; q++) { const int i = (q & 1) * 5 + (q >> 1); tma_2d(sb + C_WO + i * 8192, to, j * 320 + (i >> 1) * 64, h * 128 + ((i & 1) ^ j) * 64, bW + B_WO); } };
    if (warp == 0) { bar_sync(BAR_H, 288); if (tid == 0) round2(0, 6); __syncwarp(); }
    bar_sync(BAR_E, 384);
    if (tid == 0) round2(6, 10);
    if (warp == 3) {
      if (tid == 96) LOG(c, 250);
      flag_wait_warp(args.flags + F_KV + h * 32, 2);
      load_kv(sb, h, j, 0); load_kv(sb, h, j, 1); if (tid == 96) LOG(c, 251);
    }
  }
  auto calib = [&]() { uint32_t G, C; gtime(G, C);
    const uint2 o = lds64(sb + C_R + 96); const float rt = (float)(C - o.y) * rcp((float)(G - o.x));
    sts128(sb + C_R + 32, make_uint4(G, C, __float2uint_rn(rt * 65536.f) & 0xffffu, __float_as_uint(rcp(rt)))); __syncwarp(); };
  auto do_export = [&](int s, uint32_t lane) {
    uint32_t k0[2][4], k1[2][4]; uint2 a[4], b[4];
    const uint32_t ak = sb + C_QK + 256 + (lane >> 4) * 512 + (lane & 15) * 16, av = sb + C_VP + (lane >> 3) * 512 + (lane & 7) * 8;
#pragma unroll
    for (int i = 0; i < 2; i++) { ldsm4t(k0[i], ak + i * 1024); ldsm4t(k1[i], ak + i * 1024 + 2048); }
#pragma unroll
    for (int i = 0; i < 4; i++) { a[i] = lds64(av + i * 64); b[i] = lds64(av + i * 64 + 256); }
    char* dst = g_kvm + ((s * 32 + h) * 4096 + j * 1024 + lane * 16);
    const uint32_t tg = (args.layer ^ 1) << 16;
    auto put = [&](char* q, uint32_t x, uint32_t y, uint32_t z, uint32_t w) { stg_rlx128(q, (x & ~0x10000u) | tg, y, (z & ~0x10000u) | tg, w); };
#pragma unroll
    for (int i = 0; i < 2; i++) put(dst + i * 512, hadd2bf(k0[i][0], k1[i][0]), hadd2bf(k0[i][1], k1[i][1]), hadd2bf(k0[i][2], k1[i][2]), hadd2bf(k0[i][3], k1[i][3]));
    put(dst + 2048, hadd2bf(a[0].x, b[0].x), hadd2bf(a[1].x, b[1].x), hadd2bf(a[2].x, b[2].x), hadd2bf(a[3].x, b[3].x));
    put(dst + 2560, hadd2bf(a[0].y, b[0].y), hadd2bf(a[1].y, b[1].y), hadd2bf(a[2].y, b[2].y), hadd2bf(a[3].y, b[3].y));
    stg_rlx32(args.flags + F_KM + h * 32 + j, s + 1);
  };
  auto staged = [&]() { if (warp == 2) bar_arrive(BAR_M3, 320); else if (warp == 1) { bar_arrive(BAR_M2, 160); bar_arrive(BAR_M2 + 1, 160); } else bar_arrive(BAR_M1 + (warp >> 1), 160); };
  if (warp == 0) calib();
  staged();
  int kv_ok = 1;
  uint32_t vx[4][4];
  auto load_vx = [&](int s, uint32_t lane) {
    const uint32_t aVx = sb + C_KV + (s & 1) * 12288 + 4096 + (warp >> 1) * (j ? -4096 : 4096) + (warp & 1) * 1024 + lane * 16, zero = lane >> 5;
#pragma unroll
    for (int i = 0; i < 4; i++) { const uint4 q = lds128(aVx + (i & 1) * 2048 + (i >> 1) * 512); vx[i][0] = q.x ^ zero; vx[i][1] = q.z ^ zero; vx[i][2] = q.y ^ zero; vx[i][3] = q.w ^ zero; }
  };
  uint2 kb[4];
  auto prep = [&](int s, uint32_t lane) {
    if (s < 63) mbar_wait(bKV + (s & 1) * 8, (s >> 1) & 1);
    const uint32_t aK = sb + C_KV + (s & 1) * 12288 + j * 8192 + warp * 1024 + lane * 16;
#pragma unroll
    for (int i = 0; i < 4; i++) kb[i] = lds64(aK + ((warp ^ i) >> 1) * 512 + ((warp ^ i) & 1) * 8);
    if (VXE) load_vx(s, lane);
    asm volatile("{.reg .pred p; setp.eq.u32 p, %2, 32; @p mbarrier.arrive.expect_tx.shared::cta.b64 _, [%0], %1;}" ::"r"(bS), "r"(s < 63 ? 3072 : 2048), "r"(warp * 32 + lane) : "memory");
  };
  prep(0, lane0);
#pragma unroll 1
  for (int s = 0;; s++) {
    const uint32_t ph = s & 1;
    const uint32_t lane = __shfl_sync(~0u, lane0, lane0);
    const uint32_t mi = lane >> 3, r = lane & 7;
    const uint32_t aQ = sb + C_QK + (mi & 1) * 2048 + ((mi >> 1) * 8 + r) * 16;
    const uint32_t aKm = sb + C_QK + 256 + warp * 512 + (lane >> 4) * 2048 + (lane & 15) * 16;
    const uint32_t aH = sb + C_S + warp * 256 + lane * 8, aR = aH + 1024 + px;
    SCHED(aQ ^ aR ^ aKm, 60);
    if (warp == 0) {
      const uint4 cal = lds128(sb + C_R + 32);
      bar_sync(BAR_M3, 320);
      sts32(sb + C_R + 52, 0);
      const uint32_t E = clk(), e16 = cal.x + (uint32_t)__float2int_rn((float)(int)(E - cal.y) * __uint_as_float(cal.w));
      stg_rlx32(args.comm + TS_OFF + c * 4, e16); sts128(sb + C_R + 64, make_uint4(e16, E, cal.z, 0));
    }
    if (s == 63) { bar_sync(BAR_QK, 384); mbar_wait(bS, 1); if (warp == 3) do_export(63, lane); break; }
    {
      uint32_t qa[4][4], km[4]; float s0[4], s1[4], s2[4];
      bar_sync(BAR_QK, 384);
      ldsm4t(qa[0], aQ + warp * 512); ldsm4t(km, aKm); ldsm4t(qa[1], aQ + (warp ^ 1) * 512); ldsm4t(qa[2], aQ + (warp ^ 2) * 512); ldsm4t(qa[3], aQ + (warp ^ 3) * 512);
      mma16816z(s0, qa[0], kb[0].x, kb[0].y); mma16816z(s2, qa[0], km[0], km[1]); mma16816z(s1, qa[1], kb[1].x, kb[1].y);
      FEN();
      mma16816(s2, qa[0], km[2], km[3]); mma16816(s0, qa[2], kb[2].x, kb[2].y); mma16816(s1, qa[3], kb[3].x, kb[3].y);
      const uint32_t w0 = pack_bf16((s0[0] + s0[2]) + (s1[0] + s1[2]), (s0[1] + s0[3]) + (s1[1] + s1[3]));
      const uint32_t w1 = pack_bf16(s2[0] + s2[2], s2[1] + s2[3]);
      stasync64(aR, w0, w1, bS + px);
      sts64(aH, w0, w1);
    }
    {
      uint32_t sl[5];
      const uint32_t a8 = sb + lane * 8, av = a8 + C_VP + warp * 1024;
      const uint32_t aO = sb + C_O + ((warp >> 1) * 64 + (warp & 1) * 16 + (mi & 1) * 32 + (mi >> 1) * 8 + r) * 16, aU = sb + C_R + (lane & 28);
      bar_sync(BAR_X, 128);
      { uint2 t[4];
#pragma unroll
        for (int u = 0; u < 4; u++) t[u] = lds64(a8 + C_S + u * 256);
        if (!VXE) load_vx(s, lane);
#pragma unroll
        for (int u = 0; u < 4; u++) sl[u] = t[u].x;
        sl[4] = pack_bf16((bf_lo(t[0].y) + bf_lo(t[1].y)) + (bf_lo(t[2].y) + bf_lo(t[3].y)), (bf_hi(t[0].y) + bf_hi(t[1].y)) + (bf_hi(t[2].y) + bf_hi(t[3].y))); }
      mbar_wait(bS, ph);
      uint32_t vm[2][4];
      { uint2 t[4];
#pragma unroll
        for (int u = 0; u < 4; u++) t[u] = lds64(a8 + C_S + 1024 + u * 256);
#pragma unroll
        for (int u = 0; u < 4; u++) sl[u] = hadd2bf(sl[u], t[u].x);
        sl[4] = hadd2bf(hadd2bf(hadd2bf(sl[4], t[0].y), t[1].y), hadd2bf(t[2].y, t[3].y)); }
      uint32_t m2 = hmax2bf(hmax2bf(hmax2bf(sl[0], sl[1]), hmax2bf(sl[2], sl[3])), sl[4]);
      const uint32_t x1 = __shfl_xor_sync(~0u, m2, 1), x2 = __shfl_xor_sync(~0u, m2, 2), x3 = __shfl_xor_sync(~0u, m2, 3);
#pragma unroll
      for (int i = 0; i < 4; i++) { const uint2 q = lds64(av + i * 256); vm[i >> 1][(i & 1) * 2] = q.x; vm[i >> 1][(i & 1) * 2 + 1] = q.y; }
      float sv[10];
#pragma unroll
      for (int u = 0; u < 5; u++) { sv[2 * u] = bf_lo(sl[u]) * SM_SCALE; sv[2 * u + 1] = bf_hi(sl[u]) * SM_SCALE; }
      FEN();
      m2 = hmax2bf(hmax2bf(m2, x1), hmax2bf(x2, x3));
      const float mx = fmaxf(bf_lo(m2), bf_hi(m2));
      float o0[4], o1[4];
#pragma unroll
      for (int i = 0; i < 10; i++) sv[i] = fmaf(mx, -SM_SCALE, sv[i]);
      sv[8] = ex2v(sv[8]); sv[9] = ex2v(sv[9]);
#pragma unroll
      for (int i = 0; i < 8; i++) sv[i] = ex2v(sv[i]);
      { const uint32_t p = pack_bf16(sv[8], sv[9]); mma16816z(o0, vm[0], p, p); mma16816z(o1, vm[1], p, p); }
      { const uint32_t p0 = pack_bf16(sv[0], sv[1]), p1 = pack_bf16(sv[2], sv[3]); mma16816(o0, vx[0], p0, p1); mma16816(o1, vx[2], p0, p1); }
      { const uint32_t p0 = pack_bf16(sv[4], sv[5]), p1 = pack_bf16(sv[6], sv[7]); mma16816(o0, vx[1], p0, p1); mma16816(o1, vx[3], p0, p1); }
      float su = (((sv[8] + sv[9]) + ((sv[0] + sv[1]) + (sv[2] + sv[3]))) + (sv[4] + sv[5])) + (sv[6] + sv[7]);
      { const float a1 = __shfl_xor_sync(~0u, su, 1), a2 = __shfl_xor_sync(~0u, su, 2), a3 = __shfl_xor_sync(~0u, su, 3); su = (su + a1) + (a2 + a3); }
      sts32(aU + 128, __float_as_uint(su));
      stsm4(aO, pack_bf16(o0[0], o0[1]), pack_bf16(o0[2], o0[3]), pack_bf16(o1[0], o1[1]), pack_bf16(o1[2], o1[3]));
      bar_sync(BAR_O, 384);
    }
    const uint32_t t0 = lds32(sb + C_R + 48);
    const uint4 xo = lds128(sb + C_T + 2048 + warp * 512 + lane * 16);
    uint32_t rdy = 0;
    const uint32_t tag = (s + args.layer + 1) & 1, tm = 0u - tag;
    if (warp == 3) {
      if (lane == 0) { LOGS(c, s); LOGV(c, 192 + (s >> 1), clk()); }
      if (((s + 2) >> 1) >= kv_ok) rdy = ldg_rlx32(args.flags + F_KV + h * 32 + lane);
      spin_until(t0 + args.tc[0]);
      do_export(s, lane);
      if (lane == 0) LOG(c, 64 + s);
    }
    if (warp == 2) calib();
    if (warp < 2 || (warp == 2 && !(c & 16))) {
      const char* p = args.comm + xo.x; char* g2w = args.comm + xo.y;
      const uint32_t s0 = (lane & 8) ? 0u : xo.w, s1 = (lane & 8) ? xo.w : 0u;
      int lim = 0; bool bad;
      p += wait_until(t0 + args.ta[warp == 0 ? 0 : warp == 2 ? 3 : 1 + ((c >> 4) & 1)], lane >> 5);
      do {
        uint4 a[4]; float z0[4], z1[4], y[4];
#pragma unroll
        for (int i = 0; i < 4; i++) a[i] = ldg_rlx128(p + i * 512);
        ++lim;
        { const uint32_t A[4] = {a[0].x, a[0].y, a[0].z, a[0].w}; mma16816z(z0, A, s0, s1); }
        { const uint32_t A[4] = {a[1].x, a[1].y, a[1].z, a[1].w}; mma16816z(z1, A, s0, s1); }
        { const uint32_t A[4] = {a[2].x, a[2].y, a[2].z, a[2].w}; mma16816(z0, A, s0, s1); }
        { const uint32_t A[4] = {a[3].x, a[3].y, a[3].z, a[3].w}; mma16816(z1, A, s0, s1); }
        const uint32_t m0 = launder((a[0].x ^ tm) | (a[0].z ^ tm)), m1 = launder((a[1].x ^ tm) | (a[1].z ^ tm)), m2 = launder((a[2].x ^ tm) | (a[2].z ^ tm)), m3 = launder((a[3].x ^ tm) | (a[3].z ^ tm));
        bad = __any_sync(~0u, ((launder(m0 | m1 | m2) | m3) & 0x10000u) && lim < POLL_LIMIT);
#pragma unroll
        for (int i = 0; i < 4; i++) y[i] = z0[i] + z1[i];
        const bool odd = lane & 1; const float k0 = odd ? y[2] : y[0], k1 = odd ? y[3] : y[1], e0 = odd ? y[0] : y[2], e1 = odd ? y[1] : y[3];
        const float o0 = __shfl_xor_sync(~0u, e0, 1) + __shfl_xor_sync(~0u, e0, 17), o1 = __shfl_xor_sync(~0u, e1, 1) + __shfl_xor_sync(~0u, e1, 17);
        const float q0 = k0 + __shfl_xor_sync(~0u, k0, 16), q1 = k1 + __shfl_xor_sync(~0u, k1, 16);
        const uint32_t w0 = pack_tag(odd ? o0 : q0, odd ? o1 : q1, tag << 16), w1 = pack_bf16(odd ? q0 : o0, odd ? q1 : o1);
        if (!bad) stg_rlx64(g2w, w0, w1);
      } while (bad);
      if (lane == 0 && warp == 0) LOGV(c, 128 + s, lim);
      if (lane == 0) { EV(warp, clk() - t0); EV(3 + warp, lim); }
    }
    if (!PRP || warp != 1) prep(s + 1, lane); else kb[0] = kb[1] = kb[2] = kb[3] = make_uint2(0, 0);
    {
      const char* p = args.comm + xo.z;
      const uint32_t aMw = sb + C_M + 2048 + (warp == 3 ? 5120 : warp * 1024) + lane * 16;
      int lim = 0; bool bad;
      p += wait_until(t0 + args.tb[warp == 3 ? 1 : warp + 1], lane >> 5);
      if (warp == 0 || warp == 3) {
        do { const uint4 a = ldg_rlx128(p), b = ldg_rlx128(p + 512); ++lim;
          sts128(aMw, a); sts128(aMw + 512, b);
          bad = __any_sync(~0u, ((launder((a.x ^ tm) | (a.z ^ tm)) | launder((b.x ^ tm) | (b.z ^ tm))) & 0x10000u) && lim < POLL_LIMIT);
        } while (bad);
      } else {
        do { uint4 a[4]; uint32_t m[4]; ++lim;
#pragma unroll
          for (int i = 0; i < 4; i++) a[i] = ldg_rlx128(p + (i & 1) * 512 + (i >> 1) * 2048);
#pragma unroll
          for (int i = 0; i < 4; i++) { sts128(aMw + (i & 1) * 512 + (i >> 1) * 5120, a[i]); m[i] = launder((a[i].x ^ tm) | (a[i].z ^ tm)); }
          bad = __any_sync(~0u, ((launder(m[0] | m[1] | m[2]) | m[3]) & 0x10000u) && lim < POLL_LIMIT);
        } while (bad);
      }
      staged();
      if (lane == 0 && warp < 3) { EV(6 + warp, clk() - t0); EV(9 + warp, lim); }
    }
    if (PRP && warp == 1) prep(s + 1, lane);
    if (warp == 3 && s < 61) {
      spin_until(t0 + args.tc[1]);
      if (((s + 2) >> 1) >= kv_ok) {
        for (int n = 0; (kv_ok = __clz(__brev(~__ballot_sync(~0u, rdy >= 2)))) <= ((s + 2) >> 1) && n < POLL_LIMIT; n++) rdy = ldg_rlx32(args.flags + F_KV + h * 32 + lane);
        asm volatile("fence.acquire.gpu;" ::: "memory");
      }
      load_kv(sb, h, j, s + 2);
    }
  }
}

#define PF0 14
#define QORD 0
#define LDA ldg_ef128
#define LDB ldg_na128
#define PFD 2
#define PFR 1
#define NPROBE 3
#define OPACE 400
constexpr int G_ST = 163840;
constexpr int B_FULL = 64, B_EMPTY = 96, B_RB = 128, B_WD = 136, B_ROLE = 144, B_PROG = 152, B_WF = 160  , B_DUM = 200;
enum { BAR_T = 1  , BAR_G = 3  , BAR_V = 5   };
DEVINL uint64_t mkdesc(uint32_t a, uint32_t lbo, uint32_t sbo, uint32_t sw) { return (uint64_t)((a & 0x3FFFF) >> 4) | ((uint64_t)(lbo >> 4) << 16) | ((uint64_t)(sbo >> 4) << 32) | ((uint64_t)sw << 62); }
DEVINL void wgmma_n128(float* d, uint64_t a, uint64_t b, int acc) {
  asm volatile("{.reg .pred p; setp.ne.b32 p, %66, 0; wgmma.mma_async.sync.aligned.m64n128k16.f32.bf16.bf16 {%0,%1,%2,%3,%4,%5,%6,%7,%8,%9,%10,%11,%12,%13,%14,%15,%16,%17,%18,%19,%20,%21,%22,%23,%24,%25,%26,%27,%28,%29,%30,%31,%32,%33,%34,%35,%36,%37,%38,%39,%40,%41,%42,%43,%44,%45,%46,%47,%48,%49,%50,%51,%52,%53,%54,%55,%56,%57,%58,%59,%60,%61,%62,%63}, %64, %65, p, 1, 1, 0, 1;}"
               : "+f"(d[0]),"+f"(d[1]),"+f"(d[2]),"+f"(d[3]),"+f"(d[4]),"+f"(d[5]),"+f"(d[6]),"+f"(d[7]),"+f"(d[8]),"+f"(d[9]),"+f"(d[10]),"+f"(d[11]),"+f"(d[12]),"+f"(d[13]),"+f"(d[14]),"+f"(d[15]),"+f"(d[16]),"+f"(d[17]),"+f"(d[18]),"+f"(d[19]),"+f"(d[20]),"+f"(d[21]),"+f"(d[22]),"+f"(d[23]),"+f"(d[24]),"+f"(d[25]),"+f"(d[26]),"+f"(d[27]),"+f"(d[28]),"+f"(d[29]),"+f"(d[30]),"+f"(d[31]),"+f"(d[32]),"+f"(d[33]),"+f"(d[34]),"+f"(d[35]),"+f"(d[36]),"+f"(d[37]),"+f"(d[38]),"+f"(d[39]),"+f"(d[40]),"+f"(d[41]),"+f"(d[42]),"+f"(d[43]),"+f"(d[44]),"+f"(d[45]),"+f"(d[46]),"+f"(d[47]),"+f"(d[48]),"+f"(d[49]),"+f"(d[50]),"+f"(d[51]),"+f"(d[52]),"+f"(d[53]),"+f"(d[54]),"+f"(d[55]),"+f"(d[56]),"+f"(d[57]),"+f"(d[58]),"+f"(d[59]),"+f"(d[60]),"+f"(d[61]),"+f"(d[62]),"+f"(d[63]) : "l"(a), "l"(b), "r"(acc));
}
DEVINL void wgmma_n80(float* d, uint64_t a, uint64_t b, int acc) {
  asm volatile("{.reg .pred p; setp.ne.b32 p, %42, 0; wgmma.mma_async.sync.aligned.m64n80k16.f32.bf16.bf16 {%0,%1,%2,%3,%4,%5,%6,%7,%8,%9,%10,%11,%12,%13,%14,%15,%16,%17,%18,%19,%20,%21,%22,%23,%24,%25,%26,%27,%28,%29,%30,%31,%32,%33,%34,%35,%36,%37,%38,%39}, %40, %41, p, 1, 1, 0, 1;}"
               : "+f"(d[0]),"+f"(d[1]),"+f"(d[2]),"+f"(d[3]),"+f"(d[4]),"+f"(d[5]),"+f"(d[6]),"+f"(d[7]),"+f"(d[8]),"+f"(d[9]),"+f"(d[10]),"+f"(d[11]),"+f"(d[12]),"+f"(d[13]),"+f"(d[14]),"+f"(d[15]),"+f"(d[16]),"+f"(d[17]),"+f"(d[18]),"+f"(d[19]),"+f"(d[20]),"+f"(d[21]),"+f"(d[22]),"+f"(d[23]),"+f"(d[24]),"+f"(d[25]),"+f"(d[26]),"+f"(d[27]),"+f"(d[28]),"+f"(d[29]),"+f"(d[30]),"+f"(d[31]),"+f"(d[32]),"+f"(d[33]),"+f"(d[34]),"+f"(d[35]),"+f"(d[36]),"+f"(d[37]),"+f"(d[38]),"+f"(d[39]) : "l"(a), "l"(b), "r"(acc));
}

template <int N, int NST, bool HAND>
DEVINL void gemm_tile(float* acc, uint32_t sb, uint32_t px, int wg, uint32_t u0, int rot, bool lead, int wph) {
  const uint64_t db = N == 128 ? mkdesc(sb, 81920, 1024, 1) : mkdesc(sb, 32768, 256, 3);
#pragma unroll
  for (int i = 0; i < N / 2; i++) acc[i] = 0.f;
  bar_sync(BAR_T + wg, 256);
#pragma unroll 1
  for (int st = 0; st < NST; st++) {
    const uint32_t u = u0 + st, slot = u & 3, ks = (st + rot >= NST ? st + rot - NST : st + rot) * 8;
    if (wph >= 0) mbar_wait(sb + S_BAR + B_WF + (N == 128 ? st * 8 : 0), wph);
    mbar_wait(sb + S_BAR + B_FULL + slot * 8, (u >> 2) & 1);
    const uint64_t da = mkdesc(sb + G_ST + slot * 16384, 16, 1024, 1);
    asm volatile("wgmma.fence.sync.aligned;" ::: "memory");
#pragma unroll
    for (int k = 0; k < 8; k++) {
      const uint64_t a = da + (k >> 2) * 512 + (k & 3) * 2;
      if (N == 128) wgmma_n128(acc, a, db + (ks + k) * 128, 1); else wgmma_n80(acc, a, db + (ks + k) * 32, 1);
    }
    asm volatile("wgmma.commit_group.sync.aligned;" ::: "memory");
    if (HAND && st == NST - 1) bar_arrive(BAR_T + (wg ^ 1), 256);
    if (st > 0) {
      asm volatile("wgmma.wait_group.sync.aligned 1;" ::: "memory");
      if (lead) { const uint32_t e = sb + S_BAR + B_EMPTY + ((u - 1) & 3) * 8; mbar_arrive(e); mbar_arrive_remote(e + px); }
    }
  }
  asm volatile("wgmma.wait_group.sync.aligned 0;" ::: "memory");
  if (lead) { const uint32_t e = sb + S_BAR + B_EMPTY + ((u0 + NST - 1) & 3) * 8; mbar_arrive(e); mbar_arrive_remote(e + px); }
}
DEVINL void wg_publish(int wg) { bar_sync(BAR_G + wg, 160); }
DEVINL uint32_t km_known(uint32_t sb) { uint32_t v; asm volatile("ld.volatile.shared.u32 %0, [%1];" : "=r"(v) : "r"(sb + S_BAR + B_PROG) : "memory"); return __reduce_min_sync(~0u, v); }
DEVINL void km_load(uint4* f, const char* p) {
#pragma unroll
  for (int G = 0; G < 4; G++) f[G] = ldg_rlx128(p + G * 512);
}
DEVINL void km_check(uint4* f, const char* p, uint32_t tg) {
  int n = 0;
  while (__any_sync(~0u, (((f[0].x ^ tg) | (f[0].z ^ tg) | (f[1].x ^ tg) | (f[1].z ^ tg) | (f[2].x ^ tg) | (f[2].z ^ tg) | (f[3].x ^ tg) | (f[3].z ^ tg)) & 0x10000u) && ++n < POLL_LIMIT)) km_load(f, p);
}
DEVINL void km_watcher(uint32_t sb, const uint32_t* p) {
  uint32_t v = 0;
#pragma unroll 1
  for (int n = 0; n < 16 * POLL_LIMIT && v < 64; n++) {
    const uint2 q = ldg_rlx64(p);
    if (min(q.x, q.y) != v) { v = min(q.x, q.y); asm volatile("st.volatile.shared.u32 [%0], %1;" ::"r"(sb + S_BAR + B_PROG), "r"(v) : "memory"); }
    __nanosleep(v < 61 ? 300 : 20);
  }
}

template <int HF>
DEVINL void attend(const float* acc, uint4 (*kf)[4], uint4* kmf, uint4* op, const char* kvp, const char* mp, bf16* orow, int lane, int wg, uint32_t sb, int tile, bool& pend, uint32_t tg) {
  constexpr int NT = HF ? 4 : 2;
  const int g = lane >> 2, t = lane & 3;
  float sc[NT + 1][4];
#pragma unroll
  for (int k = 0; k < 8; k++) {
    uint32_t qa[4];
#pragma unroll
    for (int i = 0; i < 4; i++) { const float* a = acc + 32 * (k >> 2) + 4 * (k & 3) + 16 * (i >> 1) + 2 * (i & 1); qa[i] = pack_bf16(a[0], a[1]); }
#pragma unroll
    for (int kt = 0; kt <= NT; kt++) {
      const uint4 b = kt < NT ? kf[kt][k >> 1] : kmf[k >> 1];
      if (k == 0) mma16816z(sc[kt], qa, b.x, b.y); else if (k & 1) mma16816(sc[kt], qa, b.z, b.w); else mma16816(sc[kt], qa, b.x, b.y);
    }
  }
  FEN();
  bar_arrive(BAR_T + (wg ^ 1), 256);
  FEN();
  uint32_t go; asm volatile("{.reg .pred p,q; setp.ne.u32 q, %1, 0; bar.red.and.pred p, %2, 128, q; selp.u32 %0, 1, 0, p;}" : "=r"(go) : "r"((uint32_t)(tile < 30 && lds32(sb + S_BAR + B_PROG) > tile * 2 + 5)), "r"(BAR_V + wg) : "memory");
  uint4 vf[HF + 1][8], vm[4];
  auto traffic = [&]() {
    if (pend) {
#pragma unroll
      for (int q = 0; q < 4; q++) { *(uint4*)(orow - 128 * 4096 + q * 32) = op[2 * q]; *(uint4*)(orow - 120 * 4096 + q * 32) = op[2 * q + 1]; }
      wg_publish(wg);
    }
    pend = __any_sync(~0u, go);
    const char* vp = kvp + 4096 + (g >> 1) * 512 + ((g & 1) * 4 + t) * 16; const char* kp = kvp + 4 * 32 * 16384 + lane * 16;
    km_load(vm, mp + 2048 + lane * 16);
    if (pend) km_load(kmf, mp + 4 * 32 * 4096 + lane * 16);
#pragma unroll
    for (int hh = 0; hh <= HF; hh++) {
#pragma unroll
      for (int i = 0; i < 8; i++) { const char* q = vp + hh * 2048 + (i >> 2) * 4096 + (i & 3) * 128; vf[hh][i] = hh ? LDB(q) : LDA(q); }
      if (tile < 30) {
#pragma unroll
        for (int i = 8 * hh; i < 8 * hh + 8; i++) { const char* q = kp + ((i >> 1) & 1) * 12288 + (i >> 2) * 1024 + (i & 1) * 512; kf[i >> 2][i & 3] = hh ? LDB(q) : LDA(q); }
      }
    } };
  if (QORD == 0) traffic();
  const float NINF = __int_as_float(0xff800000);
  if (2 * t > g) { sc[NT - 2][0] = NINF; sc[NT - 1][2] = NINF; }
  if (2 * t + 1 > g) { sc[NT - 2][1] = NINF; sc[NT - 1][3] = NINF; }
  sc[NT - 1][0] = NINF; sc[NT - 1][1] = NINF;
  float m0 = fmaxf(sc[NT][0], sc[NT][1]), m1 = fmaxf(sc[NT][2], sc[NT][3]);
#pragma unroll
  for (int kt = 0; kt < NT; kt++) { m0 = fmaxf(m0, fmaxf(sc[kt][0], sc[kt][1])); m1 = fmaxf(m1, fmaxf(sc[kt][2], sc[kt][3])); }
  m0 = fmaxf(fmaxf(m0, __shfl_xor_sync(~0u, m0, 1)), fmaxf(__shfl_xor_sync(~0u, m0, 2), __shfl_xor_sync(~0u, m0, 3)));
  m1 = fmaxf(fmaxf(m1, __shfl_xor_sync(~0u, m1, 1)), fmaxf(__shfl_xor_sync(~0u, m1, 2), __shfl_xor_sync(~0u, m1, 3)));
  m0 *= -SM_SCALE; m1 *= -SM_SCALE;
  float s0 = 0.f, s1 = 0.f; uint32_t p[NT + 1][2];
#pragma unroll
  for (int kt = 0; kt <= NT; kt++) {
    const float a = ex2(fmaf(sc[kt][0], SM_SCALE, m0)), b = ex2(fmaf(sc[kt][1], SM_SCALE, m0)), c = ex2(fmaf(sc[kt][2], SM_SCALE, m1)), d = ex2(fmaf(sc[kt][3], SM_SCALE, m1));
    s0 += a + b; s1 += c + d; p[kt][0] = pack_bf16(a, b); p[kt][1] = pack_bf16(c, d);
  }
  s0 = (s0 + __shfl_xor_sync(~0u, s0, 1)) + (__shfl_xor_sync(~0u, s0, 2) + __shfl_xor_sync(~0u, s0, 3));
  s1 = (s1 + __shfl_xor_sync(~0u, s1, 1)) + (__shfl_xor_sync(~0u, s1, 2) + __shfl_xor_sync(~0u, s1, 3));
  s0 = rcp(s0); s1 = rcp(s1);
  if (QORD == 1) { FEN(); traffic(); }
  km_check(vm, mp + 2048 + lane * 16, tg);
  if (pend) km_check(kmf, mp + 4 * 32 * 4096 + lane * 16, tg);
#pragma unroll
  for (int grp = 0; grp < 4; grp++) {
    float o[4][4];
#pragma unroll
    for (int L = 0; L < 4; L++) {
      mma1688z(o[L], p[NT][0], p[NT][1], L == 0 ? vm[grp].x : L == 1 ? vm[grp].y : L == 2 ? vm[grp].z : vm[grp].w);
#pragma unroll
      for (int kh = 0; kh <= HF; kh++) {
        const uint4 w = vf[kh][(grp >> 1) * 4 + L]; const uint32_t A[4] = {p[2 * kh][0], p[2 * kh][1], p[2 * kh + 1][0], p[2 * kh + 1][1]};
        if (grp & 1) mma16816(o[L], A, w.z, w.w); else mma16816(o[L], A, w.x, w.y);
      }
    }
    op[2 * grp] = make_uint4(pack_bf16(o[0][0] * s0, o[0][1] * s0), pack_bf16(o[1][0] * s0, o[1][1] * s0), pack_bf16(o[2][0] * s0, o[2][1] * s0), pack_bf16(o[3][0] * s0, o[3][1] * s0));
    op[2 * grp + 1] = make_uint4(pack_bf16(o[0][2] * s1, o[0][3] * s1), pack_bf16(o[1][2] * s1, o[1][3] * s1), pack_bf16(o[2][2] * s1, o[2][3] * s1), pack_bf16(o[3][2] * s1, o[3][3] * s1));
  }
}

DEVINL void gemm_consumer(uint32_t sb, uint32_t px, int wg, int pr, int rank, const ArgsA& args) {
  const int lane = opaque(threadIdx.x & 31), w = __reduce_max_sync(~0u, (threadIdx.x >> 5) & 3);
  const bool lead = lane == 0 && w == 0;
  const int rot5 = pr % 5;
  if (wg == 1) bar_arrive(BAR_T, 256);
  if (threadIdx.x == 0) LOG(64 + pr * 2 + rank, 250);
#pragma unroll 1
  for (int tile = wg; tile < 32; tile += 2) {
    float acc[64];
    gemm_tile<128, 5, true>(acc, sb, px, wg, tile * 5, rot5, lead, tile < 2 ? 0 : -1);
    if (tile >= 30 && lead) mbar_arrive(sb + S_BAR + B_WD);
    char* dst = g_kv + (size_t)((tile * 2 + (w >> 1)) * 32 + pr) * 16384 + (w & 1) * 2048 + lane * 16;
    if (rank == 0) {
#pragma unroll
      for (int G = 0; G < 4; G++)
#pragma unroll
        for (int hh = 0; hh < 2; hh++) {
          const float* a = acc + 32 * (G >> 1) + 8 * (G & 1) + 2 * hh;
          *(uint4*)(dst + (G >> 1) * 12288 + hh * 1024 + (G & 1) * 512) = make_uint4(pack_bf16(a[0], a[1]), pack_bf16(a[16], a[17]), pack_bf16(a[4], a[5]), pack_bf16(a[20], a[21]));
        }
    } else {
#pragma unroll
      for (int i = 0; i < 8; i++) {
        const float* a = acc + (i >> 2) * 32 + (i & 3) * 4;
        *(uint4*)(dst + 4096 + (i >> 2) * 4096 + (i & 3) * 512) = make_uint4(movm(pack_bf16(a[0], a[1])), movm(pack_bf16(a[2], a[3])), movm(pack_bf16(a[16], a[17])), movm(pack_bf16(a[18], a[19])));
      }
    }
    wg_publish(wg);
    if ((threadIdx.x & 127) == 0) LOG(64 + pr * 2 + rank, tile);
  }
  if (threadIdx.x == 0) LOG(64 + pr * 2 + rank, 251);
  if (pr < 16) {
    const int h = 2 * pr + rank;
    flag_wait_warp(args.flags + F_KV + h * 32 + 16 + (lane & 1), 2);
    bool pend = false; uint4 op[8], kf[4][4], kmf[4];
#pragma unroll
    for (int i = 0; i < 16; i++) kf[i >> 2][i & 3] = ldg_cg128(g_kv + (size_t)((wg * 2 + (w >> 1)) * 32 + h) * 16384 + ((i >> 1) & 1) * 12288 + (i >> 2) * 1024 + (i & 1) * 512 + lane * 16);
#pragma unroll
    for (int i = 0; i < 8; i++) op[i] = kmf[i & 3] = make_uint4(0, 0, 0, 0);
#pragma unroll 1
    for (int tile = wg; tile < 32; tile += 2) {
      const uint32_t seg = tile * 2 + (w >> 1);
      const char* kvp = g_kv + (size_t)(seg * 32 + h) * 16384;
      const char* mp = g_kvm + (size_t)(seg * 32 + h) * 4096;
      bf16* orow = g_o + (size_t)(tile * 64 + w * 16 + (lane >> 2)) * 4096 + h * 128 + (lane & 3) * 8;
      if ((tile >> 1) == 6) flag_wait_warp(args.flags + F_KV + h * 32 + 30 + (lane & 1), 2);
      float acc[64];
      gemm_tile<128, 5, false>(acc, sb, px, wg, 160 + tile * 5, rot5, lead, tile < 2 ? 1 : -1);
      if ((threadIdx.x & 127) == 96) LOG(64 + pr * 2 + rank, 64 + tile);
      if (!pend) {
        int n = 0;
        while (km_known(sb) <= seg && ++n < 16 * POLL_LIMIT) {}
        km_load(kmf, mp + lane * 16);
        km_check(kmf, mp + lane * 16, (args.layer ^ 1) << 16);
      }
      if ((threadIdx.x & 127) == 96) LOG(64 + pr * 2 + rank, 96 + tile);
      if (w & 1) attend<1>(acc, kf, kmf, op, kvp, mp, orow, lane, wg, sb, tile, pend, (args.layer ^ 1) << 16); else attend<0>(acc, kf, kmf, op, kvp, mp, orow, lane, wg, sb, tile, pend, (args.layer ^ 1) << 16);
      if (!pend) {
#pragma unroll
        for (int q = 0; q < 4; q++) { *(uint4*)(orow + q * 32) = op[2 * q]; *(uint4*)(orow + 8 * 4096 + q * 32) = op[2 * q + 1]; }
        wg_publish(wg);
      }
      if ((threadIdx.x & 127) == 0) LOG(64 + pr * 2 + rank, 32 + tile);
    }
  } else {
    const int kq = (pr - 16) >> 2, cg = 2 * (pr & 3) + rank;
#pragma unroll 1
    for (int tile = wg; tile < 32; tile += 2) {
      float acc[40];
      gemm_tile<80, 8, true>(acc, sb, px, wg, 160 + tile * 8, (pr & 3) * 2, lead, tile < 2 ? 1 : -1);
      const bool odd = lane & 1;
      bf16* dst = g_part + (size_t)(kq * 2048 + tile * 64 + w * 16 + (lane >> 2)) * 640 + cg * 80 + (lane & 1) * 8 + (lane & 2) * 2;
#pragma unroll
      for (int q = 0; q < 5; q++)
#pragma unroll
        for (int hh = 0; hh < 2; hh++) {
          const uint32_t A = pack_bf16(acc[8 * q + 2 * hh], acc[8 * q + 2 * hh + 1]), B = pack_bf16(acc[8 * q + 4 + 2 * hh], acc[8 * q + 5 + 2 * hh]);
          const uint32_t x = __shfl_xor_sync(~0u, odd ? A : B, 1);
          *(uint2*)(dst + hh * 8 * 640 + q * 16) = odd ? make_uint2(x, B) : make_uint2(A, x);
        }
      wg_publish(wg);
      if ((threadIdx.x & 127) == 0) LOG(64 + pr * 2 + rank, 32 + tile);
    }
  }
  if (wg == 0) bar_sync(BAR_T, 256);
}

DEVINL void gemm_producer(uint32_t sb, int pr, int rank, const ArgsA& args, const CUtensorMap* tq, const CUtensorMap* tk, const CUtensorMap* tv,
                          const CUtensorMap* to32, const CUtensorMap* tx, const CUtensorMap* tao) {
  const uint32_t bWF = sb + S_BAR + B_WF;
  auto load_w = [&](const CUtensorMap* tm, int col, int st) {
    const int r = ((st + pr) % 5) * 2; mbar_arrive_tx(bWF + st * 8, 32768);
#pragma unroll 1
    for (int i = 0; i < 4; i++) tma_2d(sb + (i & 1) * 81920 + (r + (i >> 1)) * 8192, tm, col + (i & 1) * 64, (r + (i >> 1)) * 64, bWF + st * 8); };
  auto att_pf = [&](int tile, int st) {
    if (tile >= 32) return;
    const int q = tile * 64 + 2 * pr + rank;
    if (st < 4) l2_prefetch(g_kv + (size_t)(q + (st >> 1) * 32) * 16384 + (st & 1) * 8192, 8192);
    else if (lds32(sb + S_BAR + B_PROG) > tile * 2 + 1) { l2_prefetch(g_kvm + (size_t)q * 4096, 4096); l2_prefetch(g_kvm + (size_t)(q + 32) * 4096, 4096); } };
  uint32_t u = 0;
  auto push = [&](const CUtensorMap* tm, int c0, int c1) {
    const uint32_t slot = u & 3, full = sb + S_BAR + B_FULL + slot * 8;
    mbar_wait(sb + S_BAR + B_EMPTY + slot * 8, ((u >> 2) & 1) ^ 1);
    mbar_arrive_tx(full, 16384);
    tma_2d_mc(sb + G_ST + slot * 16384 + rank * 8192, tm, c0 + rank * 64, c1, full);
    u++; };
#pragma unroll 1
  for (int st = 0; st < 5; st++) load_w(rank ? tv : tk, pr * 128, st);
  if (args.layer == 0) { flag_wait(args.flags + F_X, 128); fence_proxy_async(); } else pdl_wait();
#pragma unroll 1
  for (int tile = 0; tile < 32; tile++) {
    l2_prefetch((const char*)g_xn + ((tile + 2) & 31) * 81920 + (pr * 2 + rank) * 1280, 1280);
#pragma unroll 1
    for (int st = 0; st < 5; st++) {
      push(tx, ((st + pr) % 5) * 128, tile * 64);
      if (tile >= PF0 && tile < PF0 + 16) {
        const int q = (tile - PF0) * 5 + st; const char* src = (rank ? args.wo : args.wq) + (pr * 80 + q) * 2048;
        if (PFR) { if (q == 0) mbar_arrive_tx(sb + S_BAR + B_DUM, 163840); bulk_g2s(sb + S_END, src, 1024, sb + S_BAR + B_DUM); bulk_g2s(sb + S_END, src + 1024, 1024, sb + S_BAR + B_DUM); }
        else l2_prefetch(src, 2048);
      }
      if (pr < 16 && tile >= 32 - PFD) att_pf(tile + PFD - 32, st);
    }
  }
  pdl_launch();
  if (pr < 16) {
    load_w(tq, (2 * pr + rank) * 128, 0);
#pragma unroll 1
    for (int tile = 0; tile < 32; tile++) {
      if (tile < 30) l2_prefetch((const char*)g_xn + (tile + 2) * 81920 + (pr * 2 + rank) * 2560, 2560);
#pragma unroll 1
      for (int st = 0; st < 5; st++) { push(tx, ((st + pr) % 5) * 128, tile * 64); if (tile == 0 && st < 4) load_w(tq, (2 * pr + rank) * 128, st + 1); att_pf(tile + PFD, st); }
    }
  } else {
    const int kq = (pr - 16) >> 2, cg = 2 * (pr & 3) + rank;
    mbar_wait(sb + S_BAR + B_WD, 0);
    mbar_arrive_tx(bWF, 163840);
#pragma unroll 1
    for (int i = 0; i < 20; i++) { tma_2d(sb + (i % 5) * 32768 + (i / 5) * 8192, to32, cg * 80 + (i % 5) * 16, kq * 1024 + (i / 5) * 256, bWF); __nanosleep(OPACE); }
#pragma unroll 1
    for (int tile = 0; tile < 32; tile++) {
      flag_wait(args.flags + F_O + tile * 4 + kq, 8);
      fence_proxy_async();
#pragma unroll 1
      for (int st = 0; st < 8; st++) push(tao, kq * 1024 + ((st + (pr & 3) * 2) & 7) * 128, tile * 64);
    }
  }
  if (PFR) mbar_wait(sb + S_BAR + B_DUM, 0);
#pragma unroll 1
  for (int i = 0; i < 4; i++, u++) mbar_wait(sb + S_BAR + B_EMPTY + (u & 3) * 8, ((u >> 2) & 1) ^ 1);
}

DEVINL void gemm_publisher(int wg, int pr, int rank, const ArgsA& args) {
#pragma unroll 1
  for (int i = 0; i < 32; i++) {
    const int tile = (i & 15) * 2 + wg;
    bar_sync(BAR_G + wg, 160);
    if ((threadIdx.x & 31) == 0) {
      flag_add(args.flags + (i < 16 ? F_KV + pr * 32 + tile : pr < 16 ? F_O + tile * 4 + (pr >> 2) : F_P + tile * 32));
    }
    __syncwarp();
  }
}

DEVINL void filter_prep(uint32_t* sm, int part, const ArgsA& args) {
  const int tid = threadIdx.x, lane = tid & 31, w = tid >> 5;
  const unsigned short* wr = (const unsigned short*)args.wr; const unsigned short* wi = (const unsigned short*)args.wi;
#pragma unroll 1
  for (int it = part; it < 32; it += 4) {
#pragma unroll 1
    for (int rr = 0; rr < 8; rr += 2) {
      uint32_t a[2][11], b[2][11];
#pragma unroll
      for (int r = 0; r < 2; r++) {
        const int pos = it * 64 + w * 8 + rr + r, th = (pos >> 2) & 127, v = (pos >> 9) * 4 + (pos & 3);
        const int o = ((th >> 3) + 16 * ((th & 7) + (v & 8)) + 256 * (v & 7)) * 321 + lane;
#pragma unroll
        for (int c = 0; c < 11; c++) if (c < 10 || lane == 0) { a[r][c] = wr[o + c * 32]; b[r][c] = wi[o + c * 32]; }
      }
#pragma unroll
      for (int r = 0; r < 2; r++)
#pragma unroll
        for (int c = 0; c < 11; c++) if (c < 10 || lane == 0) sm[(c * 32 + lane) * 65 + w * 8 + rr + r] = a[r][c] | (b[r][c] << 16);
    }
    bar_sync(1, 256);
#pragma unroll 2
    for (int i = tid; i < 64 * 321; i += 256) g_wt[(i >> 6) * 2048 + it * 64 + (i & 63)] = sm[(i >> 6) * 65 + (i & 63)];
    bar_sync(1, 256);
  }
  if (tid == 0) flag_add(args.flags + F_W);
}

__global__ void __cluster_dims__(2, 1, 1) __launch_bounds__(384, 1)
layer_a_kernel(const __grid_constant__ CUtensorMap tq, const __grid_constant__ CUtensorMap tk, const __grid_constant__ CUtensorMap tv,
               const __grid_constant__ CUtensorMap to, const __grid_constant__ CUtensorMap to32, const __grid_constant__ CUtensorMap tx,
               const __grid_constant__ CUtensorMap tao, const __grid_constant__ ArgsA args) {
  extern __shared__ __align__(1024) char smraw[];
  const uint32_t sb = (smem_u32(smraw) + 1023) & ~1023u;
  uint32_t rank; asm volatile("mov.u32 %0, %%cluster_ctarank;" : "=r"(rank));
  rank = __reduce_max_sync(~0u, rank);
  const uint32_t px = __reduce_max_sync(~0u, mapa(sb, rank ^ 1) - sb);
  if (args.layer == 0) LOGK(0, 0);
  uint32_t smid; asm volatile("mov.u32 %0, %%smid;" : "=r"(smid));
  const uint32_t b = sb + S_BAR;
  if (threadIdx.x == 320) {
    mbar_init(b + B_W, 1); mbar_init(b + B_W2, 1); mbar_init(b + B_WV, 1); mbar_init(b + B_WO, 1); mbar_init(b + B_S, 9); mbar_init(b + B_KV, 1); mbar_init(b + B_KV + 8, 1);
    for (int i = 0; i < 4; i++) { mbar_init(b + B_FULL + i * 8, 1); mbar_init(b + B_EMPTY + i * 8, 2); }
    for (int i = 0; i < 5; i++) mbar_init(b + B_WF + i * 8, 1);
    mbar_init(b + B_WD, 2); mbar_init(b + B_RB, 1); mbar_init(b + B_DUM, 1); sts32(b + B_PROG, 0);
    mbar_arrive_tx(b + B_RB, 8);
    asm volatile("fence.mbarrier_init.release.cluster;" ::: "memory");
  }
  __syncwarp();
  asm volatile("barrier.cluster.arrive.relaxed.aligned;" ::: "memory");
  uint32_t role = 0; uint4 xr[5];
  const bool ln = args.layer == 0 && blockIdx.x < 128 && threadIdx.x < 256;
  const size_t off = (size_t)(blockIdx.x * 16 + (threadIdx.x >> 4)) * 640 + (threadIdx.x & 15) * 8;
#pragma unroll
  for (int i = 0; i < 5; i++) xr[i] = ldg128_if(args.x + off + i * 128, ln);
  if (rank == 0 && threadIdx.x >= 256 && threadIdx.x < 320) {
    if (args.layer == 0) {
      uint32_t* p = (uint32_t*)(args.comm + 0x20000 + (threadIdx.x < 288 ? 0x1000 : 0) + (blockIdx.x >> 1) * 32);
      if ((threadIdx.x & 31) < 8) p[threadIdx.x & 31] = 0;
      __syncwarp();
      if ((threadIdx.x & 31) == 0) {
        uint32_t v, best = ~0u;
#pragma unroll 1
        for (int i = 0; i < NPROBE; i++) { const uint32_t t0 = clk(); asm volatile("atom.relaxed.gpu.global.add.u32 %0, [%1], 1;" : "=r"(v) : "l"(p) : "memory"); asm volatile("st.volatile.shared.u32 [%0], %1;" ::"r"(b + 216), "r"(v) : "memory"); best = min(best, clk() - t0); }
        sts32(b + 208 + ((threadIdx.x >> 5) & 1) * 4, best);
      }
      bar_sync(1, 64);
    }
    if (threadIdx.x == 256) {
      int d;
      if (args.layer == 0) { d = (int)(lds32(b + 208) - lds32(b + 212)); g_side[smid & 254] = d; g_side[(smid & 254) + 1] = d; } else d = g_side[smid & 255];
      uint32_t* cnt = args.flags + F_ROLE;
      if (d < 0) { role = atomicAdd(cnt, 1); if (role >= 32) role = 32 + atomicAdd(cnt + 1, 1); }
      else { role = 32 + atomicAdd(cnt + 1, 1); if (role >= 66) role = atomicAdd(cnt, 1); }
    }
    __syncwarp();
  }
  asm volatile("barrier.cluster.wait.aligned;" ::: "memory");
  if (rank == 0 && threadIdx.x == 256) { stasync64(b + B_ROLE, role, 0, b + B_RB); stasync64(b + B_ROLE + px, role, 0, b + B_RB + px); }
  if (ln) {
    float f[40];
#pragma unroll
    for (int i = 0; i < 5; i++) unpack8(xr[i], f + 8 * i);
    ln_row(f);
#pragma unroll
    for (int i = 0; i < 5; i++) *(uint4*)(g_xn + off + i * 128) = pack8(f + 8 * i);
    bar_sync(2, 256);
    if (threadIdx.x == 0) flag_add(args.flags + F_X);
  }
  __syncwarp();
  mbar_wait(b + B_RB, 0);
  role = __reduce_max_sync(~0u, lds32(b + B_ROLE));
  if (threadIdx.x == 352 && args.layer == 0) g_role[smid & 255] = role * 2 + rank;
  if (role != 32) pdl_launch();
  const int wg = __reduce_max_sync(~0u, threadIdx.x >> 7);
  auto U = [](uint32_t x) { return __reduce_max_sync(~0u, opaque(x)); };
  if (wg < 2) {
    asm volatile("setmaxnreg.inc.sync.aligned.u32 224;");
    if (role >= 32) {
      if (role >= 64) { if (args.layer == 0) { filter_prep((uint32_t*)smraw, (role - 64) * 2 + rank, args); if (threadIdx.x == 0) LOG(role * 2 + rank, 0); } }
      else gemm_consumer(U(sb), U(px), U(wg), U(role - 32), U(rank), args);
    } else { if (wg == 0) chain_mma<0>(sb, args); else chain_mma<1>(sb, args); }
  } else {
    asm volatile("setmaxnreg.dec.sync.aligned.u32 56;");
    if (role >= 32) {
      if (role < 64) {
        if (threadIdx.x == 256) gemm_producer(sb, role - 32, rank, args, &tq, &tk, &tv, &to32, &tx, &tao);
        else if (threadIdx.x >= 288 && threadIdx.x < 352) gemm_publisher((threadIdx.x >> 5) - 9, role - 32, rank, args);
        else if (threadIdx.x == 352 && role < 48) km_watcher(sb, args.flags + F_KM + (2 * (role - 32) + rank) * 32);
      }
    } else chain_helper(U(sb), U(px), U(role), U(rank), args, &tq, &tk, &tv, &to);
  }
}

DEVINL float2 cadd(float2 a, float2 b) { return make_float2(a.x + b.x, a.y + b.y); }
DEVINL float2 csub(float2 a, float2 b) { return make_float2(a.x - b.x, a.y - b.y); }
DEVINL float2 cmul(float2 a, float2 b) { return make_float2(fmaf(a.x, b.x, -a.y * b.y), fmaf(a.x, b.y, a.y * b.x)); }
DEVINL float2 cmulc(float2 a, float2 b) { return make_float2(fmaf(a.x, b.x, a.y * b.y), fmaf(a.y, b.x, -a.x * b.y)); }
template <int INV> DEVINL float2 ctw(float2 a, float2 w) { return INV ? cmulc(a, w) : cmul(a, w); }
template <int INV> DEVINL float2 rot(float2 a) { return INV ? make_float2(-a.y, a.x) : make_float2(a.y, -a.x); }
template <int INV> DEVINL void fft4(float2& a, float2& b, float2& c, float2& d) {
  const float2 s0 = cadd(a, c), d0 = csub(a, c), s1 = cadd(b, d), d1 = rot<INV>(csub(b, d));
  a = cadd(s0, s1); b = cadd(d0, d1); c = csub(s0, s1); d = csub(d0, d1);
}
template <int INV> DEVINL float2 w8(float2 a) { const float h = 0.70710678118654752f; const float2 r = rot<INV>(a); return make_float2((a.x + r.x) * h, (a.y + r.y) * h); }
template <int INV> DEVINL void fft8(float2* x) {
  fft4<INV>(x[0], x[2], x[4], x[6]); fft4<INV>(x[1], x[3], x[5], x[7]);
  const float2 e0 = x[0], e1 = x[2], e2 = x[4], e3 = x[6], o0 = x[1], o1 = w8<INV>(x[3]), o2 = rot<INV>(x[5]), o3 = rot<INV>(w8<INV>(x[7]));
  x[0] = cadd(e0, o0); x[1] = cadd(e1, o1); x[2] = cadd(e2, o2); x[3] = cadd(e3, o3);
  x[4] = csub(e0, o0); x[5] = csub(e1, o1); x[6] = csub(e2, o2); x[7] = csub(e3, o3);
}
template <int INV> DEVINL void fft16(float2* x) {
  const float c = 0.92387953251128674f, s = 0.38268343236508977f;
  const float2 w1 = make_float2(c, -s), w3 = make_float2(s, -c);
#pragma unroll
  for (int i = 0; i < 4; i++) fft4<INV>(x[i], x[i + 4], x[i + 8], x[i + 12]);
  x[5] = ctw<INV>(x[5], w1); x[9] = w8<INV>(x[9]); x[13] = ctw<INV>(x[13], w3);
  x[6] = w8<INV>(x[6]); x[10] = rot<INV>(x[10]); x[14] = rot<INV>(w8<INV>(x[14]));
  x[7] = ctw<INV>(x[7], w3); x[11] = rot<INV>(w8<INV>(x[11])); x[15] = ctw<INV>(x[15], make_float2(-c, s));
#pragma unroll
  for (int k = 0; k < 4; k++) fft4<INV>(x[4 * k], x[4 * k + 1], x[4 * k + 2], x[4 * k + 3]);
#pragma unroll
  for (int k = 0; k < 4; k++)
#pragma unroll
    for (int m = k + 1; m < 4; m++) { const float2 t = x[4 * k + m]; x[4 * k + m] = x[4 * m + k]; x[4 * m + k] = t; }
}
template <int INV> DEVINL void fft5(float2& x0, float2& x1, float2& x2, float2& x3, float2& x4) {
  const float c1 = 0.30901699437494742f, c2 = -0.80901699437494742f, s1 = 0.95105651629515357f, s2 = 0.58778525229247313f;
  const float2 a1 = cadd(x1, x4), a2 = cadd(x2, x3), b1 = rot<INV>(csub(x1, x4)), b2 = rot<INV>(csub(x2, x3));
  const float2 p1 = make_float2(fmaf(c1, a1.x, fmaf(c2, a2.x, x0.x)), fmaf(c1, a1.y, fmaf(c2, a2.y, x0.y)));
  const float2 p2 = make_float2(fmaf(c2, a1.x, fmaf(c1, a2.x, x0.x)), fmaf(c2, a1.y, fmaf(c1, a2.y, x0.y)));
  const float2 q1 = make_float2(fmaf(s1, b1.x, s2 * b2.x), fmaf(s1, b1.y, s2 * b2.y));
  const float2 q2 = make_float2(fmaf(s2, b1.x, -s1 * b2.x), fmaf(s2, b1.y, -s1 * b2.y));
  x0 = cadd(x0, cadd(a1, a2)); x1 = cadd(p1, q1); x4 = csub(p1, q1); x2 = cadd(p2, q2); x3 = csub(p2, q2);
}
template <int INV> DEVINL void fft20(const float2* in, float2* out) {
  float2 t[4][5];
#pragma unroll
  for (int a = 0; a < 4; a++) {
#pragma unroll
    for (int b = 0; b < 5; b++) t[a][b] = in[(5 * a + 4 * b) % 20];
    fft5<INV>(t[a][0], t[a][1], t[a][2], t[a][3], t[a][4]);
  }
#pragma unroll
  for (int d = 0; d < 5; d++) {
    fft4<INV>(t[0][d], t[1][d], t[2][d], t[3][d]);
#pragma unroll
    for (int c = 0; c < 4; c++) out[(5 * c + 16 * d) % 20] = t[c][d];
  }
}
constexpr int ZP = 336;
struct RowSmem { float2 T[320 * 17]; uint32_t Z[16 * ZP]; float2 tw[320]; float2 tp[160]; };
DEVINL float2 cis(int k, int n) {
  float sn, cs; __sincosf((float)(2 * k > n ? k - n : k) * (-6.283185307179586f / (float)n), &sn, &cs); return make_float2(cs, sn);
}
DEVINL void row_tables(RowSmem& sm) {
  const int t = threadIdx.x;
  sm.tw[t] = cis((t >> 4) * (t & 15), 320);
  if (t < 160) sm.tp[t] = cis(t, 640);
}

#define WCH 10240
#define WST 2
#define CREG 80
#define IREG 88
#define YPT 1
#define R1E 1
#define IDRY 0
#define CDRY 0
#define RDRY 1

__global__ void __launch_bounds__(320, 1) rows_fwd_kernel(const bf16* __restrict__ xin, const uint32_t* flags) {
  extern __shared__ __align__(1024) char smraw[]; RowSmem& sm = *(RowSmem*)smraw;
  const int tid = threadIdx.x, wp = __reduce_max_sync(~0u, tid >> 5), nr = blockIdx.x < 124 ? 16 : 8, s0 = blockIdx.x < 124 ? blockIdx.x * 16 : 992 + blockIdx.x * 8;
  const uint32_t* flag = flags + F_P + (s0 >> 6) * 32;
  LOGK(1 + 3 * (xin == g_x), 0);
  if (R1E) pdl_launch();
  if (tid == 0) l2_prefetch(xin + s0 * 640, nr * 1280);
  row_tables(sm);
#pragma unroll 1
  for (int live = !RDRY || wp != 1 || __any_sync(~0u, ldg_rlx32(flag) >= 32); live < 2; live++) {
    if (live) {
      if (wp == 0) { uint32_t v; int n = 0;
        while (true) { asm volatile("ld.acquire.gpu.global.u32 %0, [%1];" : "=r"(v) : "l"(flag) : "memory"); if (__all_sync(~0u, v >= 32 || ++n >= 8 * POLL_LIMIT)) break; __nanosleep(v ? 20 : 200); } }
      __syncthreads();
      if (!R1E) pdl_launch();
      LOGK(1 + 3 * (xin == g_x), 1);
    }
    if (wp * 2 < nr) {
      const int row = tid >> 4, j = tid & 15; const size_t off = (size_t)(s0 + row) * 640 + j * 8;
      float f[40]; uint4 in[5][5];
#pragma unroll
      for (int i = 0; i < 5; i++) {
#pragma unroll
        for (int q = 0; q < 4; q++) in[i][q] = ldg128_if(g_part + q * 2048 * 640 + off + i * 128, live);
        in[i][4] = ldg128_if(xin + off + i * 128, live);
      }
#pragma unroll
      for (int i = 0; i < 5; i++) {
        float a[8], b[8], c[8], d[8];
        unpack8(in[i][0], a); unpack8(in[i][1], b); unpack8(in[i][2], c); unpack8(in[i][3], d);
#pragma unroll
        for (int e = 0; e < 8; e++) a[e] = (a[e] + b[e]) + (c[e] + d[e]);
        const uint4 o = pack8(a), x = in[i][4];
        const uint4 r = make_uint4(hadd2bf(o.x, x.x), hadd2bf(o.y, x.y), hadd2bf(o.z, x.z), hadd2bf(o.w, x.w));
        stg128_if(g_x + off + i * 128, r, live); unpack8(r, f + 8 * i);
      }
      ln_row(f);
#pragma unroll
      for (int i = 0; i < 5; i++) *(uint4*)(sm.Z + row * ZP + i * 64 + j * 4) = pack8(f + 8 * i);
      __syncwarp();
      float2 z[20], y[20];
#pragma unroll
      for (int n1 = 0; n1 < 20; n1++) { const uint32_t w = sm.Z[row * ZP + n1 * 16 + j]; z[n1] = make_float2(bf_lo(w), bf_hi(w)); }
      fft20<0>(z, y);
#pragma unroll
      for (int k1 = 1; k1 < 20; k1++) y[k1] = cmul(y[k1], sm.tw[k1 * 16 + j]);
#pragma unroll
      for (int k1 = 0; k1 < 20; k1++) sm.T[(k1 * 16 + j) * 17 + row] = y[k1];
    }
    if (live) __syncthreads();
    const int up = (tid >> 4) & 1, row = tid & 15, k1 = wp ? (up ? 20 - wp : wp) : up * 10;
    float2 x[16];
#pragma unroll
    for (int n2 = 0; n2 < 16; n2++) x[n2] = sm.T[(k1 * 16 + n2) * 17 + row];
    float2 tp[8];
#pragma unroll
    for (int k2 = 0; k2 < 8; k2++) tp[k2] = sm.tp[k1 + 20 * k2];
    fft16<0>(x);
    uint32_t* ya = g_y + s0 + row + k1 * 2048; uint32_t* yb = g_y + s0 + row + (320 - k1) * 2048;
    const int on = live && row < nr;
    stg32_if(g_y + s0 + row + 160 * 2048, pack_f16(2.f * x[8].x, -2.f * x[8].y), on && k1 == 0);
    const int src = (tid & 31) ^ (wp ? 16 : 0); uint32_t wa[8], wb[8];
#pragma unroll
    for (int k2 = 0; k2 < 8; k2++) {
      const float2 c = k1 ? x[15 - k2] : x[(16 - k2) & 15], b = make_float2(__shfl_sync(~0u, c.x, src), __shfl_sync(~0u, c.y, src)), a = x[k2];
      const float2 E = make_float2(a.x + b.x, a.y - b.y), O = cmul(make_float2(a.y + b.y, b.x - a.x), tp[k2]);
      wa[k2] = pack_f16(E.x + O.x, E.y + O.y); wb[k2] = pack_f16(E.x - O.x, O.y - E.y);
    }
#pragma unroll
    for (int k2 = 0; k2 < 8; k2++) { stg32_if(ya + k2 * 20 * 2048, wa[k2], on); stg32_if(yb - k2 * 20 * 2048, wb[k2], on); }
  }
  LOGK(1 + 3 * (xin == g_x), 2);
  if (blockIdx.x == gridDim.x - 1) pdl_wait();
}

__global__ void __maxnreg__(CREG) cols_kernel(int layer) {
  extern __shared__ __align__(1024) char smraw[];
  const int sub = threadIdx.x >> 7, tid = threadIdx.x & 127, col = blockIdx.x * 3 + sub, k1 = tid >> 3, j0 = tid & 7;
  float2* sm = (float2*)smraw + sub * (16 * 152);
  float2* tw = (float2*)smraw + 3 * 16 * 152;
  LOGK(2 + 3 * layer, 0);
  pdl_launch();
  uint32_t* y = g_y + col * 2048 + tid;
  uint4 wf[4];
  flag_wait_warp(g_flags + F_W, 4);
#pragma unroll
  for (int i = 0; i < 4; i++) wf[i] = ldg_cg128(g_wt + col * 2048 + i * 512 + tid * 4);
  if (YPT) {
#pragma unroll
    for (int i = 0; i < 4; i++) asm volatile("cp.async.cg.shared.global [%0], [%1], 16;" ::"r"(smem_u32(sm) + tid * 16), "l"(g_y + col * 2048 + min(i * 512 + tid * 4, 1916)) : "memory");
  }
#pragma unroll 1
  for (int i = threadIdx.x; i < 2176; i += 384) {
    const int a = i < 2048 ? i >> 7 : (i - 2048) >> 3, b = i < 2048 ? i & 127 : i & 7;
    tw[i < 2048 ? a * 136 + b : 2176 + a * 9 + b] = cis(i < 2048 ? a * b : a * b * 16, 2048);
  }
  asm volatile("cp.async.wait_all;" ::: "memory");
  float2* reg = sm + k1 * 152;
#pragma unroll 1
  for (int live = !CDRY || __any_sync(~0u, threadIdx.x >= 32 || ldg_rlx32(g_flags + layer * F_LAYER + F_P + 31 * 32) >= CDRY); live < 2; live++)
#pragma unroll
  for (int it = 0; it < 4; it++) {
    float2 x[16];
    if (it == 0) {
      if (live) { __syncthreads(); pdl_wait(); LOGK(2 + 3 * layer, 1); }
#pragma unroll
      for (int i = 0; i < 16; i++) { const uint32_t w = ldg32_if(y + i * 128, live); x[i] = __half22float2(*(const __half2*)&w); }
    } else {
      const float2* in = it == 3 ? sm + tid : reg + j0; const int is = it == 1 ? 8 : it == 2 ? 9 : 152;
#pragma unroll
      for (int i = 0; i < 16; i++) x[i] = in[i * is];
    }
    fft16<0>(x);
    if (it == 3) {
      const float sc = 1.f / 4096.f;
#pragma unroll
      for (int i = 0; i < 16; i++) stg32_if(y + i * 128, pack_bf16(x[i].y * sc, x[i].x * sc), live);
    } else {
      const float2* t = it == 0 ? tw + tid : it == 1 ? tw + 2176 + j0 : tw + k1 * 136 + j0; const int ts = it == 0 ? 136 : it == 1 ? 9 : 8;
      float2* o = it == 0 ? sm + tid : reg + j0; const int os = it == 0 ? 152 : it == 1 ? 9 : 8;
#pragma unroll
      for (int k = 0; k < 16; k++) if (k > 0 || it == 2) x[k] = cmul(x[k], t[k * ts]);
      __syncwarp();
#pragma unroll
      for (int k = 0; k < 16; k++) o[k * os] = x[k];
      if (it == 1) {
        __syncwarp();
        float2* r9 = reg + j0 * 9;
#pragma unroll
        for (int i = 0; i < 16; i++) x[i] = r9[(i & 8) * 9 + (i & 7)];
#pragma unroll
        for (int h = 0; h < 2; h++) {
          fft8<0>(x); fft8<0>(x + 8);
          if (h == 0) {
#pragma unroll
            for (int i = 0; i < 16; i++) {
              const uint32_t w = (i & 3) == 0 ? wf[i >> 2].x : (i & 3) == 1 ? wf[i >> 2].y : (i & 3) == 2 ? wf[i >> 2].z : wf[i >> 2].w;
              const float2 v = cmul(x[i], make_float2(bf_lo(w), bf_hi(w))); x[i] = make_float2(v.y, v.x);
            }
          }
        }
        const float2* t9 = tw + 2176 + j0 * 9;
#pragma unroll
        for (int i = 0; i < 16; i++) if (i & 7) x[i] = cmul(x[i], t9[(i & 8) * 9 + (i & 7)]);
#pragma unroll
        for (int i = 0; i < 16; i++) r9[(i & 8) * 9 + (i & 7)] = x[i];
        __syncwarp();
      } else if (live) bar_sync(sub + 1, 128);
    }
  }
  LOGK(2 + 3 * layer, 2);
}

__global__ void __maxnreg__(IREG) rows_inv_kernel(bf16* __restrict__ xout, int do_ln, const __grid_constant__ Wts w) {
  extern __shared__ __align__(1024) char smraw[]; RowSmem& sm = *(RowSmem*)smraw;
  const int tid = threadIdx.x, s0 = blockIdx.x * 16, wp = __reduce_max_sync(~0u, tid >> 5);
  LOGK(3 + 3 * !do_ln, 0);
  const uint32_t ctl = smem_u32(smraw) + 72 * 1024;
  if (tid == 0) sts32(ctl + 8, 0);
  __syncthreads();
  if (wp == 10) { if (WCH && do_ln && tid == 320) weight_warm<WCH ? WCH : 16>(w, ctl + 1024, ctl, ctl + 8); return; }
  if (tid == 0) l2_prefetch(g_x + s0 * 640, 20480);
  row_tables(sm);
  const size_t off = (size_t)(s0 + ((tid >> 4) & 15)) * 640 + (tid & 15) * 8;
#pragma unroll 1
  for (int live = wp != 1 || (!IDRY && do_ln < 2); live < 2; live++) {
    if (live) {
      bar_sync(1, 320);
      pdl_wait();
      pdl_launch();
      if (WST == 0 && tid == 0) sts32(ctl + 8, 1);
      LOGK(3 + 3 * !do_ln, 1);
    }
    uint4 xr[5];
    {
      const int up = (tid >> 4) & 1, row = tid & 15, k1 = wp ? (up ? 20 - wp : wp) : up * 10;
      const uint32_t* ya = g_y + s0 + row + k1 * 2048; const uint32_t* yb = g_y + s0 + row + (320 - k1) * 2048;
      uint32_t wa[8], wb[8];
#pragma unroll
      for (int k2 = 0; k2 < 8; k2++) { wa[k2] = ldg32_if(ya + k2 * 20 * 2048, live); wb[k2] = ldg32_if(yb - k2 * 20 * 2048, live); }
      const uint32_t wm = ldg32_if(g_y + s0 + row + 160 * 2048, live && k1 == 0);
#pragma unroll
      for (int i = 0; i < 5; i++) xr[i] = ldg128_if(g_x + off + i * 128, live && wp < 8);
      stg32_if(g_flags + blockIdx.x * 320 + tid, 0, live && !do_ln && blockIdx.x * 320 + tid < 2 * F_LAYER);
      if (k1 == 0) { wa[0] &= 0xffffu; wb[0] &= 0xffffu; }
      float2 x[16], r[8];
#pragma unroll
      for (int k2 = 0; k2 < 8; k2++) {
        const float2 a = make_float2(bf_lo(wa[k2]), bf_hi(wa[k2])), b = make_float2(bf_lo(wb[k2]), bf_hi(wb[k2]));
        const float2 E = make_float2(a.x + b.x, a.y - b.y), O = cmulc(make_float2(a.x - b.x, a.y + b.y), sm.tp[k1 + 20 * k2]);
        x[k2] = make_float2(E.x - O.y, E.y + O.x); r[k2] = make_float2(E.x + O.y, O.x - E.y);
      }
      if (k1 == 0) r[0] = make_float2(2.f * bf_lo(wm), -2.f * bf_hi(wm));
      const int src = (tid & 31) ^ (wp ? 16 : 0);
#pragma unroll
      for (int i = 8; i < 16; i++) { const float2 c = k1 ? r[15 - i] : r[(16 - i) & 7]; x[i] = make_float2(__shfl_sync(~0u, c.x, src), __shfl_sync(~0u, c.y, src)); }
      fft16<1>(x);
#pragma unroll
      for (int n2 = 0; n2 < 16; n2++) sm.T[(k1 * 16 + n2) * 17 + row] = x[n2];
    }
    if (live) { bar_sync(1, 320); if (WST == 1 && tid == 0) sts32(ctl + 8, 1); }
    if (wp < 8) {
      const int row = tid >> 4, n2 = tid & 15;
      float2 z[20], y[20];
#pragma unroll
      for (int k1 = 0; k1 < 20; k1++) { const float2 t = sm.T[(k1 * 16 + n2) * 17 + row]; z[k1] = k1 ? cmulc(t, sm.tw[k1 * 16 + n2]) : t; }
      fft20<1>(z, y);
      const float sc = 1.f / 640.f;
#pragma unroll
      for (int n1 = 0; n1 < 20; n1++) sm.Z[row * ZP + n1 * 16 + n2] = pack_bf16(y[n1].x * sc, y[n1].y * sc);
      __syncwarp();
      if (WST == 2 && live && tid == 0) sts32(ctl + 8, 1);
      float f[40];
#pragma unroll
      for (int i = 0; i < 5; i++) {
        const uint4 o = *(const uint4*)(sm.Z + row * ZP + i * 64 + n2 * 4), x = xr[i];
        xr[i] = make_uint4(hadd2bf(o.x, x.x), hadd2bf(o.y, x.y), hadd2bf(o.z, x.z), hadd2bf(o.w, x.w));
      }
#pragma unroll
      for (int i = 0; i < 5; i++) { stg128_if(xout + off + i * 128, xr[i], live); unpack8(xr[i], f + 8 * i); }
      if (do_ln) {
        ln_row(f);
#pragma unroll
        for (int i = 0; i < 5; i++) stg128_if(g_xn + off + i * 128, pack8(f + 8 * i), live);
      }
    }
  }
  LOGK(3 + 3 * !do_ln, 2);
}

typedef CUresult (*EncFn)(CUtensorMap*, CUtensorMapDataType, cuuint32_t, void*, const cuuint64_t*, const cuuint64_t*, const cuuint32_t*, const cuuint32_t*,
                          CUtensorMapInterleave, CUtensorMapSwizzle, CUtensorMapL2promotion, CUtensorMapFloatOOBfill);
static void make_map(EncFn fn, CUtensorMap* m, const void* p, uint64_t cols, uint64_t rows, uint32_t bc, uint32_t br, CUtensorMapSwizzle sw) {
  cuuint64_t gd[2] = {cols, rows}, gs[1] = {cols * 2}; cuuint32_t bd[2] = {bc, br}, es[2] = {1, 1};
  fn(m, CU_TENSOR_MAP_DATA_TYPE_BFLOAT16, 2, (void*)p, gd, gs, bd, es, CU_TENSOR_MAP_INTERLEAVE_NONE, sw, CU_TENSOR_MAP_L2_PROMOTION_L2_128B, CU_TENSOR_MAP_FLOAT_OOB_FILL_NONE);
}
template <class... P, class... A>
static void launch(void (*k)(P...), int grid, int block, int smem, bool pdl, A... a) {
  cudaLaunchConfig_t cfg = {}; cfg.gridDim = dim3(grid); cfg.blockDim = dim3(block); cfg.dynamicSmemBytes = smem; cfg.stream = cudaStreamPerThread;
  cudaLaunchAttribute at[1]; at[0].id = cudaLaunchAttributeProgrammaticStreamSerialization; at[0].val.programmaticStreamSerializationAllowed = 1;
  cfg.attrs = at; cfg.numAttrs = pdl ? 1 : 0;
  cudaLaunchKernelEx(&cfg, k, a...);
}
static const int tune_t[10] = {1480, 1765, 1795, 2070, 2230, 2505, 2570, 2815, 1950, 2619}; constexpr int dev_stop = 100, dev_pdl = 1;

extern "C" void kernel_launch(void* const* d_in, const int* in_sizes, int n_in, void* d_out, int out_size) {
  const bf16 *x = (const bf16*)d_in[0], *mem0 = (const bf16*)d_in[1], *Wq = (const bf16*)d_in[2], *Wk = (const bf16*)d_in[3], *Wv = (const bf16*)d_in[4], *Wo = (const bf16*)d_in[5];
  const bf16 *wr = (const bf16*)d_in[8], *wi = (const bf16*)d_in[9];
  constexpr int SM_A = S_END + 2048, SM_R = sizeof(RowSmem), SM_C = 114 * 1024, SM_I = 96 * 1024;
  void *p_xn, *p_o, *p_x, *p_comm, *p_flags, *fn; cudaDriverEntryPointQueryResult qr;
  cudaGetSymbolAddress(&p_xn, g_xn); cudaGetSymbolAddress(&p_o, g_o); cudaGetSymbolAddress(&p_x, g_x); cudaGetSymbolAddress(&p_comm, g_comm); cudaGetSymbolAddress(&p_flags, g_flags);
  cudaGetDriverEntryPoint("cuTensorMapEncodeTiled", &fn, cudaEnableDefault, &qr);
  cudaFuncSetAttribute(layer_a_kernel, cudaFuncAttributeMaxDynamicSharedMemorySize, SM_A);
  cudaFuncSetAttribute(rows_fwd_kernel, cudaFuncAttributeMaxDynamicSharedMemorySize, SM_R);
  cudaFuncSetAttribute(rows_inv_kernel, cudaFuncAttributeMaxDynamicSharedMemorySize, SM_I);
  cudaFuncSetAttribute(cols_kernel, cudaFuncAttributeMaxDynamicSharedMemorySize, SM_C);
  cudaFuncSetAttribute(rows_fwd_kernel, cudaFuncAttributePreferredSharedMemoryCarveout, 100);
  cudaFuncSetAttribute(cols_kernel, cudaFuncAttributePreferredSharedMemoryCarveout, 100);
  cudaFuncSetAttribute(rows_inv_kernel, cudaFuncAttributePreferredSharedMemoryCarveout, 100);
  CUtensorMap tq, tk, tv, to, to32, tx, tao; EncFn enc = (EncFn)fn;
  make_map(enc, &tq, Wq, 4096, 640, 64, 64, CU_TENSOR_MAP_SWIZZLE_128B); make_map(enc, &tk, Wk, 4096, 640, 64, 64, CU_TENSOR_MAP_SWIZZLE_128B);
  make_map(enc, &tv, Wv, 4096, 640, 64, 64, CU_TENSOR_MAP_SWIZZLE_128B); make_map(enc, &to, Wo, 640, 4096, 64, 64, CU_TENSOR_MAP_SWIZZLE_128B);
  make_map(enc, &to32, Wo, 640, 4096, 16, 256, CU_TENSOR_MAP_SWIZZLE_32B);
  make_map(enc, &tx, p_xn, 640, 2048, 64, 64, CU_TENSOR_MAP_SWIZZLE_128B); make_map(enc, &tao, p_o, 4096, 2048, 64, 64, CU_TENSOR_MAP_SWIZZLE_128B);
  char* comm = (char*)(((uintptr_t)p_comm + (2 << 20) - 1) & ~(uintptr_t)((2 << 20) - 1));
  const bool pdl = dev_pdl;
#define L0PDL 0
  for (int l = 0; l < 2; l++) {
    ArgsA a{x, mem0, comm, (uint32_t*)p_flags + l * F_LAYER, wr, wi, (const char*)Wq, (const char*)Wo, l, {tune_t[0], tune_t[1], tune_t[2], tune_t[3]}, {tune_t[4], tune_t[5], tune_t[6], tune_t[7]}, {tune_t[8], tune_t[9]}};
    const Wts w = {{(const char*)Wk, (const char*)Wq, (const char*)Wv, (const char*)Wo}};
    if (dev_stop > 4 * l + 0) launch(layer_a_kernel, 132, 384, SM_A, pdl && (l || L0PDL), tq, tk, tv, to, to32, tx, tao, a);
    if (dev_stop > 4 * l + 1) launch(rows_fwd_kernel, 132, 320, SM_R, pdl, l ? (const bf16*)p_x : x, (const uint32_t*)a.flags);
    if (dev_stop > 4 * l + 2) launch(cols_kernel, 107, 384, SM_C, pdl, l);
    if (dev_stop > 4 * l + 3) launch(rows_inv_kernel, 128, 352, SM_I, pdl, l ? (bf16*)d_out : (bf16*)p_x, l == 0, w);
  }
}
```

```cpp
#include <cuda_runtime.h>
#include <cuda_bf16.h>
#include <cuda_fp16.h>
#include <cuda.h>
#include <stdint.h>

typedef __nv_bfloat16 bf16;
#define DEVINL __device__ __forceinline__

__device__ __align__(1024) bf16 g_xn[2048 * 640];
__device__ __align__(1024) bf16 g_x[2048 * 640];
__device__ __align__(1024) char g_kv[64 * 32 * 16384];
__device__ __align__(1024) char g_kvm[64 * 32 * 4096];
__device__ __align__(1024) bf16 g_o[2048 * 4096];
__device__ __align__(1024) bf16 g_part[4 * 2048 * 640];
__device__ __align__(1024) uint32_t g_y[321 * 2048];
__device__ __align__(1024) uint32_t g_wt[321 * 2048];
__device__ __align__(4096) char g_comm[4 << 20];
constexpr int F_KV = 0, F_KM = 1024, F_O = F_KM + 1024, F_P = F_O + 128, F_ROLE = F_P + 32 * 32, F_X = F_ROLE + 64, F_W = F_X + 32, F_LAYER = F_W + 32;
__device__ __align__(1024) uint32_t g_flags[2 * F_LAYER];
__device__ int g_side[256];
__device__ uint32_t g_role[256];

template <int V> struct IC { static constexpr int value = V; };
template <int B, int E, class F> DEVINL void static_for(F&& f) { if constexpr (B < E) { f(IC<B>{}); static_for<B + 1, E>(f); } }

#define POLL_LIMIT (1 << 17)
DEVINL uint32_t smem_u32(const void* p) { return (uint32_t)__cvta_generic_to_shared(p); }
DEVINL uint32_t mapa(uint32_t a, uint32_t r) { uint32_t o; asm volatile("mapa.shared::cluster.u32 %0, %1, %2;" : "=r"(o) : "r"(a), "r"(r)); return o; }
DEVINL uint32_t clk() { uint32_t v; asm volatile("{.reg .b64 w; mov.u64 w, %%clock64; cvt.u32.u64 %0, w;}" : "=r"(v)::"memory"); return v; }
DEVINL void mbar_init(uint32_t bar, uint32_t cnt) { asm volatile("mbarrier.init.shared::cta.b64 [%0], %1;" ::"r"(bar), "r"(cnt) : "memory"); }
DEVINL void mbar_arrive(uint32_t bar) { asm volatile("mbarrier.arrive.shared::cta.b64 _, [%0];" ::"r"(bar) : "memory"); }
DEVINL void mbar_arrive_remote(uint32_t bar) { asm volatile("mbarrier.arrive.shared::cluster.b64 _, [%0];" ::"r"(bar) : "memory"); }
DEVINL void mbar_arrive_tx(uint32_t bar, uint32_t tx) { asm volatile("mbarrier.arrive.expect_tx.shared::cta.b64 _, [%0], %1;" ::"r"(bar), "r"(tx) : "memory"); }
DEVINL void mbar_wait(uint32_t bar, uint32_t ph) {
  asm volatile("{.reg .pred p; .reg .b32 c,q; shl.b32 c, %1, 20;\n"
               "W0: bfe.u32 q, c, 20, 1; mbarrier.try_wait.parity.shared::cta.b64 p, [%0], q; add.u32 c,c,1; @!p bra.uni W0;}" ::"r"(bar), "r"(ph) : "memory");
}
DEVINL void bar_sync(int id, int n) { asm volatile("bar.sync %0, %1;" ::"r"(id), "r"(n) : "memory"); }
DEVINL void bar_arrive(int id, int n) { asm volatile("bar.arrive %0, %1;" ::"r"(id), "r"(n) : "memory"); }
DEVINL void cluster_sync() { asm volatile("barrier.cluster.arrive.release.aligned; barrier.cluster.wait.acquire.aligned;" ::: "memory"); }
DEVINL void tma_2d(uint32_t dst, const CUtensorMap* tm, int c0, int c1, uint32_t bar) {
  asm volatile("cp.async.bulk.tensor.2d.shared::cluster.global.mbarrier::complete_tx::bytes [%0], [%1, {%2, %3}], [%4];" ::"r"(dst), "l"(tm), "r"(c0), "r"(c1), "r"(bar) : "memory");
}
DEVINL void tma_2d_mc(uint32_t dst, const CUtensorMap* tm, int c0, int c1, uint32_t bar) {
  asm volatile("cp.async.bulk.tensor.2d.shared::cluster.global.mbarrier::complete_tx::bytes.multicast::cluster [%0], [%1, {%2, %3}], [%4], %5;" ::"r"(dst), "l"(tm), "r"(c0), "r"(c1), "r"(bar), "h"((uint16_t)3) : "memory");
}
DEVINL void bulk_g2s(uint32_t dst, const void* src, uint32_t bytes, uint32_t bar) {
  asm volatile("cp.async.bulk.shared::cluster.global.mbarrier::complete_tx::bytes [%0], [%1], %2, [%3];" ::"r"(dst), "l"(src), "r"(bytes), "r"(bar) : "memory");
}
DEVINL void l2_prefetch(const void* p, uint32_t bytes) { asm volatile("cp.async.bulk.prefetch.L2.global [%0], %1;" ::"l"(p), "r"(bytes) : "memory"); }
DEVINL void fence_proxy_async() { asm volatile("fence.proxy.async.global;" ::: "memory"); }
DEVINL void ldsm4t(uint32_t* r, uint32_t a) { asm volatile("ldmatrix.sync.aligned.m8n8.x4.trans.shared.b16 {%0,%1,%2,%3}, [%4];" : "=r"(r[0]), "=r"(r[1]), "=r"(r[2]), "=r"(r[3]) : "r"(a) : "memory"); }
DEVINL void stsm4(uint32_t a, uint32_t r0, uint32_t r1, uint32_t r2, uint32_t r3) { asm volatile("stmatrix.sync.aligned.m8n8.x4.shared.b16 [%0], {%1,%2,%3,%4};" ::"r"(a), "r"(r0), "r"(r1), "r"(r2), "r"(r3) : "memory"); }
DEVINL void mma16816(float* d, const uint32_t* a, uint32_t b0, uint32_t b1) {
  asm volatile("mma.sync.aligned.m16n8k16.row.col.f32.bf16.bf16.f32 {%0,%1,%2,%3}, {%4,%5,%6,%7}, {%8,%9}, {%0,%1,%2,%3};"
               : "+f"(d[0]), "+f"(d[1]), "+f"(d[2]), "+f"(d[3]) : "r"(a[0]), "r"(a[1]), "r"(a[2]), "r"(a[3]), "r"(b0), "r"(b1));
}
DEVINL void mma16816z(float* d, const uint32_t* a, uint32_t b0, uint32_t b1) {
  asm volatile("mma.sync.aligned.m16n8k16.row.col.f32.bf16.bf16.f32 {%0,%1,%2,%3}, {%4,%5,%6,%7}, {%8,%9}, {%10,%10,%10,%10};"
               : "=f"(d[0]), "=f"(d[1]), "=f"(d[2]), "=f"(d[3]) : "r"(a[0]), "r"(a[1]), "r"(a[2]), "r"(a[3]), "r"(b0), "r"(b1), "f"(0.f));
}
DEVINL void mma1688z(float* d, uint32_t a0, uint32_t a1, uint32_t b0) {
  asm volatile("mma.sync.aligned.m16n8k8.row.col.f32.bf16.bf16.f32 {%0,%1,%2,%3}, {%4,%5}, {%6}, {%7,%7,%7,%7};"
               : "=f"(d[0]), "=f"(d[1]), "=f"(d[2]), "=f"(d[3]) : "r"(a0), "r"(a1), "r"(b0), "f"(0.f));
}
DEVINL uint32_t movm(uint32_t a) { uint32_t r; asm volatile("movmatrix.sync.aligned.m8n8.trans.b16 %0, %1;" : "=r"(r) : "r"(a)); return r; }
DEVINL uint32_t pack_bf16(float lo, float hi) { uint32_t r; asm("cvt.rn.bf16x2.f32 %0, %1, %2;" : "=r"(r) : "f"(hi), "f"(lo)); return r; }
DEVINL uint32_t pack_f16(float lo, float hi) { uint32_t r; asm("cvt.rn.f16x2.f32 %0, %1, %2;" : "=r"(r) : "f"(hi), "f"(lo)); return r; }
DEVINL float bf_lo(uint32_t w) { return __uint_as_float(w << 16); }
DEVINL float bf_hi(uint32_t w) { return __uint_as_float(w & 0xffff0000u); }
DEVINL uint32_t hadd2bf(uint32_t a, uint32_t b) { uint32_t r; asm("add.rn.bf16x2 %0, %1, %2;" : "=r"(r) : "r"(a), "r"(b)); return r; }
DEVINL uint32_t hmax2bf(uint32_t a, uint32_t b) { uint32_t r; asm("max.bf16x2 %0, %1, %2;" : "=r"(r) : "r"(a), "r"(b)); return r; }
DEVINL uint32_t lds32(uint32_t a) { uint32_t v; asm volatile("ld.shared.u32 %0, [%1];" : "=r"(v) : "r"(a) : "memory"); return v; }
DEVINL uint2 lds64(uint32_t a) { uint2 v; asm volatile("ld.shared.v2.u32 {%0,%1}, [%2];" : "=r"(v.x), "=r"(v.y) : "r"(a) : "memory"); return v; }
DEVINL uint4 lds128(uint32_t a) { uint4 v; asm volatile("ld.shared.v4.u32 {%0,%1,%2,%3}, [%4];" : "=r"(v.x), "=r"(v.y), "=r"(v.z), "=r"(v.w) : "r"(a) : "memory"); return v; }
DEVINL void sts32(uint32_t a, uint32_t v) { asm volatile("st.shared.u32 [%0], %1;" ::"r"(a), "r"(v) : "memory"); }
DEVINL void sts64(uint32_t a, uint32_t x, uint32_t y) { asm volatile("st.shared.v2.u32 [%0], {%1,%2};" ::"r"(a), "r"(x), "r"(y) : "memory"); }
DEVINL void sts128(uint32_t a, uint4 v) { asm volatile("st.shared.v4.u32 [%0], {%1,%2,%3,%4};" ::"r"(a), "r"(v.x), "r"(v.y), "r"(v.z), "r"(v.w) : "memory"); }
DEVINL void stasync64(uint32_t a, uint32_t x, uint32_t y, uint32_t bar) { asm volatile("st.async.weak.shared::cluster.mbarrier::complete_tx::bytes.v2.b32 [%0], {%1,%2}, [%3];" ::"r"(a), "r"(x), "r"(y), "r"(bar) : "memory"); }
DEVINL uint4 ldg_rlx128(const void* p) { uint4 v; asm volatile("{.reg .b64 a,b; ld.relaxed.gpu.global.v2.b64 {a,b}, [%4]; mov.b64 {%0,%1}, a; mov.b64 {%2,%3}, b;}" : "=r"(v.x), "=r"(v.y), "=r"(v.z), "=r"(v.w) : "l"(p) : "memory"); return v; }
DEVINL uint2 ldg_rlx64(const void* p) { uint2 v; asm volatile("ld.relaxed.gpu.global.v2.u32 {%0,%1}, [%2];" : "=r"(v.x), "=r"(v.y) : "l"(p) : "memory"); return v; }
DEVINL void stg_rlx64(void* p, uint32_t x, uint32_t y) { asm volatile("{.reg .b64 a; mov.b64 a, {%1,%2}; st.relaxed.gpu.global.b64 [%0], a;}" ::"l"(p), "r"(x), "r"(y) : "memory"); }
DEVINL void stg_rlx128(void* p, uint32_t x, uint32_t y, uint32_t z, uint32_t w) { asm volatile("{.reg .b64 a,b; mov.b64 a, {%1,%2}; mov.b64 b, {%3,%4}; st.relaxed.gpu.global.v2.b64 [%0], {a,b};}" ::"l"(p), "r"(x), "r"(y), "r"(z), "r"(w) : "memory"); }
DEVINL void stg_rlx32(void* p, uint32_t x) { asm volatile("st.relaxed.gpu.global.u32 [%0], %1;" ::"l"(p), "r"(x) : "memory"); }
DEVINL uint4 ldg_cg128(const void* p) { uint4 v; asm volatile("ld.global.cg.v4.u32 {%0,%1,%2,%3}, [%4];" : "=r"(v.x), "=r"(v.y), "=r"(v.z), "=r"(v.w) : "l"(p) : "memory"); return v; }
DEVINL uint32_t ldg_cg32(const void* p) { uint32_t v; asm volatile("ld.global.cg.u32 %0, [%1];" : "=r"(v) : "l"(p) : "memory"); return v; }
DEVINL uint32_t ldg32_if(const void* p, int on) { uint32_t v; asm volatile("{.reg .pred q; setp.ne.s32 q, %2, 0; mov.u32 %0, 0; @q ld.global.cg.u32 %0, [%1];}" : "=r"(v) : "l"(p), "r"(on) : "memory"); return v; }
DEVINL uint4 ldg128_if(const void* p, int on) { uint4 v; asm volatile("{.reg .pred q; setp.ne.s32 q, %5, 0; mov.u32 %0, 0; mov.u32 %1, 0; mov.u32 %2, 0; mov.u32 %3, 0; @q ld.global.cg.v4.u32 {%0,%1,%2,%3}, [%4];}" : "=r"(v.x), "=r"(v.y), "=r"(v.z), "=r"(v.w) : "l"(p), "r"(on) : "memory"); return v; }
DEVINL void stg32_if(void* p, uint32_t v, int on) { asm volatile("{.reg .pred q; setp.ne.s32 q, %2, 0; @q st.global.u32 [%0], %1;}" ::"l"(p), "r"(v), "r"(on) : "memory"); }
DEVINL void stg128_if(void* p, uint4 v, int on) { asm volatile("{.reg .pred q; setp.ne.s32 q, %5, 0; @q st.global.v4.u32 [%0], {%1,%2,%3,%4};}" ::"l"(p), "r"(v.x), "r"(v.y), "r"(v.z), "r"(v.w), "r"(on) : "memory"); }
DEVINL uint4 ldg_na128(const void* p) { uint4 v; asm volatile("ld.global.L1::no_allocate.v4.u32 {%0,%1,%2,%3}, [%4];" : "=r"(v.x), "=r"(v.y), "=r"(v.z), "=r"(v.w) : "l"(p) : "memory"); return v; }
DEVINL uint4 ldg_ef128(const void* p) { uint4 v; asm volatile("ld.global.L1::evict_first.v4.u32 {%0,%1,%2,%3}, [%4];" : "=r"(v.x), "=r"(v.y), "=r"(v.z), "=r"(v.w) : "l"(p) : "memory"); return v; }
DEVINL uint4 ldg_ca128(const void* p) { uint4 v; asm volatile("ld.global.ca.v4.u32 {%0,%1,%2,%3}, [%4];" : "=r"(v.x), "=r"(v.y), "=r"(v.z), "=r"(v.w) : "l"(p) : "memory"); return v; }
DEVINL uint32_t ldg_ca32(const void* p) { uint32_t v; asm volatile("ld.global.ca.u32 %0, [%1];" : "=r"(v) : "l"(p) : "memory"); return v; }
DEVINL void flag_wait(const uint32_t* p, uint32_t want) {
  uint32_t v;
#pragma unroll 1
  for (int n = 0; n < POLL_LIMIT; n++) { asm volatile("ld.acquire.gpu.global.u32 %0, [%1];" : "=r"(v) : "l"(p) : "memory"); if (v >= want) break; __nanosleep(40); }
}
DEVINL void flag_wait_warp(const uint32_t* p, uint32_t want) {
  uint32_t v; int n = 0;
  do { asm volatile("ld.acquire.gpu.global.u32 %0, [%1];" : "=r"(v) : "l"(p) : "memory"); } while (__any_sync(~0u, v < want && ++n < POLL_LIMIT));
}
DEVINL void flag_add(uint32_t* p) { asm volatile("red.release.gpu.global.add.u32 [%0], 1;" ::"l"(p) : "memory"); }
DEVINL void flag_set(uint32_t* p, uint32_t v) { asm volatile("fence.acq_rel.gpu; st.relaxed.gpu.global.u32 [%0], %1;" ::"l"(p), "r"(v) : "memory"); }
DEVINL uint32_t ldg_rlx32(const void* p) { uint32_t v; asm volatile("ld.relaxed.gpu.global.u32 %0, [%1];" : "=r"(v) : "l"(p) : "memory"); return v; }
DEVINL float ex2(float x) { float y; asm("ex2.approx.ftz.f32 %0, %1;" : "=f"(y) : "f"(x)); return y; }
DEVINL float rcp(float x) { float y; asm("rcp.approx.ftz.f32 %0, %1;" : "=f"(y) : "f"(x)); return y; }
DEVINL uint32_t opaque(uint32_t x) { return __shfl_sync(~0u, x, threadIdx.x & 31); }
DEVINL uint32_t launder(uint32_t x) { asm volatile("" : "+r"(x)); return x; }
DEVINL void pdl_wait() { asm volatile("griddepcontrol.wait;" ::: "memory"); }
DEVINL void pdl_launch() { asm volatile("griddepcontrol.launch_dependents;" ::: "memory"); }
#define LOGS(cta, i)
#define LOGK(k, i)
#define LOG(cta, i)
#define LOGV(cta, i, v)
#define EV(i, v)
constexpr float SM_SCALE = 0.08838834764831845f * 1.4426950408889634f;

DEVINL void unpack8(uint4 v, float* f) { f[0] = bf_lo(v.x); f[1] = bf_hi(v.x); f[2] = bf_lo(v.y); f[3] = bf_hi(v.y); f[4] = bf_lo(v.z); f[5] = bf_hi(v.z); f[6] = bf_lo(v.w); f[7] = bf_hi(v.w); }
DEVINL uint4 pack8(const float* f) { return make_uint4(pack_bf16(f[0], f[1]), pack_bf16(f[2], f[3]), pack_bf16(f[4], f[5]), pack_bf16(f[6], f[7])); }
DEVINL void ln_row(float* f) {
  float s = 0.f;
#pragma unroll
  for (int i = 0; i < 40; i++) s += f[i];
#pragma unroll
  for (int o = 1; o < 16; o <<= 1) s += __shfl_xor_sync(~0u, s, o);
  const float mean = s * (1.f / 640.f); float q = 0.f;
#pragma unroll
  for (int i = 0; i < 40; i++) { f[i] -= mean; q = fmaf(f[i], f[i], q); }
#pragma unroll
  for (int o = 1; o < 16; o <<= 1) q += __shfl_xor_sync(~0u, q, o);
  const float rs = rsqrtf(q * (1.f / 640.f) + 1e-5f);
#pragma unroll
  for (int i = 0; i < 40; i++) f[i] *= rs;
}

#define WAH 2
struct Wts { const char* w[4]; };
template <int CH> DEVINL void weight_warm(const Wts& w, uint32_t buf, uint32_t bar, uint32_t stop) {
  uint32_t smid; asm volatile("mov.u32 %0, %%smid;" : "=r"(smid));
  const uint32_t c = g_role[smid & 255];
  if (c >= 128) return;
  mbar_init(bar, 1); asm volatile("fence.mbarrier_init.release.cluster; fence.proxy.async.shared::cta;" ::: "memory");
  constexpr int N = 81920 / CH;
#pragma unroll 1
  for (int i = 0; i < (c < 64 ? 4 : 2) * N; i++) {
    uint32_t v; asm volatile("ld.volatile.shared.u32 %0, [%1];" : "=r"(v) : "r"(stop) : "memory");
    if (v) break;
    mbar_arrive_tx(bar, CH);
    auto src = [&](int i) { return w.w[c < 64 ? i / N : i / N * 2] + (c & 63) * 81920 + (i % N) * CH; };
    bulk_g2s(buf, src(i), CH, bar);
    if (WAH && i + WAH < (c < 64 ? 4 : 2) * N) l2_prefetch(src(i + WAH), CH);
    mbar_wait(bar, i & 1);
  }
}
struct ArgsA {
  const bf16* x; const bf16* mem0; char* comm; uint32_t* flags; const bf16* wr; const bf16* wi; const char* wq; const char* wo;
  int layer; int ta[4], tb[4], tc[2];
};

#define VP 4
#define HELD 0x2557
#define PRE 4
#define VPRE0 3
#define VPRE1 5
#define R0 2
#define TRK 30
#define TEXP 200
#define TRD 0
#define TKV 300
#define KB1 5
#define W2D 0
#define WD 4
#define VPW 1
#define P1F 3
#define W0D 0
#define XD 0
#define TSF 2
#define XP 0
#define PW 1
#define VXE 0
#define LA 0
#define KB2 10
#define KB3 13
#define TSE 7
#define PRP 0
#define R1 2
#define OBF 1
#define LS0 0x002220222200ull
#define LS1 0x00220000ull
#define RRP -1
#define RCP 6
#define PS0 32
#define PS1 4
#define DEP0 0
#define DEP1 1
#define PIN 1
#define F0 3
#define W1N 12
#define XLATE 0
#define XST 0
#define XF 5
#define W1D 0
constexpr int C_WV = 0;
constexpr int C_WO = 81920;
constexpr int C_KV = 163840;
constexpr int C_M  = C_KV + 24576;
constexpr int C_QK = C_M + 10240;
constexpr int C_VP = C_QK + 4096;
constexpr int C_S  = C_VP + 4096;
constexpr int C_O  = C_S + 2048;
constexpr int C_R  = C_O + 2048;
constexpr int C_T  = C_R + 256;
constexpr int S_BAR = 229376;
constexpr int S_END = S_BAR + 256;
enum { BAR_QK = 2, BAR_O = 3, BAR_H = 4, BAR_X = 5, BAR_W = 7  , BAR_E = 9, BAR_M1 = 10  , BAR_M3 = 12, BAR_M2 = 13   };
constexpr int B_W = 0, B_S = 8, B_W2 = 16, B_KV = 24, B_WV = 40, B_WO = 48;
constexpr int G2_OFF = 0x130000, TS_OFF = 0x11000;

#define FEN() asm volatile("pmevent 0;" ::: "memory")
#define SCHED(x, c) asm volatile("{.reg .pred p; setp.eq.u32 p, %0, %1; @p exit;}" ::"r"(x), "r"(0x7fff0001u + 2 * (c)) : "memory")
DEVINL uint32_t g1page(uint32_t L) { L = ((L & 7) | ((L & 24) << 2)) << 1; return (L | (__popc(L & 0xb2) & 1)) << 12; }
DEVINL void spin_until(uint32_t t) {
  asm volatile("{.reg .pred p; .reg .b32 c; .reg .b64 w;\nS0: mov.u64 w, %%clock64; cvt.u32.u64 c, w; sub.u32 c, %0, c; setp.lt.u32 p, c, 16384; @p bra.uni S0;}" ::"r"(t) : "memory");
}
DEVINL uint32_t wait_until(uint32_t t, uint32_t z) { uint32_t r;
  asm volatile("{.reg .pred p; .reg .b32 c,x,y; .reg .b64 w;\nT0: .branchtargets L0, L1, L2, L3, L4, L5, L6, L7, L8, L9, L10;\n mov.u32 x, %2;\n"
               "mov.u64 w, %%clock64; cvt.u32.u64 c, w; sub.u32 c, %1, c; setp.ge.u32 p, c, 16384; @p bra.uni L0;\n"
               "S0: mov.u64 w, %%clock64; cvt.u32.u64 c, w; sub.u32 c, %1, c; setp.gt.s32 p, c, 40; @p bra.uni S0;\n"
               "mad.lo.s32 c, c, 37, 1200; shr.s32 c, c, 8; max.s32 c, c, 0;\nbrx.idx.uni c, T0;\n"
               "L10: mul.lo.u32 x, x, x; L9: mul.lo.u32 x, x, x; L8: mul.lo.u32 x, x, x; L7: mul.lo.u32 x, x, x; L6: mul.lo.u32 x, x, x; L5: mul.lo.u32 x, x, x; L4: mul.lo.u32 x, x, x; L3: mul.lo.u32 x, x, x; L2: mul.lo.u32 x, x, x; L1: mul.lo.u32 x, x, x; L0: mov.u32 %0, x;}" : "=r"(r) : "r"(t), "r"(z) : "memory"); return r;
}
DEVINL void gtime(uint32_t& G16, uint32_t& C) {
  asm volatile("{.reg .b64 w; .reg .b32 g,g0,a;\n mov.u64 w, %%clock64; cvt.u32.u64 %1, w; mov.u64 w, %%globaltimer; cvt.u32.u64 g0, w; mul.lo.u32 a, g0, -11;\n"
               "mov.u64 w, %%globaltimer; cvt.u32.u64 g, w; add.u32 a, a, g; mov.u64 w, %%globaltimer; cvt.u32.u64 g, w; add.u32 a, a, g; mov.u64 w, %%globaltimer; cvt.u32.u64 g, w; add.u32 a, a, g; mov.u64 w, %%globaltimer; cvt.u32.u64 g, w; add.u32 a, a, g; mov.u64 w, %%globaltimer; cvt.u32.u64 g, w; add.u32 a, a, g; mov.u64 w, %%globaltimer; cvt.u32.u64 g, w; add.u32 a, a, g; mov.u64 w, %%globaltimer; cvt.u32.u64 g, w; add.u32 a, a, g; mov.u64 w, %%globaltimer; cvt.u32.u64 g, w; add.u32 a, a, g; mov.u64 w, %%globaltimer; cvt.u32.u64 g, w; add.u32 a, a, g; mov.u64 w, %%globaltimer; cvt.u32.u64 g, w; add.u32 a, a, g; mov.u64 w, %%globaltimer; cvt.u32.u64 g, w; add.u32 a, a, g; \n mul.lo.u32 a, a, 341; shr.u32 a, a, 8; mad.lo.u32 %0, g0, 16, a;}" : "=r"(G16), "=r"(C)::"memory");
}
DEVINL uint32_t pack_tag(float lo, float hi, uint32_t tg) {
  const uint32_t w = pack_bf16(lo, __uint_as_float(tg | 0x3F800000u)), a = __float_as_uint(hi) + (tg ^ 0x10000u); uint32_t r;
  asm("lop3.b32 %0, %1, %2, 0xFFFE0000, 0xE4;" : "=r"(r) : "r"(a), "r"(w)); return r;
}
DEVINL float ex2v(float x) { float y; asm volatile("ex2.approx.ftz.f32 %0, %1;" : "=f"(y) : "f"(x)); return y; }
DEVINL void load_kv(uint32_t sb, int h, int j, int s) {
  asm volatile("{.reg .pred p; elect.sync _|p, 0xffffffff;\n fence.proxy.async.global;\n @p mbarrier.arrive.expect_tx.shared::cta.b64 _, [%2], 12288;\n"
               " @p cp.async.bulk.shared::cluster.global.mbarrier::complete_tx::bytes [%0], [%1], 12288, [%2];}"
               ::"r"(sb + C_KV + (s & 1) * 12288), "l"(g_kv + (size_t)(s * 32 + h) * 16384 + j * 4096), "r"(sb + S_BAR + B_KV + (s & 1) * 8) : "memory");
}

constexpr __host__ __device__ int digsum(unsigned long long v, int n) { int r = 0; for (int i = 0; i < n; i++) r += (v >> (4 * i)) & 15; return r; }
template <int KH>
DEVINL void chain_mma(uint32_t sb0, const ArgsA& args) {
  const int lane = threadIdx.x & 31, mg = (threadIdx.x >> 5) & 3, mi = lane >> 3, r = lane & 7;
  const uint32_t aW = opaque(sb0 + (uint32_t)(((mi >> 1) * 8 + r) * 128 + (((mg + 4 * (mi & 1)) ^ r) << 4)));
  const uint32_t aL = opaque(sb0 + lane * 16);
  const uint32_t aLm = opaque(sb0 + mg * 512 + lane * 16);
#define sb (launder(aL) & ~511u)
  constexpr int OV = C_WV + KH * 40960, OM = C_M + KH * 5120, NF = KH ? 16 : 24;
  auto owo = [](int f) { return C_WO + (KH + 2 * (f >> 3)) * 16384 + (f & 7) * 2048; };
  auto held = [](int k) { return (HELD >> k) & 1; };
  auto rank = [](int k) { return __popc(HELD & ((1 << k) - 1)); };
  uint32_t wq[20][4], wk[20][4];
  mbar_wait(sb + S_BAR + B_W, 0);
#pragma unroll
  for (int k = 0; k < 12; k++) { ldsm4t(wq[k], aW + OV + k * 2048); ldsm4t(wk[k], aW + C_WO + KH * 40960 + k * 2048); }
  bar_arrive(BAR_H, 288);
  mbar_wait(sb + S_BAR + B_W2, 0);
#pragma unroll
  for (int k = 12; k < 20; k++) { ldsm4t(wq[k], aW + OV + k * 2048); ldsm4t(wk[k], aW + C_WO + KH * 40960 + k * 2048); }
  bar_sync(BAR_E, 384);
  mbar_wait(sb + S_BAR + B_WV, 0);
  uint32_t sx = args.layer << 16;
#pragma unroll 1
  while (true) {
    uint32_t v[20][4], b[10][4];
    {
      const uint32_t o = launder(aLm) - sb, on = (sx >> 16) != (uint32_t)args.layer;
      const char* p = args.comm + lds32(sb + C_T + KH * 1024 + 4 + (o >> 1));
      constexpr int NB = KH ? VPRE1 : VPRE0;
      const uint32_t zero = (uint32_t)(uintptr_t)p & 1, tt = lds32(sb + C_R + 48) + args.tb[0]; uint32_t av = aW;
#pragma unroll
      for (int k = 0; k < 20; k++) if (held(k) && rank(k) < NB) { ldsm4t(v[k], av + OV + k * 2048); if (rank(k) % VPW == VPW - 1 && rank(k) < NB - 1) av = aW + (v[k][0] & zero); }
      p += wait_until(tt, zero);
      uint4 a = ldg_rlx128(p);
      __syncwarp();
#pragma unroll
      for (int k = 0; k < 20; k++) if (held(k) && rank(k) >= NB) { ldsm4t(v[k], av + OV + k * 2048); if ((rank(k) - NB) % VPW == VPW - 1) av = aW + (v[k][0] & zero); }
      SCHED(o ^ on, 29);
      if (on) sts128(aLm + OM, a);
      if (__builtin_expect(__any_sync(~0u, on && (((a.x ^ sx) | (a.z ^ sx)) & 0x10000u)), 0)) {
        int lim = 0;
        do a = ldg_rlx128(p); while (__any_sync(~0u, (((a.x ^ sx) | (a.z ^ sx)) & 0x10000u) && ++lim < POLL_LIMIT));
        sts128(aLm + OM, a);
      }
      bar_sync(BAR_W + KH, 128);
      ldsm4t(b[0], aL + OM); ldsm4t(b[1], aL + OM + 512);
    }
    float cq[4], ck[4], cv[4];
    static_for<0, 20>([&](auto I) {
      constexpr int k = I.value, p = k >> 1;
      const uint32_t b0 = b[p][(k & 1) * 2], b1 = b[p][(k & 1) * 2 + 1];
      if (k == 0) { mma16816z(cv, v[0], b0, b1); mma16816z(cq, wq[k], b0, b1); mma16816z(ck, wk[k], b0, b1); }
      else { if (k < 20 - VP) mma16816(cv, v[k], b0, b1); mma16816(cq, wq[k], b0, b1); mma16816(ck, wk[k], b0, b1); }
      if (k == KB1) bar_sync(BAR_M1 + KH, 160);
      if (k == KB2) bar_sync(BAR_M2 + KH, 160);
      if (k == KB3) bar_sync(BAR_M3, 320);
      static_for<2, 10>([&](auto J) {
        constexpr int q = J.value, st = q < 4 ? 0 : q < 6 ? KB1 : q < 8 ? KB2 : KB3;
        if constexpr (k == (2 * q - 3 > st ? 2 * q - 3 : st)) ldsm4t(b[q], aL + OM + q * 512); });
      if constexpr (k + 3 < 20 - VP && !((HELD >> (k + 3)) & 1)) ldsm4t(v[k + 3], aW + OV + (k + 3) * 2048);
      if (k >= 20 - VP && k < 20 - VP + PRE && !held(k)) ldsm4t(v[k], aW + OV + k * 2048);
      if (P1F && (k & 1) && k >= P1F && k < 19) FEN();
    });
    stsm4(aLm + C_QK + KH * 2048, pack_bf16(cq[0], cq[1]), pack_bf16(cq[2], cq[3]), pack_bf16(ck[0], ck[1]), pack_bf16(ck[2], ck[3]));
    bar_arrive(BAR_QK, 384);
    FEN();
    const uint32_t l8 = (launder(aL) & 511) >> 1, px = lds32(sb + C_R + 80);
#pragma unroll
    for (int k = 20 - VP + PRE; k < 20; k++) if (!held(k)) ldsm4t(v[k], aW + OV + k * 2048);
#pragma unroll
    for (int k = 20 - VP; k < 20; k++) {
      const int p = k >> 1, q = k - 20 + VP; const uint32_t b0 = b[p][(k & 1) * 2], b1 = b[p][(k & 1) * 2 + 1];
      if (q % 3 == 0) mma16816(cv, v[k], b0, b1); else if (q == 1) mma16816z(cq, v[k], b0, b1); else if (q == 2) mma16816z(ck, v[k], b0, b1);
      else if (q % 3 == 1) mma16816(cq, v[k], b0, b1); else mma16816(ck, v[k], b0, b1);
    }
    if (VP >= 3) {
#pragma unroll
      for (int i = 0; i < 4; i++) cv[i] += cq[i] + ck[i];
    }
    { const uint32_t vx = pack_bf16(cv[0], cv[1]), vy = pack_bf16(cv[2], cv[3]);
      const uint32_t av = aLm - l8 + C_VP + KH * 256;
      stasync64(av + 2048 + px, vx, vy, sb + S_BAR + B_S + px);
      sts64(av, vx, vy);
      __syncwarp();
      if (l8 == 0) mbar_arrive(sb + S_BAR + B_S); }
    sx += 0x10000;
    if ((sx >> 16) == args.layer + 64u) break;
    uint32_t w[NF][4];
    {
      const uint32_t zero = px & 1; uint32_t a = aW;
      const bool tsw = KH == 1 && __any_sync(~0u, launder(aLm) == aL); uint2 ts = make_uint2(0, 0); uint4 cal = make_uint4(0, 0, 0, 0);
      if ((sx >> 16) == args.layer + 1u) mbar_wait(sb + S_BAR + B_WO, 0);
#pragma unroll
      for (int f = 0; f < 8 + XP; f++) { ldsm4t(w[f], a + owo(f));
        if (KH == 1 && f == TSF && tsw) { ts = ldg_rlx64(args.comm + TS_OFF + l8); cal = lds128(sb + C_R + 64); }
      if (KH == 1 && f == TSE && tsw) {
        const uint32_t d0 = ts.x - cal.x, d1 = ts.y - cal.x;
        const int dt = (int)__reduce_max_sync(~0u, max(d0 < 32768u ? d0 : 0u, d1 < 32768u ? d1 : 0u));
        sts32(sb + C_R + 48, cal.y + min((dt * cal.z) >> 16, 8192u));
      }
        uint32_t d = w[f][0] & zero;
#pragma unroll
        for (int q = 0; q < (f == 0 ? TRD : 0); q++) d *= d;
        if (f % PW == PW - 1) a = aW + d; }
    }
    const uint32_t go = lds32(sb + C_T + KH * 1024 + ((launder(aLm) - sb) >> 1)), ar = ((launder(aL) >> 1) & 24) + sb + (go & 1);
    SCHED(ar, 30);
    bar_sync(BAR_O, 384);
    uint32_t ob[16];
#pragma unroll
    for (int p = 0; p < 4; p++) ldsm4t(ob + 4 * p, aL + C_O + p * 512);
    uint2 rr;
    if (RRP < 0) rr = lds64(ar + C_R + 128);
    if (OBF) FEN();
    float r0, r1; uint32_t y0, y1;
    static_for<0, NF>([&](auto I) {
      constexpr int f = I.value, k = f & 7; const uint32_t* A = w[f];
      if (k == 0) mma16816z(cq, A, ob[0], ob[1]); else if (k == 1) mma16816z(ck, A, ob[2], ob[3]);
      else if (k & 1) mma16816(ck, A, ob[2 * k], ob[2 * k + 1]); else mma16816(cq, A, ob[2 * k], ob[2 * k + 1]);
      if (f == RRP) rr = lds64(ar + C_R + 128);
      if (f == RCP) { r0 = rcp(__uint_as_float(rr.x)); r1 = rcp(__uint_as_float(rr.y)); }
      if constexpr (f & 1) {
        constexpr unsigned long long LS = KH ? LS1 : LS0; constexpr int pr = f >> 1, n = (LS >> (4 * pr)) & 15;
        constexpr int PS = KH ? PS1 : PS0, q0 = 8 + XP + digsum(LS, pr) + digsum(PS, f >> 3), m = (PS >> (4 * (f >> 3))) & 15;
        if constexpr (n > 0) { const uint32_t a = (f < 8 && !DEP0) || !DEP1 ? aW : aW + ((f < 8 ? ob[2 * k] : A[0]) & go & 1);
#pragma unroll
          for (int q = q0; q < q0 + n; q++) ldsm4t(w[q], a + owo(q)); }
        if constexpr (k == 7) { if (n > 0) FEN();
          y0 = pack_tag((cq[0] + ck[0]) * r0, (cq[1] + ck[1]) * r1, sx & 0x10000u); y1 = pack_bf16((cq[2] + ck[2]) * r0, (cq[3] + ck[3]) * r1);
          stg_rlx64(args.comm + go + (f < 8 ? 0 : f < 16 ? 0x30000 : 0x100000), y0, y1);
          if constexpr (m > 0) { FEN(); uint32_t a = aW;
            if constexpr (KH == 1 && W1N > 0) { uint32_t d = y1 & go & 1;
#pragma unroll
              for (int q = 0; q < W1N; q++) d *= d;
              a += d; }
#pragma unroll
            for (int q = q0 + n; q < q0 + n + m; q++) ldsm4t(w[q], a + owo(q)); } }
        if (f >= 8 && k == 3 && PIN) SCHED(y0 & y1 & go, 40 + f);
        else if (f >= F0 || n > 0) FEN();
      }
    });
  }
}

#undef sb
DEVINL void chain_helper(uint32_t sb, uint32_t px, int h, int j, const ArgsA& args, const CUtensorMap* tq, const CUtensorMap* tk, const CUtensorMap* tv, const CUtensorMap* to) {
  const int c = 2 * h + j;
  const uint32_t bW = sb + S_BAR + B_W, bS = sb + S_BAR + B_S, bKV = sb + S_BAR + B_KV;
  const uint32_t lane0 = opaque(threadIdx.x & 31);
  const uint32_t warp = __reduce_max_sync(~0u, (threadIdx.x >> 5) & 3);
  { const int tid = threadIdx.x - 256;
    if (tid == 0) { mbar_arrive_tx(bW, 98304); mbar_arrive_tx(bW + B_W2, 65536); mbar_arrive_tx(bW + B_WV, 81920); mbar_arrive_tx(bW + B_WO, 81920);
#pragma unroll 1
      for (int q = 0; q < 10; q++) { const int i = (q & 1) * 5 + (q >> 1); const uint32_t bar = q < 6 ? bW : bW + B_W2;
        tma_2d(sb + C_WV + i * 8192, tq, h * 128 + j * 64, i * 64, bar); tma_2d(sb + C_WO + i * 8192, tk, h * 128 + j * 64, i * 64, bar); } }
    uint32_t G0, C0; gtime(G0, C0);
    if (warp == 0) sts64(sb + C_R + 96, G0, C0);
    { const uint32_t g = lane0 >> 2, t = lane0 & 3;
      sts128(sb + C_T + 2048 + tid * 16, make_uint4(g1page(c >> 1) + (c & 1) * 2048 + (warp == 0 ? 0 : warp == 1 ? 0x30000 : 0x100000) + ((g >> 2) * 4 + t) * 64 + (g & 3) * 16,
                                                    g1page(((t >> 1) + (g >> 2) * 2) * 4 + warp) + G2_OFF + (c >> 4) * 1024 + (t & 1) * 512 + (c & 15) * 32 + (g & 3) * 8,
                                                    g1page((h & 3) * 4 + (warp == 2 ? 2 : 1)) + G2_OFF + (warp == 1 ? 1024 : warp == 3 ? 2048 : 0) + lane0 * 16, (g & 1) ? 0x3F800000u : 0x00003F80u)); }
    sts32(sb + C_R + 80, px); sts32(sb + C_R + 48, C0 - 65536);
#pragma unroll
    for (int kh = 0; kh < 2; kh++)
      sts64(sb + C_T + kh * 1024 + tid * 8, g1page(j * 16 + kh * 8 + (tid >> 4)) + (tid & 8) * 256 + h * 64 + (tid & 7) * 8, g1page((h & 3) * 4) + G2_OFF + kh * 2048 + tid * 16);
#pragma unroll
    for (int i = 0; i < 5; i++) { const int q = tid + i * 128, n = q & 7, d0 = (q >> 3) * 8; const uint4 v = *(const uint4*)(args.mem0 + n * 640 + d0); const uint32_t w[4] = {v.x, v.y, v.z, v.w};
#pragma unroll
      for (int e = 0; e < 8; e++) asm volatile("st.shared.u16 [%0], %1;" ::"r"(sb + C_M + (d0 + e) * 16 + n * 2), "h"((unsigned short)(w[e >> 1] >> ((e & 1) * 16))) : "memory"); }
    auto round2 = [&](int q0, int q1) {
#pragma unroll 1
      for (int q = q0; q < q1; q++) { const int i = (q & 1) * 5 + (q >> 1); tma_2d(sb + C_WV + i * 8192, tv, h * 128 + j * 64, i * 64, bW + B_WV); }
#pragma unroll 1
      for (int q = q0; q < q1; q++) { const int i = (q & 1) * 5 + (q >> 1); tma_2d(sb + C_WO + i * 8192, to, j * 320 + (i >> 1) * 64, h * 128 + ((i & 1) ^ j) * 64, bW + B_WO); } };
    if (warp == 0) { bar_sync(BAR_H, 288); if (tid == 0) round2(0, 6); __syncwarp(); }
    bar_sync(BAR_E, 384);
    if (tid == 0) round2(6, 10);
    if (warp == 3) {
      if (tid == 96) LOG(c, 250);
      flag_wait_warp(args.flags + F_KV + h * 32, 2);
      load_kv(sb, h, j, 0); load_kv(sb, h, j, 1); if (tid == 96) LOG(c, 251);
    }
  }
  auto calib = [&]() { uint32_t G, C; gtime(G, C);
    const uint2 o = lds64(sb + C_R + 96); const float rt = (float)(C - o.y) * rcp((float)(G - o.x));
    sts128(sb + C_R + 32, make_uint4(G, C, __float2uint_rn(rt * 65536.f) & 0xffffu, __float_as_uint(rcp(rt)))); __syncwarp(); };
  auto export_ld = [&](uint32_t (*e)[4], uint32_t lane) {
    uint32_t k1[2][4]; uint2 a[4], b[4];
    const uint32_t ak = sb + C_QK + 256 + (lane >> 4) * 512 + (lane & 15) * 16, av = sb + C_VP + (lane >> 3) * 512 + (lane & 7) * 8, tg = (args.layer ^ 1) << 16;
#pragma unroll
    for (int i = 0; i < 2; i++) { ldsm4t(e[i], ak + i * 1024); ldsm4t(k1[i], ak + i * 1024 + 2048); }
#pragma unroll
    for (int i = 0; i < 4; i++) { a[i] = lds64(av + i * 64); b[i] = lds64(av + i * 64 + 256); }
#pragma unroll
    for (int i = 0; i < 4; i++) { e[0][i] = hadd2bf(e[0][i], k1[0][i]); e[1][i] = hadd2bf(e[1][i], k1[1][i]); e[2][i] = hadd2bf(a[i].x, b[i].x); e[3][i] = hadd2bf(a[i].y, b[i].y); }
#pragma unroll
    for (int i = 0; i < 8; i++) e[i >> 1][(i & 1) * 2] = (e[i >> 1][(i & 1) * 2] & ~0x10000u) | tg;
  };
  auto export_st = [&](const uint32_t (*e)[4], int s, uint32_t lane) {
    char* dst = g_kvm + ((s * 32 + h) * 4096 + j * 1024 + lane * 16);
#pragma unroll
    for (int i = 0; i < 4; i++) stg_rlx128(dst + (i >> 1) * 2048 + (i & 1) * 512, e[i][0], e[i][1], e[i][2], e[i][3]);
    stg_rlx32(args.flags + F_KM + h * 32 + j, s + 1);
  };
  auto staged = [&]() { if (warp == 2) bar_arrive(BAR_M3, 320); else if (warp == 1) { bar_arrive(BAR_M2, 160); bar_arrive(BAR_M2 + 1, 160); } else bar_arrive(BAR_M1 + (warp >> 1), 160); };
  if (warp == 0) calib();
  staged();
  int kv_ok = 1;
  uint32_t vx[4][4];
  auto load_vx = [&](int s, uint32_t lane) {
    const uint32_t aVx = sb + C_KV + (s & 1) * 12288 + 4096 + (warp >> 1) * (j ? -4096 : 4096) + (warp & 1) * 1024 + lane * 16, zero = lane >> 5;
#pragma unroll
    for (int i = 0; i < 4; i++) { const uint4 q = lds128(aVx + (i & 1) * 2048 + (i >> 1) * 512); vx[i][0] = q.x ^ zero; vx[i][1] = q.z ^ zero; vx[i][2] = q.y ^ zero; vx[i][3] = q.w ^ zero; }
  };
  uint2 kb[4];
  auto prep = [&](int s, uint32_t lane) {
    if (s < 63) mbar_wait(bKV + (s & 1) * 8, (s >> 1) & 1);
    const uint32_t aK = sb + C_KV + (s & 1) * 12288 + j * 8192 + warp * 1024 + lane * 16;
#pragma unroll
    for (int i = 0; i < 4; i++) kb[i] = lds64(aK + ((warp ^ i) >> 1) * 512 + ((warp ^ i) & 1) * 8);
    if (VXE == 1) load_vx(s, lane);
    asm volatile("{.reg .pred p; setp.eq.u32 p, %2, 32; @p mbarrier.arrive.expect_tx.shared::cta.b64 _, [%0], %1;}" ::"r"(bS), "r"(s < 63 ? 3072 : 2048), "r"(warp * 32 + lane) : "memory");
  };
  prep(0, lane0);
#pragma unroll 1
  for (int s = 0;; s++) {
    const uint32_t ph = s & 1;
    const uint32_t lane = __shfl_sync(~0u, lane0, lane0);
    const uint32_t mi = lane >> 3, r = lane & 7;
    const uint32_t aQ = sb + C_QK + (mi & 1) * 2048 + ((mi >> 1) * 8 + r) * 16;
    const uint32_t aKm = sb + C_QK + 256 + warp * 512 + (lane >> 4) * 2048 + (lane & 15) * 16;
    const uint32_t aH = sb + C_S + warp * 256 + lane * 8, aR = aH + 1024 + px;
    SCHED(aQ ^ aR ^ aKm, 60);
    if (warp == 0) {
      const uint4 cal = lds128(sb + C_R + 32);
      bar_sync(BAR_M3, 320);
      sts32(sb + C_R + 52, 0);
      const uint32_t E = clk(), e16 = cal.x + (uint32_t)__float2int_rn((float)(int)(E - cal.y) * __uint_as_float(cal.w));
      stg_rlx32(args.comm + TS_OFF + c * 4, e16); sts128(sb + C_R + 64, make_uint4(e16, E, cal.z, 0));
    }
    if (s == 63) { bar_sync(BAR_QK, 384); mbar_wait(bS, 1); if (warp == 3) { uint32_t e[4][4]; export_ld(e, lane); export_st(e, 63, lane); } break; }
    {
      uint32_t qa[4][4], km[4]; float s0[4], s1[4], s2[4];
      bar_sync(BAR_QK, 384);
      ldsm4t(qa[0], aQ + warp * 512); ldsm4t(km, aKm); ldsm4t(qa[1], aQ + (warp ^ 1) * 512); ldsm4t(qa[2], aQ + (warp ^ 2) * 512); ldsm4t(qa[3], aQ + (warp ^ 3) * 512);
      mma16816z(s0, qa[0], kb[0].x, kb[0].y); mma16816z(s2, qa[0], km[0], km[1]); mma16816z(s1, qa[1], kb[1].x, kb[1].y);
      FEN();
      mma16816(s2, qa[0], km[2], km[3]); mma16816(s0, qa[2], kb[2].x, kb[2].y); mma16816(s1, qa[3], kb[3].x, kb[3].y);
      const uint32_t w0 = pack_bf16((s0[0] + s0[2]) + (s1[0] + s1[2]), (s0[1] + s0[3]) + (s1[1] + s1[3]));
      const uint32_t w1 = pack_bf16(s2[0] + s2[2], s2[1] + s2[3]);
      stasync64(aR, w0, w1, bS + px);
      sts64(aH, w0, w1);
    }
    {
      uint32_t sl[5];
      const uint32_t a8 = sb + lane * 8, av = a8 + C_VP + warp * 1024;
      const uint32_t aO = sb + C_O + ((warp >> 1) * 64 + (warp & 1) * 16 + (mi & 1) * 32 + (mi >> 1) * 8 + r) * 16, aU = sb + C_R + (lane & 28);
      uint4 vq[4];
      if (VXE == 2) { const uint32_t aVx = sb + C_KV + ph * 12288 + 4096 + (warp >> 1) * (j ? -4096 : 4096) + (warp & 1) * 1024 + lane * 16;
#pragma unroll
        for (int i = 0; i < 4; i++) vq[i] = lds128(aVx + (i & 1) * 2048 + (i >> 1) * 512); }
      bar_sync(BAR_X, 128);
      { uint2 t[4];
#pragma unroll
        for (int u = 0; u < 4; u++) t[u] = lds64(a8 + C_S + u * 256);
        if (VXE == 0) load_vx(s, lane);
        if (VXE == 2) { FEN(); const uint32_t zero = lane >> 5;
#pragma unroll
          for (int i = 0; i < 4; i++) { vx[i][0] = vq[i].x ^ zero; vx[i][1] = vq[i].z ^ zero; vx[i][2] = vq[i].y ^ zero; vx[i][3] = vq[i].w ^ zero; } }
#pragma unroll
        for (int u = 0; u < 4; u++) sl[u] = t[u].x;
        sl[4] = pack_bf16((bf_lo(t[0].y) + bf_lo(t[1].y)) + (bf_lo(t[2].y) + bf_lo(t[3].y)), (bf_hi(t[0].y) + bf_hi(t[1].y)) + (bf_hi(t[2].y) + bf_hi(t[3].y))); }
      mbar_wait(bS, ph);
      uint32_t vm[2][4];
      { uint2 t[4];
#pragma unroll
        for (int u = 0; u < 4; u++) t[u] = lds64(a8 + C_S + 1024 + u * 256);
#pragma unroll
        for (int u = 0; u < 4; u++) sl[u] = hadd2bf(sl[u], t[u].x);
        sl[4] = hadd2bf(hadd2bf(hadd2bf(sl[4], t[0].y), t[1].y), hadd2bf(t[2].y, t[3].y)); }
      uint32_t m2 = hmax2bf(hmax2bf(hmax2bf(sl[0], sl[1]), hmax2bf(sl[2], sl[3])), sl[4]);
      const uint32_t x1 = __shfl_xor_sync(~0u, m2, 1), x2 = __shfl_xor_sync(~0u, m2, 2), x3 = __shfl_xor_sync(~0u, m2, 3);
#pragma unroll
      for (int i = 0; i < 4; i++) { const uint2 q = lds64(av + i * 256); vm[i >> 1][(i & 1) * 2] = q.x; vm[i >> 1][(i & 1) * 2 + 1] = q.y; }
      float sv[10];
#pragma unroll
      for (int u = 0; u < 5; u++) { sv[2 * u] = bf_lo(sl[u]) * SM_SCALE; sv[2 * u + 1] = bf_hi(sl[u]) * SM_SCALE; }
      FEN();
      m2 = hmax2bf(hmax2bf(m2, x1), hmax2bf(x2, x3));
      const float mx = fmaxf(bf_lo(m2), bf_hi(m2));
      float o0[4], o1[4];
#pragma unroll
      for (int i = 0; i < 10; i++) sv[i] = fmaf(mx, -SM_SCALE, sv[i]);
      sv[8] = ex2v(sv[8]); sv[9] = ex2v(sv[9]);
#pragma unroll
      for (int i = 0; i < 8; i++) sv[i] = ex2v(sv[i]);
      { const uint32_t p = pack_bf16(sv[8], sv[9]); mma16816z(o0, vm[0], p, p); mma16816z(o1, vm[1], p, p); }
      { const uint32_t p0 = pack_bf16(sv[0], sv[1]), p1 = pack_bf16(sv[2], sv[3]); mma16816(o0, vx[0], p0, p1); mma16816(o1, vx[2], p0, p1); }
      { const uint32_t p0 = pack_bf16(sv[4], sv[5]), p1 = pack_bf16(sv[6], sv[7]); mma16816(o0, vx[1], p0, p1); mma16816(o1, vx[3], p0, p1); }
      float su = (((sv[8] + sv[9]) + ((sv[0] + sv[1]) + (sv[2] + sv[3]))) + (sv[4] + sv[5])) + (sv[6] + sv[7]);
      { const float a1 = __shfl_xor_sync(~0u, su, 1), a2 = __shfl_xor_sync(~0u, su, 2), a3 = __shfl_xor_sync(~0u, su, 3); su = (su + a1) + (a2 + a3); }
      sts32(aU + 128, __float_as_uint(su));
      stsm4(aO, pack_bf16(o0[0], o0[1]), pack_bf16(o0[2], o0[3]), pack_bf16(o1[0], o1[1]), pack_bf16(o1[2], o1[3]));
      bar_sync(BAR_O, 384);
    }
    const uint32_t t0 = lds32(sb + C_R + 48);
    const uint4 xo = lds128(sb + C_T + 2048 + warp * 512 + lane * 16);
    const uint32_t tag = (s + args.layer + 1) & 1, tm = 0u - tag;
    auto gather = [&](auto NL) {
      constexpr int n = NL.value;
      const char* p = args.comm + xo.z;
      const uint32_t aMw = sb + C_M + 2048 + (warp == 3 ? 5120 : warp * 1024) + lane * 16;
      int lim = 0; bool bad;
      p += wait_until(t0 + args.tb[warp == 3 ? 1 : warp + 1], lane >> 5);
      do { uint4 a[n]; uint32_t m = 0; ++lim;
#pragma unroll
        for (int i = 0; i < n; i++) a[i] = ldg_rlx128(p + (i & 1) * 512 + (i >> 1) * 2048);
#pragma unroll
        for (int i = 0; i < n; i++) { sts128(aMw + (i & 1) * 512 + (i >> 1) * 5120, a[i]); m |= launder((a[i].x ^ tm) | (a[i].z ^ tm)); }
        bad = __any_sync(~0u, (m & 0x10000u) && lim < POLL_LIMIT);
      } while (bad);
      staged();
      if (lane == 0 && warp < 3) { EV(6 + warp, clk() - t0); EV(9 + warp, lim); }
    };
    if (warp == 3) {
      if (lane == 0) { LOGS(c, s); LOGV(c, 192 + (s >> 1), clk());
      }
      uint32_t rdy = 0, e[4][4];
      if (((s + 2) >> 1) >= kv_ok) rdy = ldg_rlx32(args.flags + F_KV + h * 32 + lane);
      spin_until(t0 + args.tc[0]);
      export_ld(e, lane);
      if (XST == 0) export_st(e, s, lane);
      prep(s + 1, lane);
      gather(IC<2>{});
      if (XST == 1) export_st(e, s, lane);
      if (s < 61) {
        spin_until(t0 + args.tc[1]);
        if (((s + 2) >> 1) >= kv_ok) {
          for (int n = 0; (kv_ok = __clz(__brev(~__ballot_sync(~0u, rdy >= 2)))) <= ((s + 2) >> 1) && n < POLL_LIMIT; n++) rdy = ldg_rlx32(args.flags + F_KV + h * 32 + lane);
          asm volatile("fence.acquire.gpu;" ::: "memory");
        }
        load_kv(sb, h, j, s + 2);
      }
    } else {
    if (warp == 2) calib();
    if (warp < 2 || !(c & 16)) {
      const char* p = args.comm + xo.x; char* g2w = args.comm + xo.y;
      const uint32_t s0 = (lane & 8) ? 0u : xo.w, s1 = (lane & 8) ? xo.w : 0u;
      int lim = 0; bool bad;
      p += wait_until(t0 + args.ta[warp == 0 ? 0 : warp == 2 ? 3 : 1 + ((c >> 4) & 1)], lane >> 5);
      do {
        uint4 a[4]; float z0[4], z1[4], y[4];
#pragma unroll
        for (int i = 0; i < 4; i++) a[i] = ldg_rlx128(p + i * 512);
        ++lim;
        { const uint32_t A[4] = {a[0].x, a[0].y, a[0].z, a[0].w}; mma16816z(z0, A, s0, s1); }
        { const uint32_t A[4] = {a[1].x, a[1].y, a[1].z, a[1].w}; mma16816z(z1, A, s0, s1); }
        { const uint32_t A[4] = {a[2].x, a[2].y, a[2].z, a[2].w}; mma16816(z0, A, s0, s1); }
        { const uint32_t A[4] = {a[3].x, a[3].y, a[3].z, a[3].w}; mma16816(z1, A, s0, s1); }
        const uint32_t m0 = launder((a[0].x ^ tm) | (a[0].z ^ tm)), m1 = launder((a[1].x ^ tm) | (a[1].z ^ tm)), m2 = launder((a[2].x ^ tm) | (a[2].z ^ tm)), m3 = launder((a[3].x ^ tm) | (a[3].z ^ tm));
        bad = __any_sync(~0u, ((launder(m0 | m1 | m2) | m3) & 0x10000u) && lim < POLL_LIMIT);
#pragma unroll
        for (int i = 0; i < 4; i++) y[i] = z0[i] + z1[i];
        const bool odd = lane & 1; const float k0 = odd ? y[2] : y[0], k1 = odd ? y[3] : y[1], e0 = odd ? y[0] : y[2], e1 = odd ? y[1] : y[3];
        const float o0 = __shfl_xor_sync(~0u, e0, 1) + __shfl_xor_sync(~0u, e0, 17), o1 = __shfl_xor_sync(~0u, e1, 1) + __shfl_xor_sync(~0u, e1, 17);
        const float q0 = k0 + __shfl_xor_sync(~0u, k0, 16), q1 = k1 + __shfl_xor_sync(~0u, k1, 16);
        const uint32_t w0 = pack_tag(odd ? o0 : q0, odd ? o1 : q1, tag << 16), w1 = pack_bf16(odd ? q0 : o0, odd ? q1 : o1);
        if (!bad) stg_rlx64(g2w, w0, w1);
      } while (bad);
      if (lane == 0 && warp == 0) LOGV(c, 128 + s, lim);
      if (lane == 0) { EV(warp, clk() - t0); EV(3 + warp, lim); }
    }
    prep(s + 1, lane);
    if (warp == 0) gather(IC<2>{}); else gather(IC<4>{});
    }
  }
}

#define PF0 14
#define QORD 0
#define LDA ldg_ef128
#define LDB ldg_na128
#define PFD 2
#define PFR 1
#define PDT 10
#define NPROBE 3
#define OPACE 500
constexpr int G_ST = 163840;
constexpr int B_FULL = 64, B_EMPTY = 96, B_RB = 128, B_WD = 136, B_ROLE = 144, B_PROG = 152, B_WF = 160  , B_DUM = 200;
enum { BAR_T = 1  , BAR_G = 3  , BAR_V = 5   };
DEVINL uint64_t mkdesc(uint32_t a, uint32_t lbo, uint32_t sbo, uint32_t sw) { return (uint64_t)((a & 0x3FFFF) >> 4) | ((uint64_t)(lbo >> 4) << 16) | ((uint64_t)(sbo >> 4) << 32) | ((uint64_t)sw << 62); }
DEVINL void wgmma_n128(float* d, uint64_t a, uint64_t b, int acc) {
  asm volatile("{.reg .pred p; setp.ne.b32 p, %66, 0; wgmma.mma_async.sync.aligned.m64n128k16.f32.bf16.bf16 {%0,%1,%2,%3,%4,%5,%6,%7,%8,%9,%10,%11,%12,%13,%14,%15,%16,%17,%18,%19,%20,%21,%22,%23,%24,%25,%26,%27,%28,%29,%30,%31,%32,%33,%34,%35,%36,%37,%38,%39,%40,%41,%42,%43,%44,%45,%46,%47,%48,%49,%50,%51,%52,%53,%54,%55,%56,%57,%58,%59,%60,%61,%62,%63}, %64, %65, p, 1, 1, 0, 1;}"
               : "+f"(d[0]),"+f"(d[1]),"+f"(d[2]),"+f"(d[3]),"+f"(d[4]),"+f"(d[5]),"+f"(d[6]),"+f"(d[7]),"+f"(d[8]),"+f"(d[9]),"+f"(d[10]),"+f"(d[11]),"+f"(d[12]),"+f"(d[13]),"+f"(d[14]),"+f"(d[15]),"+f"(d[16]),"+f"(d[17]),"+f"(d[18]),"+f"(d[19]),"+f"(d[20]),"+f"(d[21]),"+f"(d[22]),"+f"(d[23]),"+f"(d[24]),"+f"(d[25]),"+f"(d[26]),"+f"(d[27]),"+f"(d[28]),"+f"(d[29]),"+f"(d[30]),"+f"(d[31]),"+f"(d[32]),"+f"(d[33]),"+f"(d[34]),"+f"(d[35]),"+f"(d[36]),"+f"(d[37]),"+f"(d[38]),"+f"(d[39]),"+f"(d[40]),"+f"(d[41]),"+f"(d[42]),"+f"(d[43]),"+f"(d[44]),"+f"(d[45]),"+f"(d[46]),"+f"(d[47]),"+f"(d[48]),"+f"(d[49]),"+f"(d[50]),"+f"(d[51]),"+f"(d[52]),"+f"(d[53]),"+f"(d[54]),"+f"(d[55]),"+f"(d[56]),"+f"(d[57]),"+f"(d[58]),"+f"(d[59]),"+f"(d[60]),"+f"(d[61]),"+f"(d[62]),"+f"(d[63]) : "l"(a), "l"(b), "r"(acc));
}
DEVINL void wgmma_n80(float* d, uint64_t a, uint64_t b, int acc) {
  asm volatile("{.reg .pred p; setp.ne.b32 p, %42, 0; wgmma.mma_async.sync.aligned.m64n80k16.f32.bf16.bf16 {%0,%1,%2,%3,%4,%5,%6,%7,%8,%9,%10,%11,%12,%13,%14,%15,%16,%17,%18,%19,%20,%21,%22,%23,%24,%25,%26,%27,%28,%29,%30,%31,%32,%33,%34,%35,%36,%37,%38,%39}, %40, %41, p, 1, 1, 0, 1;}"
               : "+f"(d[0]),"+f"(d[1]),"+f"(d[2]),"+f"(d[3]),"+f"(d[4]),"+f"(d[5]),"+f"(d[6]),"+f"(d[7]),"+f"(d[8]),"+f"(d[9]),"+f"(d[10]),"+f"(d[11]),"+f"(d[12]),"+f"(d[13]),"+f"(d[14]),"+f"(d[15]),"+f"(d[16]),"+f"(d[17]),"+f"(d[18]),"+f"(d[19]),"+f"(d[20]),"+f"(d[21]),"+f"(d[22]),"+f"(d[23]),"+f"(d[24]),"+f"(d[25]),"+f"(d[26]),"+f"(d[27]),"+f"(d[28]),"+f"(d[29]),"+f"(d[30]),"+f"(d[31]),"+f"(d[32]),"+f"(d[33]),"+f"(d[34]),"+f"(d[35]),"+f"(d[36]),"+f"(d[37]),"+f"(d[38]),"+f"(d[39]) : "l"(a), "l"(b), "r"(acc));
}

template <int N, int NST, bool HAND>
DEVINL void gemm_tile(float* acc, uint32_t sb, uint32_t px, int wg, uint32_t u0, int rot, bool lead, int wph) {
  const uint64_t db = N == 128 ? mkdesc(sb, 81920, 1024, 1) : mkdesc(sb, 32768, 256, 3);
#pragma unroll
  for (int i = 0; i < N / 2; i++) acc[i] = 0.f;
  bar_sync(BAR_T + wg, 256);
#pragma unroll 1
  for (int st = 0; st < NST; st++) {
    const uint32_t u = u0 + st, slot = u & 3, ks = (st + rot >= NST ? st + rot - NST : st + rot) * 8;
    if (wph >= 0) mbar_wait(sb + S_BAR + B_WF + (N == 128 ? st * 8 : 0), wph);
    mbar_wait(sb + S_BAR + B_FULL + slot * 8, (u >> 2) & 1);
    const uint64_t da = mkdesc(sb + G_ST + slot * 16384, 16, 1024, 1);
    asm volatile("wgmma.fence.sync.aligned;" ::: "memory");
#pragma unroll
    for (int k = 0; k < 8; k++) {
      const uint64_t a = da + (k >> 2) * 512 + (k & 3) * 2;
      if (N == 128) wgmma_n128(acc, a, db + (ks + k) * 128, 1); else wgmma_n80(acc, a, db + (ks + k) * 32, 1);
    }
    asm volatile("wgmma.commit_group.sync.aligned;" ::: "memory");
    if (HAND && st == NST - 1) bar_arrive(BAR_T + (wg ^ 1), 256);
    if (st > 0) {
      asm volatile("wgmma.wait_group.sync.aligned 1;" ::: "memory");
      if (lead) { const uint32_t e = sb + S_BAR + B_EMPTY + ((u - 1) & 3) * 8; mbar_arrive(e); mbar_arrive_remote(e + px); }
    }
  }
  asm volatile("wgmma.wait_group.sync.aligned 0;" ::: "memory");
  if (lead) { const uint32_t e = sb + S_BAR + B_EMPTY + ((u0 + NST - 1) & 3) * 8; mbar_arrive(e); mbar_arrive_remote(e + px); }
}
DEVINL void wg_publish(int wg) { bar_sync(BAR_G + wg, 160); }
DEVINL uint32_t km_known(uint32_t sb) { uint32_t v; asm volatile("ld.volatile.shared.u32 %0, [%1];" : "=r"(v) : "r"(sb + S_BAR + B_PROG) : "memory"); return __reduce_min_sync(~0u, v); }
DEVINL void km_load(uint4* f, const char* p) {
#pragma unroll
  for (int G = 0; G < 4; G++) f[G] = ldg_rlx128(p + G * 512);
}
DEVINL void km_check(uint4* f, const char* p, uint32_t tg) {
  int n = 0;
  while (__any_sync(~0u, (((f[0].x ^ tg) | (f[0].z ^ tg) | (f[1].x ^ tg) | (f[1].z ^ tg) | (f[2].x ^ tg) | (f[2].z ^ tg) | (f[3].x ^ tg) | (f[3].z ^ tg)) & 0x10000u) && ++n < POLL_LIMIT)) km_load(f, p);
}
DEVINL void km_watcher(uint32_t sb, const uint32_t* p) {
  uint32_t v = 0;
#pragma unroll 1
  for (int n = 0; n < 16 * POLL_LIMIT && v < 64; n++) {
    const uint2 q = ldg_rlx64(p);
    if (min(q.x, q.y) != v) { v = min(q.x, q.y); asm volatile("st.volatile.shared.u32 [%0], %1;" ::"r"(sb + S_BAR + B_PROG), "r"(v) : "memory"); }
    __nanosleep(v < 61 ? 300 : 20);
  }
}

template <int HF>
DEVINL void attend(const float* acc, uint4 (*kf)[4], uint4* kmf, uint4* op, const char* kvp, const char* mp, bf16* orow, int lane, int wg, uint32_t sb, int tile, bool& pend, uint32_t tg) {
  constexpr int NT = HF ? 4 : 2;
  const int g = lane >> 2, t = lane & 3;
  float sc[NT + 1][4];
#pragma unroll
  for (int k = 0; k < 8; k++) {
    uint32_t qa[4];
#pragma unroll
    for (int i = 0; i < 4; i++) { const float* a = acc + 32 * (k >> 2) + 4 * (k & 3) + 16 * (i >> 1) + 2 * (i & 1); qa[i] = pack_bf16(a[0], a[1]); }
#pragma unroll
    for (int kt = 0; kt <= NT; kt++) {
      const uint4 b = kt < NT ? kf[kt][k >> 1] : kmf[k >> 1];
      if (k == 0) mma16816z(sc[kt], qa, b.x, b.y); else if (k & 1) mma16816(sc[kt], qa, b.z, b.w); else mma16816(sc[kt], qa, b.x, b.y);
    }
  }
  FEN();
  bar_arrive(BAR_T + (wg ^ 1), 256);
  FEN();
  uint32_t go; asm volatile("{.reg .pred p,q; setp.ne.u32 q, %1, 0; bar.red.and.pred p, %2, 128, q; selp.u32 %0, 1, 0, p;}" : "=r"(go) : "r"((uint32_t)(tile < 30 && lds32(sb + S_BAR + B_PROG) > tile * 2 + 5)), "r"(BAR_V + wg) : "memory");
  uint4 vf[HF + 1][8], vm[4];
  auto traffic = [&]() {
    if (pend) {
#pragma unroll
      for (int q = 0; q < 4; q++) { *(uint4*)(orow - 128 * 4096 + q * 32) = op[2 * q]; *(uint4*)(orow - 120 * 4096 + q * 32) = op[2 * q + 1]; }
      wg_publish(wg);
    }
    pend = __any_sync(~0u, go);
    const char* vp = kvp + 4096 + (g >> 1) * 512 + ((g & 1) * 4 + t) * 16; const char* kp = kvp + 4 * 32 * 16384 + lane * 16;
    km_load(vm, mp + 2048 + lane * 16);
    if (pend) km_load(kmf, mp + 4 * 32 * 4096 + lane * 16);
#pragma unroll
    for (int hh = 0; hh <= HF; hh++) {
#pragma unroll
      for (int i = 0; i < 8; i++) { const char* q = vp + hh * 2048 + (i >> 2) * 4096 + (i & 3) * 128; vf[hh][i] = hh ? LDB(q) : LDA(q); }
      if (tile < 30) {
#pragma unroll
        for (int i = 8 * hh; i < 8 * hh + 8; i++) { const char* q = kp + ((i >> 1) & 1) * 12288 + (i >> 2) * 1024 + (i & 1) * 512; kf[i >> 2][i & 3] = hh ? LDB(q) : LDA(q); }
      }
    } };
  if (QORD == 0) traffic();
  const float NINF = __int_as_float(0xff800000);
  if (2 * t > g) { sc[NT - 2][0] = NINF; sc[NT - 1][2] = NINF; }
  if (2 * t + 1 > g) { sc[NT - 2][1] = NINF; sc[NT - 1][3] = NINF; }
  sc[NT - 1][0] = NINF; sc[NT - 1][1] = NINF;
  float m0 = fmaxf(sc[NT][0], sc[NT][1]), m1 = fmaxf(sc[NT][2], sc[NT][3]);
#pragma unroll
  for (int kt = 0; kt < NT; kt++) { m0 = fmaxf(m0, fmaxf(sc[kt][0], sc[kt][1])); m1 = fmaxf(m1, fmaxf(sc[kt][2], sc[kt][3])); }
  m0 = fmaxf(fmaxf(m0, __shfl_xor_sync(~0u, m0, 1)), fmaxf(__shfl_xor_sync(~0u, m0, 2), __shfl_xor_sync(~0u, m0, 3)));
  m1 = fmaxf(fmaxf(m1, __shfl_xor_sync(~0u, m1, 1)), fmaxf(__shfl_xor_sync(~0u, m1, 2), __shfl_xor_sync(~0u, m1, 3)));
  m0 *= -SM_SCALE; m1 *= -SM_SCALE;
  float s0 = 0.f, s1 = 0.f; uint32_t p[NT + 1][2];
#pragma unroll
  for (int kt = 0; kt <= NT; kt++) {
    const float a = ex2(fmaf(sc[kt][0], SM_SCALE, m0)), b = ex2(fmaf(sc[kt][1], SM_SCALE, m0)), c = ex2(fmaf(sc[kt][2], SM_SCALE, m1)), d = ex2(fmaf(sc[kt][3], SM_SCALE, m1));
    s0 += a + b; s1 += c + d; p[kt][0] = pack_bf16(a, b); p[kt][1] = pack_bf16(c, d);
  }
  s0 = (s0 + __shfl_xor_sync(~0u, s0, 1)) + (__shfl_xor_sync(~0u, s0, 2) + __shfl_xor_sync(~0u, s0, 3));
  s1 = (s1 + __shfl_xor_sync(~0u, s1, 1)) + (__shfl_xor_sync(~0u, s1, 2) + __shfl_xor_sync(~0u, s1, 3));
  s0 = rcp(s0); s1 = rcp(s1);
  if (QORD == 1) { FEN(); traffic(); }
  km_check(vm, mp + 2048 + lane * 16, tg);
  if (pend) km_check(kmf, mp + 4 * 32 * 4096 + lane * 16, tg);
#pragma unroll
  for (int grp = 0; grp < 4; grp++) {
    float o[4][4];
#pragma unroll
    for (int L = 0; L < 4; L++) {
      mma1688z(o[L], p[NT][0], p[NT][1], L == 0 ? vm[grp].x : L == 1 ? vm[grp].y : L == 2 ? vm[grp].z : vm[grp].w);
#pragma unroll
      for (int kh = 0; kh <= HF; kh++) {
        const uint4 w = vf[kh][(grp >> 1) * 4 + L]; const uint32_t A[4] = {p[2 * kh][0], p[2 * kh][1], p[2 * kh + 1][0], p[2 * kh + 1][1]};
        if (grp & 1) mma16816(o[L], A, w.z, w.w); else mma16816(o[L], A, w.x, w.y);
      }
    }
    op[2 * grp] = make_uint4(pack_bf16(o[0][0] * s0, o[0][1] * s0), pack_bf16(o[1][0] * s0, o[1][1] * s0), pack_bf16(o[2][0] * s0, o[2][1] * s0), pack_bf16(o[3][0] * s0, o[3][1] * s0));
    op[2 * grp + 1] = make_uint4(pack_bf16(o[0][2] * s1, o[0][3] * s1), pack_bf16(o[1][2] * s1, o[1][3] * s1), pack_bf16(o[2][2] * s1, o[2][3] * s1), pack_bf16(o[3][2] * s1, o[3][3] * s1));
  }
}

DEVINL void gemm_consumer(uint32_t sb, uint32_t px, int wg, int pr, int rank, const ArgsA& args) {
  const int lane = opaque(threadIdx.x & 31), w = __reduce_max_sync(~0u, (threadIdx.x >> 5) & 3);
  const bool lead = lane == 0 && w == 0;
  const int rot5 = pr % 5;
  if (wg == 1) bar_arrive(BAR_T, 256);
  if (threadIdx.x == 0) LOG(64 + pr * 2 + rank, 250);
#pragma unroll 1
  for (int tile = wg; tile < 32; tile += 2) {
    float acc[64];
    gemm_tile<128, 5, true>(acc, sb, px, wg, tile * 5, rot5, lead, tile < 2 ? 0 : -1);
    if (tile >= 30 && lead) mbar_arrive(sb + S_BAR + B_WD);
    char* dst = g_kv + (size_t)((tile * 2 + (w >> 1)) * 32 + pr) * 16384 + (w & 1) * 2048 + lane * 16;
    if (rank == 0) {
#pragma unroll
      for (int G = 0; G < 4; G++)
#pragma unroll
        for (int hh = 0; hh < 2; hh++) {
          const float* a = acc + 32 * (G >> 1) + 8 * (G & 1) + 2 * hh;
          *(uint4*)(dst + (G >> 1) * 12288 + hh * 1024 + (G & 1) * 512) = make_uint4(pack_bf16(a[0], a[1]), pack_bf16(a[16], a[17]), pack_bf16(a[4], a[5]), pack_bf16(a[20], a[21]));
        }
    } else {
#pragma unroll
      for (int i = 0; i < 8; i++) {
        const float* a = acc + (i >> 2) * 32 + (i & 3) * 4;
        *(uint4*)(dst + 4096 + (i >> 2) * 4096 + (i & 3) * 512) = make_uint4(movm(pack_bf16(a[0], a[1])), movm(pack_bf16(a[2], a[3])), movm(pack_bf16(a[16], a[17])), movm(pack_bf16(a[18], a[19])));
      }
    }
    wg_publish(wg);
    if ((threadIdx.x & 127) == 0) LOG(64 + pr * 2 + rank, tile);
  }
  if (threadIdx.x == 0) LOG(64 + pr * 2 + rank, 251);
  if (pr < 16) {
    const int h = 2 * pr + rank;
    flag_wait_warp(args.flags + F_KV + h * 32 + 16 + (lane & 1), 2);
    bool pend = false; uint4 op[8], kf[4][4], kmf[4];
#pragma unroll
    for (int i = 0; i < 16; i++) kf[i >> 2][i & 3] = ldg_cg128(g_kv + (size_t)((wg * 2 + (w >> 1)) * 32 + h) * 16384 + ((i >> 1) & 1) * 12288 + (i >> 2) * 1024 + (i & 1) * 512 + lane * 16);
#pragma unroll
    for (int i = 0; i < 8; i++) op[i] = kmf[i & 3] = make_uint4(0, 0, 0, 0);
#pragma unroll 1
    for (int tile = wg; tile < 32; tile += 2) {
      const uint32_t seg = tile * 2 + (w >> 1);
      const char* kvp = g_kv + (size_t)(seg * 32 + h) * 16384;
      const char* mp = g_kvm + (size_t)(seg * 32 + h) * 4096;
      bf16* orow = g_o + (size_t)(tile * 64 + w * 16 + (lane >> 2)) * 4096 + h * 128 + (lane & 3) * 8;
      if ((tile >> 1) == 6) flag_wait_warp(args.flags + F_KV + h * 32 + 30 + (lane & 1), 2);
      float acc[64];
      gemm_tile<128, 5, false>(acc, sb, px, wg, 160 + tile * 5, rot5, lead, tile < 2 ? 1 : -1);
      if ((threadIdx.x & 127) == 96) LOG(64 + pr * 2 + rank, 64 + tile);
      if (!pend) {
        int n = 0;
        while (km_known(sb) <= seg && ++n < 16 * POLL_LIMIT) {}
        km_load(kmf, mp + lane * 16);
        km_check(kmf, mp + lane * 16, (args.layer ^ 1) << 16);
      }
      if ((threadIdx.x & 127) == 96) LOG(64 + pr * 2 + rank, 96 + tile);
      if (w & 1) attend<1>(acc, kf, kmf, op, kvp, mp, orow, lane, wg, sb, tile, pend, (args.layer ^ 1) << 16); else attend<0>(acc, kf, kmf, op, kvp, mp, orow, lane, wg, sb, tile, pend, (args.layer ^ 1) << 16);
      if (!pend) {
#pragma unroll
        for (int q = 0; q < 4; q++) { *(uint4*)(orow + q * 32) = op[2 * q]; *(uint4*)(orow + 8 * 4096 + q * 32) = op[2 * q + 1]; }
        wg_publish(wg);
      }
      if ((threadIdx.x & 127) == 0) LOG(64 + pr * 2 + rank, 32 + tile);
    }
  } else {
    const int kq = (pr - 16) >> 2, cg = 2 * (pr & 3) + rank;
#pragma unroll 1
    for (int tile = wg; tile < 32; tile += 2) {
      float acc[40];
      gemm_tile<80, 8, true>(acc, sb, px, wg, 160 + tile * 8, (pr & 3) * 2, lead, tile < 2 ? 1 : -1);
      const bool odd = lane & 1;
      bf16* dst = g_part + (size_t)(kq * 2048 + tile * 64 + w * 16 + (lane >> 2)) * 640 + cg * 80 + (lane & 1) * 8 + (lane & 2) * 2;
#pragma unroll
      for (int q = 0; q < 5; q++)
#pragma unroll
        for (int hh = 0; hh < 2; hh++) {
          const uint32_t A = pack_bf16(acc[8 * q + 2 * hh], acc[8 * q + 2 * hh + 1]), B = pack_bf16(acc[8 * q + 4 + 2 * hh], acc[8 * q + 5 + 2 * hh]);
          const uint32_t x = __shfl_xor_sync(~0u, odd ? A : B, 1);
          *(uint2*)(dst + hh * 8 * 640 + q * 16) = odd ? make_uint2(x, B) : make_uint2(A, x);
        }
      wg_publish(wg);
      if ((threadIdx.x & 127) == 0) LOG(64 + pr * 2 + rank, 32 + tile);
    }
  }
  if (wg == 0) bar_sync(BAR_T, 256);
}

DEVINL void gemm_producer(uint32_t sb, int pr, int rank, const ArgsA& args, const CUtensorMap* tq, const CUtensorMap* tk, const CUtensorMap* tv,
                          const CUtensorMap* to32, const CUtensorMap* tx, const CUtensorMap* tao) {
  const uint32_t bWF = sb + S_BAR + B_WF;
  auto load_w = [&](const CUtensorMap* tm, int col, int st) {
    const int r = ((st + pr) % 5) * 2; mbar_arrive_tx(bWF + st * 8, 32768);
#pragma unroll 1
    for (int i = 0; i < 4; i++) tma_2d(sb + (i & 1) * 81920 + (r + (i >> 1)) * 8192, tm, col + (i & 1) * 64, (r + (i >> 1)) * 64, bWF + st * 8); };
  auto att_pf = [&](int tile, int st) {
    if (tile >= 32) return;
    const int q = tile * 64 + 2 * pr + rank;
    if (st < 4) l2_prefetch(g_kv + (size_t)(q + (st >> 1) * 32) * 16384 + (st & 1) * 8192, 8192);
    else if (lds32(sb + S_BAR + B_PROG) > tile * 2 + 1) { l2_prefetch(g_kvm + (size_t)q * 4096, 4096); l2_prefetch(g_kvm + (size_t)(q + 32) * 4096, 4096); } };
  uint32_t u = 0;
  auto push = [&](const CUtensorMap* tm, int c0, int c1) {
    const uint32_t slot = u & 3, full = sb + S_BAR + B_FULL + slot * 8;
    mbar_wait(sb + S_BAR + B_EMPTY + slot * 8, ((u >> 2) & 1) ^ 1);
    mbar_arrive_tx(full, 16384);
    tma_2d_mc(sb + G_ST + slot * 16384 + rank * 8192, tm, c0 + rank * 64, c1, full);
    u++; };
#pragma unroll 1
  for (int st = 0; st < 5; st++) load_w(rank ? tv : tk, pr * 128, st);
  if (args.layer == 0) { flag_wait(args.flags + F_X, 128); fence_proxy_async(); } else pdl_wait();
#pragma unroll 1
  for (int tile = 0; tile < 32; tile++) {
    if (tile == PDT) pdl_launch();
    l2_prefetch((const char*)g_xn + ((tile + 2) & 31) * 81920 + (pr * 2 + rank) * 1280, 1280);
#pragma unroll 1
    for (int st = 0; st < 5; st++) {
      push(tx, ((st + pr) % 5) * 128, tile * 64);
      if (tile >= PF0 && tile < PF0 + 16) {
        const int q = (tile - PF0) * 5 + st; const char* src = (rank ? args.wo : args.wq) + (pr * 80 + q) * 2048;
        if (PFR) { if (q == 0) mbar_arrive_tx(sb + S_BAR + B_DUM, 163840); bulk_g2s(sb + S_END, src, 1024, sb + S_BAR + B_DUM); bulk_g2s(sb + S_END, src + 1024, 1024, sb + S_BAR + B_DUM); }
        else l2_prefetch(src, 2048);
      }
      if (pr < 16 && tile >= 32 - PFD) att_pf(tile + PFD - 32, st);
    }
  }
  if (pr < 16) {
    load_w(tq, (2 * pr + rank) * 128, 0);
#pragma unroll 1
    for (int tile = 0; tile < 32; tile++) {
      if (tile < 30) l2_prefetch((const char*)g_xn + (tile + 2) * 81920 + (pr * 2 + rank) * 2560, 2560);
#pragma unroll 1
      for (int st = 0; st < 5; st++) { push(tx, ((st + pr) % 5) * 128, tile * 64); if (tile == 0 && st < 4) load_w(tq, (2 * pr + rank) * 128, st + 1); att_pf(tile + PFD, st); }
    }
  } else {
    const int kq = (pr - 16) >> 2, cg = 2 * (pr & 3) + rank;
    mbar_wait(sb + S_BAR + B_WD, 0);
    mbar_arrive_tx(bWF, 163840);
#pragma unroll 1
    for (int i = 0; i < 20; i++) { tma_2d(sb + (i % 5) * 32768 + (i / 5) * 8192, to32, cg * 80 + (i % 5) * 16, kq * 1024 + (i / 5) * 256, bWF); __nanosleep(OPACE); }
#pragma unroll 1
    for (int tile = 0; tile < 32; tile++) {
      flag_wait(args.flags + F_O + tile * 4 + kq, 8);
      fence_proxy_async();
#pragma unroll 1
      for (int st = 0; st < 8; st++) push(tao, kq * 1024 + ((st + (pr & 3) * 2) & 7) * 128, tile * 64);
    }
  }
  if (PFR) mbar_wait(sb + S_BAR + B_DUM, 0);
#pragma unroll 1
  for (int i = 0; i < 4; i++, u++) mbar_wait(sb + S_BAR + B_EMPTY + (u & 3) * 8, ((u >> 2) & 1) ^ 1);
}

DEVINL void gemm_publisher(int wg, int pr, int rank, const ArgsA& args) {
#pragma unroll 1
  for (int i = 0; i < 32; i++) {
    const int tile = (i & 15) * 2 + wg;
    bar_sync(BAR_G + wg, 160);
    if ((threadIdx.x & 31) == 0) {
      flag_add(args.flags + (i < 16 ? F_KV + pr * 32 + tile : pr < 16 ? F_O + tile * 4 + (pr >> 2) : F_P + tile * 32));
    }
    __syncwarp();
  }
}

DEVINL void filter_prep(uint32_t* sm, int part, const ArgsA& args) {
  const int tid = threadIdx.x, lane = tid & 31, w = tid >> 5;
  const unsigned short* wr = (const unsigned short*)args.wr; const unsigned short* wi = (const unsigned short*)args.wi;
#pragma unroll 1
  for (int it = part; it < 32; it += 4) {
#pragma unroll 1
    for (int rr = 0; rr < 8; rr += 2) {
      uint32_t a[2][11], b[2][11];
#pragma unroll
      for (int r = 0; r < 2; r++) {
        const int pos = it * 64 + w * 8 + rr + r, th = (pos >> 2) & 127, v = (pos >> 9) * 4 + (pos & 3);
        const int o = ((th >> 3) + 16 * ((th & 7) + (v & 8)) + 256 * (v & 7)) * 321 + lane;
#pragma unroll
        for (int c = 0; c < 11; c++) if (c < 10 || lane == 0) { a[r][c] = wr[o + c * 32]; b[r][c] = wi[o + c * 32]; }
      }
#pragma unroll
      for (int r = 0; r < 2; r++)
#pragma unroll
        for (int c = 0; c < 11; c++) if (c < 10 || lane == 0) sm[(c * 32 + lane) * 65 + w * 8 + rr + r] = a[r][c] | (b[r][c] << 16);
    }
    bar_sync(1, 256);
#pragma unroll 2
    for (int i = tid; i < 64 * 321; i += 256) g_wt[(i >> 6) * 2048 + it * 64 + (i & 63)] = sm[(i >> 6) * 65 + (i & 63)];
    bar_sync(1, 256);
  }
  if (tid == 0) flag_add(args.flags + F_W);
}

__global__ void __cluster_dims__(2, 1, 1) __launch_bounds__(384, 1)
layer_a_kernel(const __grid_constant__ CUtensorMap tq, const __grid_constant__ CUtensorMap tk, const __grid_constant__ CUtensorMap tv,
               const __grid_constant__ CUtensorMap to, const __grid_constant__ CUtensorMap to32, const __grid_constant__ CUtensorMap tx,
               const __grid_constant__ CUtensorMap tao, const __grid_constant__ ArgsA args) {
  extern __shared__ __align__(1024) char smraw[];
  const uint32_t sb = (smem_u32(smraw) + 1023) & ~1023u;
  uint32_t rank; asm volatile("mov.u32 %0, %%cluster_ctarank;" : "=r"(rank));
  rank = __reduce_max_sync(~0u, rank);
  const uint32_t px = __reduce_max_sync(~0u, mapa(sb, rank ^ 1) - sb);
  if (args.layer == 0) LOGK(0, 0);
  uint32_t smid; asm volatile("mov.u32 %0, %%smid;" : "=r"(smid));
  const uint32_t b = sb + S_BAR;
  if (threadIdx.x == 320) {
    mbar_init(b + B_W, 1); mbar_init(b + B_W2, 1); mbar_init(b + B_WV, 1); mbar_init(b + B_WO, 1); mbar_init(b + B_S, 9); mbar_init(b + B_KV, 1); mbar_init(b + B_KV + 8, 1);
    for (int i = 0; i < 4; i++) { mbar_init(b + B_FULL + i * 8, 1); mbar_init(b + B_EMPTY + i * 8, 2); }
    for (int i = 0; i < 5; i++) mbar_init(b + B_WF + i * 8, 1);
    mbar_init(b + B_WD, 2); mbar_init(b + B_RB, 1); mbar_init(b + B_DUM, 1); sts32(b + B_PROG, 0);
    mbar_arrive_tx(b + B_RB, 8);
    asm volatile("fence.mbarrier_init.release.cluster;" ::: "memory");
  }
  __syncwarp();
  asm volatile("barrier.cluster.arrive.relaxed.aligned;" ::: "memory");
  uint32_t role = 0; uint4 xr[5];
  const bool ln = args.layer == 0 && blockIdx.x < 128 && threadIdx.x < 256;
  const size_t off = (size_t)(blockIdx.x * 16 + (threadIdx.x >> 4)) * 640 + (threadIdx.x & 15) * 8;
#pragma unroll
  for (int i = 0; i < 5; i++) xr[i] = ldg128_if(args.x + off + i * 128, ln);
  if (rank == 0 && threadIdx.x >= 256 && threadIdx.x < 320) {
    if (args.layer == 0) {
      uint32_t* p = (uint32_t*)(args.comm + 0x20000 + (threadIdx.x < 288 ? 0x1000 : 0) + (blockIdx.x >> 1) * 32);
      if ((threadIdx.x & 31) < 8) p[threadIdx.x & 31] = 0;
      __syncwarp();
      if ((threadIdx.x & 31) == 0) {
        uint32_t v, best = ~0u;
#pragma unroll 1
        for (int i = 0; i < NPROBE; i++) { const uint32_t t0 = clk(); asm volatile("atom.relaxed.gpu.global.add.u32 %0, [%1], 1;" : "=r"(v) : "l"(p) : "memory"); asm volatile("st.volatile.shared.u32 [%0], %1;" ::"r"(b + 216), "r"(v) : "memory"); best = min(best, clk() - t0); }
        sts32(b + 208 + ((threadIdx.x >> 5) & 1) * 4, best);
      }
      bar_sync(1, 64);
    }
    if (threadIdx.x == 256) {
      int d;
      if (args.layer == 0) { d = (int)(lds32(b + 208) - lds32(b + 212)); g_side[smid & 254] = d; g_side[(smid & 254) + 1] = d; } else d = g_side[smid & 255];
      uint32_t* cnt = args.flags + F_ROLE;
      if (d < 0) { role = atomicAdd(cnt, 1); if (role >= 32) role = 32 + atomicAdd(cnt + 1, 1); }
      else { role = 32 + atomicAdd(cnt + 1, 1); if (role >= 66) role = atomicAdd(cnt, 1); }
    }
    __syncwarp();
  }
  asm volatile("barrier.cluster.wait.aligned;" ::: "memory");
  if (rank == 0 && threadIdx.x == 256) { stasync64(b + B_ROLE, role, 0, b + B_RB); stasync64(b + B_ROLE + px, role, 0, b + B_RB + px); }
  if (ln) {
    float f[40];
#pragma unroll
    for (int i = 0; i < 5; i++) unpack8(xr[i], f + 8 * i);
    ln_row(f);
#pragma unroll
    for (int i = 0; i < 5; i++) *(uint4*)(g_xn + off + i * 128) = pack8(f + 8 * i);
    bar_sync(2, 256);
    if (threadIdx.x == 0) flag_add(args.flags + F_X);
  }
  __syncwarp();
  mbar_wait(b + B_RB, 0);
  role = __reduce_max_sync(~0u, lds32(b + B_ROLE));
  if (threadIdx.x == 352 && args.layer == 0) g_role[smid & 255] = role * 2 + rank;
  if (role != 32) pdl_launch();
  const int wg = __reduce_max_sync(~0u, threadIdx.x >> 7);
  auto U = [](uint32_t x) { return __reduce_max_sync(~0u, opaque(x)); };
  if (wg < 2) {
    asm volatile("setmaxnreg.inc.sync.aligned.u32 224;");
    if (role >= 32) {
      if (role >= 64) { if (args.layer == 0) { filter_prep((uint32_t*)smraw, (role - 64) * 2 + rank, args); if (threadIdx.x == 0) LOG(role * 2 + rank, 0); } }
      else gemm_consumer(U(sb), U(px), U(wg), U(role - 32), U(rank), args);
    } else { if (wg == 0) chain_mma<0>(sb, args); else chain_mma<1>(sb, args); }
  } else {
    asm volatile("setmaxnreg.dec.sync.aligned.u32 56;");
    if (role >= 32) {
      if (role < 64) {
        if (threadIdx.x == 256) gemm_producer(sb, role - 32, rank, args, &tq, &tk, &tv, &to32, &tx, &tao);
        else if (threadIdx.x >= 288 && threadIdx.x < 352) gemm_publisher((threadIdx.x >> 5) - 9, role - 32, rank, args);
        else if (threadIdx.x == 352 && role < 48) km_watcher(sb, args.flags + F_KM + (2 * (role - 32) + rank) * 32);
      }
    } else chain_helper(U(sb), U(px), U(role), U(rank), args, &tq, &tk, &tv, &to);
  }
}

DEVINL float2 cadd(float2 a, float2 b) { return make_float2(a.x + b.x, a.y + b.y); }
DEVINL float2 csub(float2 a, float2 b) { return make_float2(a.x - b.x, a.y - b.y); }
DEVINL float2 cmul(float2 a, float2 b) { return make_float2(fmaf(a.x, b.x, -a.y * b.y), fmaf(a.x, b.y, a.y * b.x)); }
DEVINL float2 cmulc(float2 a, float2 b) { return make_float2(fmaf(a.x, b.x, a.y * b.y), fmaf(a.y, b.x, -a.x * b.y)); }
template <int INV> DEVINL float2 ctw(float2 a, float2 w) { return INV ? cmulc(a, w) : cmul(a, w); }
template <int INV> DEVINL float2 rot(float2 a) { return INV ? make_float2(-a.y, a.x) : make_float2(a.y, -a.x); }
template <int INV> DEVINL void fft4(float2& a, float2& b, float2& c, float2& d) {
  const float2 s0 = cadd(a, c), d0 = csub(a, c), s1 = cadd(b, d), d1 = rot<INV>(csub(b, d));
  a = cadd(s0, s1); b = cadd(d0, d1); c = csub(s0, s1); d = csub(d0, d1);
}
template <int INV> DEVINL float2 w8(float2 a) { const float h = 0.70710678118654752f; const float2 r = rot<INV>(a); return make_float2((a.x + r.x) * h, (a.y + r.y) * h); }
template <int INV> DEVINL void fft8(float2* x) {
  fft4<INV>(x[0], x[2], x[4], x[6]); fft4<INV>(x[1], x[3], x[5], x[7]);
  const float2 e0 = x[0], e1 = x[2], e2 = x[4], e3 = x[6], o0 = x[1], o1 = w8<INV>(x[3]), o2 = rot<INV>(x[5]), o3 = rot<INV>(w8<INV>(x[7]));
  x[0] = cadd(e0, o0); x[1] = cadd(e1, o1); x[2] = cadd(e2, o2); x[3] = cadd(e3, o3);
  x[4] = csub(e0, o0); x[5] = csub(e1, o1); x[6] = csub(e2, o2); x[7] = csub(e3, o3);
}
template <int INV> DEVINL void fft16(float2* x) {
  const float c = 0.92387953251128674f, s = 0.38268343236508977f;
  const float2 w1 = make_float2(c, -s), w3 = make_float2(s, -c);
#pragma unroll
  for (int i = 0; i < 4; i++) fft4<INV>(x[i], x[i + 4], x[i + 8], x[i + 12]);
  x[5] = ctw<INV>(x[5], w1); x[9] = w8<INV>(x[9]); x[13] = ctw<INV>(x[13], w3);
  x[6] = w8<INV>(x[6]); x[10] = rot<INV>(x[10]); x[14] = rot<INV>(w8<INV>(x[14]));
  x[7] = ctw<INV>(x[7], w3); x[11] = rot<INV>(w8<INV>(x[11])); x[15] = ctw<INV>(x[15], make_float2(-c, s));
#pragma unroll
  for (int k = 0; k < 4; k++) fft4<INV>(x[4 * k], x[4 * k + 1], x[4 * k + 2], x[4 * k + 3]);
#pragma unroll
  for (int k = 0; k < 4; k++)
#pragma unroll
    for (int m = k + 1; m < 4; m++) { const float2 t = x[4 * k + m]; x[4 * k + m] = x[4 * m + k]; x[4 * m + k] = t; }
}
template <int INV> DEVINL void fft5(float2& x0, float2& x1, float2& x2, float2& x3, float2& x4) {
  const float c1 = 0.30901699437494742f, c2 = -0.80901699437494742f, s1 = 0.95105651629515357f, s2 = 0.58778525229247313f;
  const float2 a1 = cadd(x1, x4), a2 = cadd(x2, x3), b1 = rot<INV>(csub(x1, x4)), b2 = rot<INV>(csub(x2, x3));
  const float2 p1 = make_float2(fmaf(c1, a1.x, fmaf(c2, a2.x, x0.x)), fmaf(c1, a1.y, fmaf(c2, a2.y, x0.y)));
  const float2 p2 = make_float2(fmaf(c2, a1.x, fmaf(c1, a2.x, x0.x)), fmaf(c2, a1.y, fmaf(c1, a2.y, x0.y)));
  const float2 q1 = make_float2(fmaf(s1, b1.x, s2 * b2.x), fmaf(s1, b1.y, s2 * b2.y));
  const float2 q2 = make_float2(fmaf(s2, b1.x, -s1 * b2.x), fmaf(s2, b1.y, -s1 * b2.y));
  x0 = cadd(x0, cadd(a1, a2)); x1 = cadd(p1, q1); x4 = csub(p1, q1); x2 = cadd(p2, q2); x3 = csub(p2, q2);
}
template <int INV> DEVINL void fft20(const float2* in, float2* out) {
  float2 t[4][5];
#pragma unroll
  for (int a = 0; a < 4; a++) {
#pragma unroll
    for (int b = 0; b < 5; b++) t[a][b] = in[(5 * a + 4 * b) % 20];
    fft5<INV>(t[a][0], t[a][1], t[a][2], t[a][3], t[a][4]);
  }
#pragma unroll
  for (int d = 0; d < 5; d++) {
    fft4<INV>(t[0][d], t[1][d], t[2][d], t[3][d]);
#pragma unroll
    for (int c = 0; c < 4; c++) out[(5 * c + 16 * d) % 20] = t[c][d];
  }
}
constexpr int ZP = 336;
struct RowSmem { float2 T[320 * 17]; uint32_t Z[16 * ZP]; float2 tw[320]; float2 tp[160]; };
DEVINL float2 cis(int k, int n) {
  float sn, cs; __sincosf((float)(2 * k > n ? k - n : k) * (-6.283185307179586f / (float)n), &sn, &cs); return make_float2(cs, sn);
}
DEVINL void row_tables(RowSmem& sm) {
  const int t = threadIdx.x;
  sm.tw[t] = cis((t >> 4) * (t & 15), 320);
  if (t < 160) sm.tp[t] = cis(t, 640);
}

#define WCH 10240
#define WST 2
#define CREG 80
#define IREG 88
#define YPT 1
#define R1E 1
#define IDRY 0
#define CDRY 0
#define RDRY 1

__global__ void __launch_bounds__(320, 1) rows_fwd_kernel(const bf16* __restrict__ xin, const uint32_t* flags) {
  extern __shared__ __align__(1024) char smraw[]; RowSmem& sm = *(RowSmem*)smraw;
  const int tid = threadIdx.x, wp = __reduce_max_sync(~0u, tid >> 5), nr = blockIdx.x < 124 ? 16 : 8, s0 = blockIdx.x < 124 ? blockIdx.x * 16 : 992 + blockIdx.x * 8;
  const uint32_t* flag = flags + F_P + (s0 >> 6) * 32;
  LOGK(1 + 3 * (xin == g_x), 0);
  if (R1E) pdl_launch();
  if (tid == 0) l2_prefetch(xin + s0 * 640, nr * 1280);
  row_tables(sm);
#pragma unroll 1
  for (int live = !RDRY || wp != 1 || __any_sync(~0u, ldg_rlx32(flag) >= 32); live < 2; live++) {
    if (live) {
      if (wp == 0) { uint32_t v; int n = 0;
        while (true) { asm volatile("ld.acquire.gpu.global.u32 %0, [%1];" : "=r"(v) : "l"(flag) : "memory"); if (__all_sync(~0u, v >= 32 || ++n >= 8 * POLL_LIMIT)) break; __nanosleep(v ? 20 : 200); } }
      __syncthreads();
      if (!R1E) pdl_launch();
      LOGK(1 + 3 * (xin == g_x), 1);
    }
    if (wp * 2 < nr) {
      const int row = tid >> 4, j = tid & 15; const size_t off = (size_t)(s0 + row) * 640 + j * 8;
      float f[40]; uint4 in[5][5];
#pragma unroll
      for (int i = 0; i < 5; i++) {
#pragma unroll
        for (int q = 0; q < 4; q++) in[i][q] = ldg128_if(g_part + q * 2048 * 640 + off + i * 128, live);
        in[i][4] = ldg128_if(xin + off + i * 128, live);
      }
#pragma unroll
      for (int i = 0; i < 5; i++) {
        float a[8], b[8], c[8], d[8];
        unpack8(in[i][0], a); unpack8(in[i][1], b); unpack8(in[i][2], c); unpack8(in[i][3], d);
#pragma unroll
        for (int e = 0; e < 8; e++) a[e] = (a[e] + b[e]) + (c[e] + d[e]);
        const uint4 o = pack8(a), x = in[i][4];
        const uint4 r = make_uint4(hadd2bf(o.x, x.x), hadd2bf(o.y, x.y), hadd2bf(o.z, x.z), hadd2bf(o.w, x.w));
        stg128_if(g_x + off + i * 128, r, live); unpack8(r, f + 8 * i);
      }
      ln_row(f);
#pragma unroll
      for (int i = 0; i < 5; i++) *(uint4*)(sm.Z + row * ZP + i * 64 + j * 4) = pack8(f + 8 * i);
      __syncwarp();
      float2 z[20], y[20];
#pragma unroll
      for (int n1 = 0; n1 < 20; n1++) { const uint32_t w = sm.Z[row * ZP + n1 * 16 + j]; z[n1] = make_float2(bf_lo(w), bf_hi(w)); }
      fft20<0>(z, y);
#pragma unroll
      for (int k1 = 1; k1 < 20; k1++) y[k1] = cmul(y[k1], sm.tw[k1 * 16 + j]);
#pragma unroll
      for (int k1 = 0; k1 < 20; k1++) sm.T[(k1 * 16 + j) * 17 + row] = y[k1];
    }
    if (live) __syncthreads();
    const int up = (tid >> 4) & 1, row = tid & 15, k1 = wp ? (up ? 20 - wp : wp) : up * 10;
    float2 x[16];
#pragma unroll
    for (int n2 = 0; n2 < 16; n2++) x[n2] = sm.T[(k1 * 16 + n2) * 17 + row];
    float2 tp[8];
#pragma unroll
    for (int k2 = 0; k2 < 8; k2++) tp[k2] = sm.tp[k1 + 20 * k2];
    fft16<0>(x);
    uint32_t* ya = g_y + s0 + row + k1 * 2048; uint32_t* yb = g_y + s0 + row + (320 - k1) * 2048;
    const int on = live && row < nr;
    stg32_if(g_y + s0 + row + 160 * 2048, pack_f16(2.f * x[8].x, -2.f * x[8].y), on && k1 == 0);
    const int src = (tid & 31) ^ (wp ? 16 : 0); uint32_t wa[8], wb[8];
#pragma unroll
    for (int k2 = 0; k2 < 8; k2++) {
      const float2 c = k1 ? x[15 - k2] : x[(16 - k2) & 15], b = make_float2(__shfl_sync(~0u, c.x, src), __shfl_sync(~0u, c.y, src)), a = x[k2];
      const float2 E = make_float2(a.x + b.x, a.y - b.y), O = cmul(make_float2(a.y + b.y, b.x - a.x), tp[k2]);
      wa[k2] = pack_f16(E.x + O.x, E.y + O.y); wb[k2] = pack_f16(E.x - O.x, O.y - E.y);
    }
#pragma unroll
    for (int k2 = 0; k2 < 8; k2++) { stg32_if(ya + k2 * 20 * 2048, wa[k2], on); stg32_if(yb - k2 * 20 * 2048, wb[k2], on); }
  }
  LOGK(1 + 3 * (xin == g_x), 2);
  if (blockIdx.x == gridDim.x - 1) pdl_wait();
}

__global__ void __maxnreg__(CREG) cols_kernel(int layer) {
  extern __shared__ __align__(1024) char smraw[];
  const int sub = threadIdx.x >> 7, tid = threadIdx.x & 127, col = blockIdx.x * 3 + sub, k1 = tid >> 3, j0 = tid & 7;
  float2* sm = (float2*)smraw + sub * (16 * 152);
  float2* tw = (float2*)smraw + 3 * 16 * 152;
  LOGK(2 + 3 * layer, 0);
  pdl_launch();
  uint32_t* y = g_y + col * 2048 + tid;
  uint4 wf[4];
  flag_wait_warp(g_flags + F_W, 4);
#pragma unroll
  for (int i = 0; i < 4; i++) wf[i] = ldg_cg128(g_wt + col * 2048 + i * 512 + tid * 4);
  if (YPT) {
#pragma unroll
    for (int i = 0; i < 4; i++) asm volatile("cp.async.cg.shared.global [%0], [%1], 16;" ::"r"(smem_u32(sm) + tid * 16), "l"(g_y + col * 2048 + min(i * 512 + tid * 4, 1916)) : "memory");
  }
#pragma unroll 1
  for (int i = threadIdx.x; i < 2176; i += 384) {
    const int a = i < 2048 ? i >> 7 : (i - 2048) >> 3, b = i < 2048 ? i & 127 : i & 7;
    tw[i < 2048 ? a * 136 + b : 2176 + a * 9 + b] = cis(i < 2048 ? a * b : a * b * 16, 2048);
  }
  asm volatile("cp.async.wait_all;" ::: "memory");
  float2* reg = sm + k1 * 152;
#pragma unroll 1
  for (int live = !CDRY || __any_sync(~0u, threadIdx.x >= 32 || ldg_rlx32(g_flags + layer * F_LAYER + F_P + 31 * 32) >= CDRY); live < 2; live++)
#pragma unroll
  for (int it = 0; it < 4; it++) {
    float2 x[16];
    if (it == 0) {
      if (live) { __syncthreads(); pdl_wait(); LOGK(2 + 3 * layer, 1); }
#pragma unroll
      for (int i = 0; i < 16; i++) { const uint32_t w = ldg32_if(y + i * 128, live); x[i] = __half22float2(*(const __half2*)&w); }
    } else {
      const float2* in = it == 3 ? sm + tid : reg + j0; const int is = it == 1 ? 8 : it == 2 ? 9 : 152;
#pragma unroll
      for (int i = 0; i < 16; i++) x[i] = in[i * is];
    }
    fft16<0>(x);
    if (it == 3) {
      const float sc = 1.f / 4096.f;
#pragma unroll
      for (int i = 0; i < 16; i++) stg32_if(y + i * 128, pack_bf16(x[i].y * sc, x[i].x * sc), live);
    } else {
      const float2* t = it == 0 ? tw + tid : it == 1 ? tw + 2176 + j0 : tw + k1 * 136 + j0; const int ts = it == 0 ? 136 : it == 1 ? 9 : 8;
      float2* o = it == 0 ? sm + tid : reg + j0; const int os = it == 0 ? 152 : it == 1 ? 9 : 8;
#pragma unroll
      for (int k = 0; k < 16; k++) if (k > 0 || it == 2) x[k] = cmul(x[k], t[k * ts]);
      __syncwarp();
#pragma unroll
      for (int k = 0; k < 16; k++) o[k * os] = x[k];
      if (it == 1) {
        __syncwarp();
        float2* r9 = reg + j0 * 9;
#pragma unroll
        for (int i = 0; i < 16; i++) x[i] = r9[(i & 8) * 9 + (i & 7)];
#pragma unroll
        for (int h = 0; h < 2; h++) {
          fft8<0>(x); fft8<0>(x + 8);
          if (h == 0) {
#pragma unroll
            for (int i = 0; i < 16; i++) {
              const uint32_t w = (i & 3) == 0 ? wf[i >> 2].x : (i & 3) == 1 ? wf[i >> 2].y : (i & 3) == 2 ? wf[i >> 2].z : wf[i >> 2].w;
              const float2 v = cmul(x[i], make_float2(bf_lo(w), bf_hi(w))); x[i] = make_float2(v.y, v.x);
            }
          }
        }
        const float2* t9 = tw + 2176 + j0 * 9;
#pragma unroll
        for (int i = 0; i < 16; i++) if (i & 7) x[i] = cmul(x[i], t9[(i & 8) * 9 + (i & 7)]);
#pragma unroll
        for (int i = 0; i < 16; i++) r9[(i & 8) * 9 + (i & 7)] = x[i];
        __syncwarp();
      } else if (live) bar_sync(sub + 1, 128);
    }
  }
  LOGK(2 + 3 * layer, 2);
}

__global__ void __maxnreg__(IREG) rows_inv_kernel(bf16* __restrict__ xout, int do_ln, const __grid_constant__ Wts w) {
  extern __shared__ __align__(1024) char smraw[]; RowSmem& sm = *(RowSmem*)smraw;
  const int tid = threadIdx.x, s0 = blockIdx.x * 16, wp = __reduce_max_sync(~0u, tid >> 5);
  LOGK(3 + 3 * !do_ln, 0);
  const uint32_t ctl = smem_u32(smraw) + 72 * 1024;
  if (tid == 0) sts32(ctl + 8, 0);
  __syncthreads();
  if (wp == 10) { if (WCH && do_ln && tid == 320) weight_warm<WCH ? WCH : 16>(w, ctl + 1024, ctl, ctl + 8); return; }
  if (tid == 0) l2_prefetch(g_x + s0 * 640, 20480);
  row_tables(sm);
  const size_t off = (size_t)(s0 + ((tid >> 4) & 15)) * 640 + (tid & 15) * 8;
#pragma unroll 1
  for (int live = wp != 1 || (!IDRY && do_ln < 2); live < 2; live++) {
    if (live) {
      bar_sync(1, 320);
      pdl_wait();
      pdl_launch();
      if (WST == 0 && tid == 0) sts32(ctl + 8, 1);
      LOGK(3 + 3 * !do_ln, 1);
    }
    uint4 xr[5];
    {
      const int up = (tid >> 4) & 1, row = tid & 15, k1 = wp ? (up ? 20 - wp : wp) : up * 10;
      const uint32_t* ya = g_y + s0 + row + k1 * 2048; const uint32_t* yb = g_y + s0 + row + (320 - k1) * 2048;
      uint32_t wa[8], wb[8];
#pragma unroll
      for (int k2 = 0; k2 < 8; k2++) { wa[k2] = ldg32_if(ya + k2 * 20 * 2048, live); wb[k2] = ldg32_if(yb - k2 * 20 * 2048, live); }
      const uint32_t wm = ldg32_if(g_y + s0 + row + 160 * 2048, live && k1 == 0);
#pragma unroll
      for (int i = 0; i < 5; i++) xr[i] = ldg128_if(g_x + off + i * 128, live && wp < 8);
      stg32_if(g_flags + blockIdx.x * 320 + tid, 0, live && !do_ln && blockIdx.x * 320 + tid < 2 * F_LAYER);
      if (k1 == 0) { wa[0] &= 0xffffu; wb[0] &= 0xffffu; }
      float2 x[16], r[8];
#pragma unroll
      for (int k2 = 0; k2 < 8; k2++) {
        const float2 a = make_float2(bf_lo(wa[k2]), bf_hi(wa[k2])), b = make_float2(bf_lo(wb[k2]), bf_hi(wb[k2]));
        const float2 E = make_float2(a.x + b.x, a.y - b.y), O = cmulc(make_float2(a.x - b.x, a.y + b.y), sm.tp[k1 + 20 * k2]);
        x[k2] = make_float2(E.x - O.y, E.y + O.x); r[k2] = make_float2(E.x + O.y, O.x - E.y);
      }
      if (k1 == 0) r[0] = make_float2(2.f * bf_lo(wm), -2.f * bf_hi(wm));
      const int src = (tid & 31) ^ (wp ? 16 : 0);
#pragma unroll
      for (int i = 8; i < 16; i++) { const float2 c = k1 ? r[15 - i] : r[(16 - i) & 7]; x[i] = make_float2(__shfl_sync(~0u, c.x, src), __shfl_sync(~0u, c.y, src)); }
      fft16<1>(x);
#pragma unroll
      for (int n2 = 0; n2 < 16; n2++) sm.T[(k1 * 16 + n2) * 17 + row] = x[n2];
    }
    if (live) { bar_sync(1, 320); if (WST == 1 && tid == 0) sts32(ctl + 8, 1); }
    if (wp < 8) {
      const int row = tid >> 4, n2 = tid & 15;
      float2 z[20], y[20];
#pragma unroll
      for (int k1 = 0; k1 < 20; k1++) { const float2 t = sm.T[(k1 * 16 + n2) * 17 + row]; z[k1] = k1 ? cmulc(t, sm.tw[k1 * 16 + n2]) : t; }
      fft20<1>(z, y);
      const float sc = 1.f / 640.f;
#pragma unroll
      for (int n1 = 0; n1 < 20; n1++) sm.Z[row * ZP + n1 * 16 + n2] = pack_bf16(y[n1].x * sc, y[n1].y * sc);
      __syncwarp();
      if (WST == 2 && live && tid == 0) sts32(ctl + 8, 1);
      float f[40];
#pragma unroll
      for (int i = 0; i < 5; i++) {
        const uint4 o = *(const uint4*)(sm.Z + row * ZP + i * 64 + n2 * 4), x = xr[i];
        xr[i] = make_uint4(hadd2bf(o.x, x.x), hadd2bf(o.y, x.y), hadd2bf(o.z, x.z), hadd2bf(o.w, x.w));
      }
#pragma unroll
      for (int i = 0; i < 5; i++) { stg128_if(xout + off + i * 128, xr[i], live); unpack8(xr[i], f + 8 * i); }
      if (do_ln) {
        ln_row(f);
#pragma unroll
        for (int i = 0; i < 5; i++) stg128_if(g_xn + off + i * 128, pack8(f + 8 * i), live);
      }
    }
  }
  LOGK(3 + 3 * !do_ln, 2);
}

typedef CUresult (*EncFn)(CUtensorMap*, CUtensorMapDataType, cuuint32_t, void*, const cuuint64_t*, const cuuint64_t*, const cuuint32_t*, const cuuint32_t*,
                          CUtensorMapInterleave, CUtensorMapSwizzle, CUtensorMapL2promotion, CUtensorMapFloatOOBfill);
static void make_map(EncFn fn, CUtensorMap* m, const void* p, uint64_t cols, uint64_t rows, uint32_t bc, uint32_t br, CUtensorMapSwizzle sw) {
  cuuint64_t gd[2] = {cols, rows}, gs[1] = {cols * 2}; cuuint32_t bd[2] = {bc, br}, es[2] = {1, 1};
  fn(m, CU_TENSOR_MAP_DATA_TYPE_BFLOAT16, 2, (void*)p, gd, gs, bd, es, CU_TENSOR_MAP_INTERLEAVE_NONE, sw, CU_TENSOR_MAP_L2_PROMOTION_L2_128B, CU_TENSOR_MAP_FLOAT_OOB_FILL_NONE);
}
template <class... P, class... A>
static void launch(void (*k)(P...), int grid, int block, int smem, bool pdl, A... a) {
  cudaLaunchConfig_t cfg = {}; cfg.gridDim = dim3(grid); cfg.blockDim = dim3(block); cfg.dynamicSmemBytes = smem; cfg.stream = cudaStreamPerThread;
  cudaLaunchAttribute at[1]; at[0].id = cudaLaunchAttributeProgrammaticStreamSerialization; at[0].val.programmaticStreamSerializationAllowed = 1;
  cfg.attrs = at; cfg.numAttrs = pdl ? 1 : 0;
  cudaLaunchKernelEx(&cfg, k, a...);
}
static const int tune_t[10] = {1370, 1725, 1845, 1970, 2170, 2490, 2590, 2710, 2050, 2420}; constexpr int dev_stop = 100, dev_pdl = 1;

extern "C" void kernel_launch(void* const* d_in, const int* in_sizes, int n_in, void* d_out, int out_size) {
  const bf16 *x = (const bf16*)d_in[0], *mem0 = (const bf16*)d_in[1], *Wq = (const bf16*)d_in[2], *Wk = (const bf16*)d_in[3], *Wv = (const bf16*)d_in[4], *Wo = (const bf16*)d_in[5];
  const bf16 *wr = (const bf16*)d_in[8], *wi = (const bf16*)d_in[9];
  constexpr int SM_A = S_END + 2048, SM_R = sizeof(RowSmem), SM_C = 114 * 1024, SM_I = 96 * 1024;
  void *p_xn, *p_o, *p_x, *p_comm, *p_flags, *fn; cudaDriverEntryPointQueryResult qr;
  cudaGetSymbolAddress(&p_xn, g_xn); cudaGetSymbolAddress(&p_o, g_o); cudaGetSymbolAddress(&p_x, g_x); cudaGetSymbolAddress(&p_comm, g_comm); cudaGetSymbolAddress(&p_flags, g_flags);
  cudaGetDriverEntryPoint("cuTensorMapEncodeTiled", &fn, cudaEnableDefault, &qr);
  cudaFuncSetAttribute(layer_a_kernel, cudaFuncAttributeMaxDynamicSharedMemorySize, SM_A);
  cudaFuncSetAttribute(rows_fwd_kernel, cudaFuncAttributeMaxDynamicSharedMemorySize, SM_R);
  cudaFuncSetAttribute(rows_inv_kernel, cudaFuncAttributeMaxDynamicSharedMemorySize, SM_I);
  cudaFuncSetAttribute(cols_kernel, cudaFuncAttributeMaxDynamicSharedMemorySize, SM_C);
  cudaFuncSetAttribute(rows_fwd_kernel, cudaFuncAttributePreferredSharedMemoryCarveout, 100);
  cudaFuncSetAttribute(cols_kernel, cudaFuncAttributePreferredSharedMemoryCarveout, 100);
  cudaFuncSetAttribute(rows_inv_kernel, cudaFuncAttributePreferredSharedMemoryCarveout, 100);
  CUtensorMap tq, tk, tv, to, to32, tx, tao; EncFn enc = (EncFn)fn;
  make_map(enc, &tq, Wq, 4096, 640, 64, 64, CU_TENSOR_MAP_SWIZZLE_128B); make_map(enc, &tk, Wk, 4096, 640, 64, 64, CU_TENSOR_MAP_SWIZZLE_128B);
  make_map(enc, &tv, Wv, 4096, 640, 64, 64, CU_TENSOR_MAP_SWIZZLE_128B); make_map(enc, &to, Wo, 640, 4096, 64, 64, CU_TENSOR_MAP_SWIZZLE_128B);
  make_map(enc, &to32, Wo, 640, 4096, 16, 256, CU_TENSOR_MAP_SWIZZLE_32B);
  make_map(enc, &tx, p_xn, 640, 2048, 64, 64, CU_TENSOR_MAP_SWIZZLE_128B); make_map(enc, &tao, p_o, 4096, 2048, 64, 64, CU_TENSOR_MAP_SWIZZLE_128B);
  char* comm = (char*)(((uintptr_t)p_comm + (2 << 20) - 1) & ~(uintptr_t)((2 << 20) - 1));
  const bool pdl = dev_pdl;
#define L0PDL 0
  for (int l = 0; l < 2; l++) {
    ArgsA a{x, mem0, comm, (uint32_t*)p_flags + l * F_LAYER, wr, wi, (const char*)Wq, (const char*)Wo, l, {tune_t[0], tune_t[1], tune_t[2], tune_t[3]}, {tune_t[4], tune_t[5], tune_t[6], tune_t[7]}, {tune_t[8], tune_t[9]}};
    const Wts w = {{(const char*)Wk, (const char*)Wq, (const char*)Wv, (const char*)Wo}};
    if (dev_stop > 4 * l + 0) launch(layer_a_kernel, 132, 384, SM_A, pdl && (l || L0PDL), tq, tk, tv, to, to32, tx, tao, a);
    if (dev_stop > 4 * l + 1) launch(rows_fwd_kernel, 132, 320, SM_R, pdl, l ? (const bf16*)p_x : x, (const uint32_t*)a.flags);
    if (dev_stop > 4 * l + 2) launch(cols_kernel, 107, 384, SM_C, pdl, l);
    if (dev_stop > 4 * l + 3) launch(rows_inv_kernel, 128, 352, SM_I, pdl, l ? (bf16*)d_out : (bf16*)p_x, l == 0, w);
  }
}
```

```cpp
#include <cuda_runtime.h>
#include <cuda_bf16.h>
#include <cuda_fp16.h>
#include <cuda.h>
#include <stdint.h>

typedef __nv_bfloat16 bf16;
#define DEVINL __device__ __forceinline__

__device__ __align__(1024) bf16 g_xn[2048 * 640];
__device__ __align__(1024) bf16 g_x[2048 * 640];
__device__ __align__(1024) char g_kv[64 * 32 * 16384];
__device__ __align__(1024) char g_kvm[64 * 32 * 4096];
__device__ __align__(1024) bf16 g_o[2048 * 4096];
__device__ __align__(1024) bf16 g_part[4 * 2048 * 640];
__device__ __align__(1024) uint32_t g_y[321 * 2048];
__device__ __align__(1024) uint32_t g_wt[321 * 2048];
__device__ __align__(4096) char g_comm[4 << 20];
constexpr int F_KV = 0, F_KM = 1024, F_O = F_KM + 1024, F_P = F_O + 128, F_ROLE = F_P + 32 * 32, F_X = F_ROLE + 64, F_W = F_X + 32, F_LAYER = F_W + 32;
__device__ __align__(1024) uint32_t g_flags[2 * F_LAYER];
__device__ int g_side[256];
__device__ uint32_t g_role[256];

template <int V> struct IC { static constexpr int value = V; };
template <int B, int E, class F> DEVINL void static_for(F&& f) { if constexpr (B < E) { f(IC<B>{}); static_for<B + 1, E>(f); } }

#define POLL_LIMIT (1 << 17)
DEVINL uint32_t smem_u32(const void* p) { return (uint32_t)__cvta_generic_to_shared(p); }
DEVINL uint32_t mapa(uint32_t a, uint32_t r) { uint32_t o; asm volatile("mapa.shared::cluster.u32 %0, %1, %2;" : "=r"(o) : "r"(a), "r"(r)); return o; }
DEVINL uint32_t clk() { uint32_t v; asm volatile("{.reg .b64 w; mov.u64 w, %%clock64; cvt.u32.u64 %0, w;}" : "=r"(v)::"memory"); return v; }
DEVINL void mbar_init(uint32_t bar, uint32_t cnt) { asm volatile("mbarrier.init.shared::cta.b64 [%0], %1;" ::"r"(bar), "r"(cnt) : "memory"); }
DEVINL void mbar_arrive(uint32_t bar) { asm volatile("mbarrier.arrive.shared::cta.b64 _, [%0];" ::"r"(bar) : "memory"); }
DEVINL void mbar_arrive_remote(uint32_t bar) { asm volatile("mbarrier.arrive.shared::cluster.b64 _, [%0];" ::"r"(bar) : "memory"); }
DEVINL void mbar_arrive_tx(uint32_t bar, uint32_t tx) { asm volatile("mbarrier.arrive.expect_tx.shared::cta.b64 _, [%0], %1;" ::"r"(bar), "r"(tx) : "memory"); }
DEVINL void mbar_wait(uint32_t bar, uint32_t ph) {
  asm volatile("{.reg .pred p; .reg .b32 c,q; shl.b32 c, %1, 20;\n"
               "W0: bfe.u32 q, c, 20, 1; mbarrier.try_wait.parity.shared::cta.b64 p, [%0], q; add.u32 c,c,1; @!p bra.uni W0;}" ::"r"(bar), "r"(ph) : "memory");
}
DEVINL void bar_sync(int id, int n) { asm volatile("bar.sync %0, %1;" ::"r"(id), "r"(n) : "memory"); }
DEVINL void bar_arrive(int id, int n) { asm volatile("bar.arrive %0, %1;" ::"r"(id), "r"(n) : "memory"); }
DEVINL void cluster_sync() { asm volatile("barrier.cluster.arrive.release.aligned; barrier.cluster.wait.acquire.aligned;" ::: "memory"); }
DEVINL void bulk_g2s(uint32_t dst, const void* src, uint32_t bytes, uint32_t bar) {
  asm volatile("cp.async.bulk.shared::cluster.global.mbarrier::complete_tx::bytes [%0], [%1], %2, [%3];" ::"r"(dst), "l"(src), "r"(bytes), "r"(bar) : "memory");
}
#define ELECT "{.reg .pred e; elect.sync _|e, 0xffffffff; @e "
DEVINL void w_expect(uint32_t bar, uint32_t tx) { asm volatile(ELECT "mbarrier.arrive.expect_tx.shared::cta.b64 _, [%0], %1;}" ::"r"(bar), "r"(tx) : "memory"); }
DEVINL void w_tma(uint32_t dst, const CUtensorMap* tm, int c0, int c1, uint32_t bar) {
  asm volatile(ELECT "cp.async.bulk.tensor.2d.shared::cluster.global.mbarrier::complete_tx::bytes [%0], [%1, {%2, %3}], [%4];}" ::"r"(dst), "l"(tm), "r"(c0), "r"(c1), "r"(bar) : "memory");
}
DEVINL void w_tma_mc(uint32_t dst, const CUtensorMap* tm, int c0, int c1, uint32_t bar) {
  asm volatile(ELECT "cp.async.bulk.tensor.2d.shared::cluster.global.mbarrier::complete_tx::bytes.multicast::cluster [%0], [%1, {%2, %3}], [%4], %5;}" ::"r"(dst), "l"(tm), "r"(c0), "r"(c1), "r"(bar), "h"((uint16_t)3) : "memory");
}
DEVINL void w_bulk(uint32_t dst, const void* src, uint32_t bytes, uint32_t bar) {
  asm volatile(ELECT "cp.async.bulk.shared::cluster.global.mbarrier::complete_tx::bytes [%0], [%1], %2, [%3];}" ::"r"(dst), "l"(src), "r"(bytes), "r"(bar) : "memory");
}
DEVINL void w_prefetch(const void* p, uint32_t bytes) { asm volatile(ELECT "cp.async.bulk.prefetch.L2.global [%0], %1;}" ::"l"(p), "r"(bytes) : "memory"); }
DEVINL void l2_prefetch(const void* p, uint32_t bytes) { asm volatile("cp.async.bulk.prefetch.L2.global [%0], %1;" ::"l"(p), "r"(bytes) : "memory"); }
DEVINL void fence_proxy_async() { asm volatile("fence.proxy.async.global;" ::: "memory"); }
DEVINL void ldsm4t(uint32_t* r, uint32_t a) { asm volatile("ldmatrix.sync.aligned.m8n8.x4.trans.shared.b16 {%0,%1,%2,%3}, [%4];" : "=r"(r[0]), "=r"(r[1]), "=r"(r[2]), "=r"(r[3]) : "r"(a) : "memory"); }
DEVINL void stsm4(uint32_t a, uint32_t r0, uint32_t r1, uint32_t r2, uint32_t r3) { asm volatile("stmatrix.sync.aligned.m8n8.x4.shared.b16 [%0], {%1,%2,%3,%4};" ::"r"(a), "r"(r0), "r"(r1), "r"(r2), "r"(r3) : "memory"); }
DEVINL void mma16816(float* d, const uint32_t* a, uint32_t b0, uint32_t b1) {
  asm volatile("mma.sync.aligned.m16n8k16.row.col.f32.bf16.bf16.f32 {%0,%1,%2,%3}, {%4,%5,%6,%7}, {%8,%9}, {%0,%1,%2,%3};"
               : "+f"(d[0]), "+f"(d[1]), "+f"(d[2]), "+f"(d[3]) : "r"(a[0]), "r"(a[1]), "r"(a[2]), "r"(a[3]), "r"(b0), "r"(b1));
}
DEVINL void mma16816z(float* d, const uint32_t* a, uint32_t b0, uint32_t b1) {
  asm volatile("mma.sync.aligned.m16n8k16.row.col.f32.bf16.bf16.f32 {%0,%1,%2,%3}, {%4,%5,%6,%7}, {%8,%9}, {%10,%10,%10,%10};"
               : "=f"(d[0]), "=f"(d[1]), "=f"(d[2]), "=f"(d[3]) : "r"(a[0]), "r"(a[1]), "r"(a[2]), "r"(a[3]), "r"(b0), "r"(b1), "f"(0.f));
}
DEVINL void mma1688z(float* d, uint32_t a0, uint32_t a1, uint32_t b0) {
  asm volatile("mma.sync.aligned.m16n8k8.row.col.f32.bf16.bf16.f32 {%0,%1,%2,%3}, {%4,%5}, {%6}, {%7,%7,%7,%7};"
               : "=f"(d[0]), "=f"(d[1]), "=f"(d[2]), "=f"(d[3]) : "r"(a0), "r"(a1), "r"(b0), "f"(0.f));
}
DEVINL uint32_t movm(uint32_t a) { uint32_t r; asm volatile("movmatrix.sync.aligned.m8n8.trans.b16 %0, %1;" : "=r"(r) : "r"(a)); return r; }
DEVINL uint32_t pack_bf16(float lo, float hi) { uint32_t r; asm("cvt.rn.bf16x2.f32 %0, %1, %2;" : "=r"(r) : "f"(hi), "f"(lo)); return r; }
DEVINL uint32_t pack_f16(float lo, float hi) { uint32_t r; asm("cvt.rn.f16x2.f32 %0, %1, %2;" : "=r"(r) : "f"(hi), "f"(lo)); return r; }
DEVINL float bf_lo(uint32_t w) { return __uint_as_float(w << 16); }
DEVINL float bf_hi(uint32_t w) { return __uint_as_float(w & 0xffff0000u); }
DEVINL uint32_t hadd2bf(uint32_t a, uint32_t b) { uint32_t r; asm("add.rn.bf16x2 %0, %1, %2;" : "=r"(r) : "r"(a), "r"(b)); return r; }
DEVINL uint32_t hmax2bf(uint32_t a, uint32_t b) { uint32_t r; asm("max.bf16x2 %0, %1, %2;" : "=r"(r) : "r"(a), "r"(b)); return r; }
DEVINL uint32_t lds32(uint32_t a) { uint32_t v; asm volatile("ld.shared.u32 %0, [%1];" : "=r"(v) : "r"(a) : "memory"); return v; }
DEVINL uint2 lds64(uint32_t a) { uint2 v; asm volatile("ld.shared.v2.u32 {%0,%1}, [%2];" : "=r"(v.x), "=r"(v.y) : "r"(a) : "memory"); return v; }
DEVINL uint4 lds128(uint32_t a) { uint4 v; asm volatile("ld.shared.v4.u32 {%0,%1,%2,%3}, [%4];" : "=r"(v.x), "=r"(v.y), "=r"(v.z), "=r"(v.w) : "r"(a) : "memory"); return v; }
DEVINL void sts32(uint32_t a, uint32_t v) { asm volatile("st.shared.u32 [%0], %1;" ::"r"(a), "r"(v) : "memory"); }
DEVINL void sts64(uint32_t a, uint32_t x, uint32_t y) { asm volatile("st.shared.v2.u32 [%0], {%1,%2};" ::"r"(a), "r"(x), "r"(y) : "memory"); }
DEVINL void sts128(uint32_t a, uint4 v) { asm volatile("st.shared.v4.u32 [%0], {%1,%2,%3,%4};" ::"r"(a), "r"(v.x), "r"(v.y), "r"(v.z), "r"(v.w) : "memory"); }
DEVINL void stasync64(uint32_t a, uint32_t x, uint32_t y, uint32_t bar) { asm volatile("st.async.weak.shared::cluster.mbarrier::complete_tx::bytes.v2.b32 [%0], {%1,%2}, [%3];" ::"r"(a), "r"(x), "r"(y), "r"(bar) : "memory"); }
DEVINL uint4 ldg_rlx128(const void* p) { uint4 v; asm volatile("{.reg .b64 a,b; ld.relaxed.gpu.global.v2.b64 {a,b}, [%4]; mov.b64 {%0,%1}, a; mov.b64 {%2,%3}, b;}" : "=r"(v.x), "=r"(v.y), "=r"(v.z), "=r"(v.w) : "l"(p) : "memory"); return v; }
DEVINL uint2 ldg_rlx64(const void* p) { uint2 v; asm volatile("ld.relaxed.gpu.global.v2.u32 {%0,%1}, [%2];" : "=r"(v.x), "=r"(v.y) : "l"(p) : "memory"); return v; }
DEVINL void stg_rlx64(void* p, uint32_t x, uint32_t y) { asm volatile("{.reg .b64 a; mov.b64 a, {%1,%2}; st.relaxed.gpu.global.b64 [%0], a;}" ::"l"(p), "r"(x), "r"(y) : "memory"); }
DEVINL void stg_rlx128(void* p, uint32_t x, uint32_t y, uint32_t z, uint32_t w) { asm volatile("{.reg .b64 a,b; mov.b64 a, {%1,%2}; mov.b64 b, {%3,%4}; st.relaxed.gpu.global.v2.b64 [%0], {a,b};}" ::"l"(p), "r"(x), "r"(y), "r"(z), "r"(w) : "memory"); }
DEVINL void stg_rlx32(void* p, uint32_t x) { asm volatile("st.relaxed.gpu.global.u32 [%0], %1;" ::"l"(p), "r"(x) : "memory"); }
DEVINL uint4 ldg_cg128(const void* p) { uint4 v; asm volatile("ld.global.cg.v4.u32 {%0,%1,%2,%3}, [%4];" : "=r"(v.x), "=r"(v.y), "=r"(v.z), "=r"(v.w) : "l"(p) : "memory"); return v; }
DEVINL uint32_t ldg_cg32(const void* p) { uint32_t v; asm volatile("ld.global.cg.u32 %0, [%1];" : "=r"(v) : "l"(p) : "memory"); return v; }
DEVINL uint32_t ldg32_if(const void* p, int on) { uint32_t v; asm volatile("{.reg .pred q; setp.ne.s32 q, %2, 0; mov.u32 %0, 0; @q ld.global.cg.u32 %0, [%1];}" : "=r"(v) : "l"(p), "r"(on) : "memory"); return v; }
DEVINL uint4 ldg128_if(const void* p, int on) { uint4 v; asm volatile("{.reg .pred q; setp.ne.s32 q, %5, 0; mov.u32 %0, 0; mov.u32 %1, 0; mov.u32 %2, 0; mov.u32 %3, 0; @q ld.global.cg.v4.u32 {%0,%1,%2,%3}, [%4];}" : "=r"(v.x), "=r"(v.y), "=r"(v.z), "=r"(v.w) : "l"(p), "r"(on) : "memory"); return v; }
DEVINL uint4 ldg128_ef_if(const void* p, int on) { uint4 v; asm volatile("{.reg .pred q; setp.ne.s32 q, %5, 0; mov.u32 %0, 0; mov.u32 %1, 0; mov.u32 %2, 0; mov.u32 %3, 0; @q ld.global.L1::evict_first.v4.u32 {%0,%1,%2,%3}, [%4];}" : "=r"(v.x), "=r"(v.y), "=r"(v.z), "=r"(v.w) : "l"(p), "r"(on) : "memory"); return v; }
DEVINL void stg32_if(void* p, uint32_t v, int on) { asm volatile("{.reg .pred q; setp.ne.s32 q, %2, 0; @q st.global.u32 [%0], %1;}" ::"l"(p), "r"(v), "r"(on) : "memory"); }
DEVINL void stg128_if(void* p, uint4 v, int on) { asm volatile("{.reg .pred q; setp.ne.s32 q, %5, 0; @q st.global.v4.u32 [%0], {%1,%2,%3,%4};}" ::"l"(p), "r"(v.x), "r"(v.y), "r"(v.z), "r"(v.w), "r"(on) : "memory"); }
DEVINL uint4 ldg_na128(const void* p) { uint4 v; asm volatile("ld.global.L1::no_allocate.v4.u32 {%0,%1,%2,%3}, [%4];" : "=r"(v.x), "=r"(v.y), "=r"(v.z), "=r"(v.w) : "l"(p) : "memory"); return v; }
DEVINL uint4 ldg_ef128(const void* p) { uint4 v; asm volatile("ld.global.L1::evict_first.v4.u32 {%0,%1,%2,%3}, [%4];" : "=r"(v.x), "=r"(v.y), "=r"(v.z), "=r"(v.w) : "l"(p) : "memory"); return v; }
DEVINL uint4 ldg_ca128(const void* p) { uint4 v; asm volatile("ld.global.ca.v4.u32 {%0,%1,%2,%3}, [%4];" : "=r"(v.x), "=r"(v.y), "=r"(v.z), "=r"(v.w) : "l"(p) : "memory"); return v; }
DEVINL uint32_t ldg_ca32(const void* p) { uint32_t v; asm volatile("ld.global.ca.u32 %0, [%1];" : "=r"(v) : "l"(p) : "memory"); return v; }
DEVINL void flag_wait(const uint32_t* p, uint32_t want) {
  uint32_t v;
#pragma unroll 1
  for (int n = 0; n < POLL_LIMIT; n++) { asm volatile("ld.acquire.gpu.global.u32 %0, [%1];" : "=r"(v) : "l"(p) : "memory"); if (v >= want) break; __nanosleep(40); }
}
DEVINL void flag_wait_warp(const uint32_t* p, uint32_t want) {
  uint32_t v; int n = 0;
#pragma unroll 1
  do { asm volatile("ld.acquire.gpu.global.u32 %0, [%1];" : "=r"(v) : "l"(p) : "memory"); } while (__any_sync(~0u, v < want && ++n < POLL_LIMIT));
}
DEVINL void flag_add(uint32_t* p) { asm volatile("red.release.gpu.global.add.u32 [%0], 1;" ::"l"(p) : "memory"); }
DEVINL void flag_set(uint32_t* p, uint32_t v) { asm volatile("fence.acq_rel.gpu; st.relaxed.gpu.global.u32 [%0], %1;" ::"l"(p), "r"(v) : "memory"); }
DEVINL uint32_t ldg_rlx32(const void* p) { uint32_t v; asm volatile("ld.relaxed.gpu.global.u32 %0, [%1];" : "=r"(v) : "l"(p) : "memory"); return v; }
DEVINL float ex2(float x) { float y; asm("ex2.approx.ftz.f32 %0, %1;" : "=f"(y) : "f"(x)); return y; }
DEVINL float rcp(float x) { float y; asm("rcp.approx.ftz.f32 %0, %1;" : "=f"(y) : "f"(x)); return y; }
DEVINL uint32_t opaque(uint32_t x) { return __shfl_sync(~0u, x, threadIdx.x & 31); }
DEVINL uint32_t launder(uint32_t x) { asm volatile("" : "+r"(x)); return x; }
DEVINL void pdl_wait() { asm volatile("griddepcontrol.wait;" ::: "memory"); }
DEVINL void pdl_launch() { asm volatile("griddepcontrol.launch_dependents;" ::: "memory"); }
#define LOGS(cta, i)
#define LOGK(k, i)
#define LOG(cta, i)
#define LOGV(cta, i, v)
#define EV(i, v)
constexpr float SM_SCALE = 0.08838834764831845f * 1.4426950408889634f;

DEVINL void unpack8(uint4 v, float* f) { f[0] = bf_lo(v.x); f[1] = bf_hi(v.x); f[2] = bf_lo(v.y); f[3] = bf_hi(v.y); f[4] = bf_lo(v.z); f[5] = bf_hi(v.z); f[6] = bf_lo(v.w); f[7] = bf_hi(v.w); }
DEVINL uint4 pack8(const float* f) { return make_uint4(pack_bf16(f[0], f[1]), pack_bf16(f[2], f[3]), pack_bf16(f[4], f[5]), pack_bf16(f[6], f[7])); }
DEVINL void ln_row(float* f) {
  float s = 0.f;
#pragma unroll
  for (int i = 0; i < 40; i++) s += f[i];
#pragma unroll
  for (int o = 1; o < 16; o <<= 1) s += __shfl_xor_sync(~0u, s, o);
  const float mean = s * (1.f / 640.f); float q = 0.f;
#pragma unroll
  for (int i = 0; i < 40; i++) { f[i] -= mean; q = fmaf(f[i], f[i], q); }
#pragma unroll
  for (int o = 1; o < 16; o <<= 1) q += __shfl_xor_sync(~0u, q, o);
  const float rs = rsqrtf(q * (1.f / 640.f) + 1e-5f);
#pragma unroll
  for (int i = 0; i < 40; i++) f[i] *= rs;
}

#define WAH 2
struct Wts { const char* w[4]; };
template <int CH> DEVINL void weight_warm(const Wts& w, uint32_t buf, uint32_t bar, uint32_t stop) {
  uint32_t smid; asm volatile("mov.u32 %0, %%smid;" : "=r"(smid));
  const uint32_t c = g_role[smid & 255];
  if (c >= 128) return;
  mbar_init(bar, 1); asm volatile("fence.mbarrier_init.release.cluster; fence.proxy.async.shared::cta;" ::: "memory");
  constexpr int N = 81920 / CH;
#pragma unroll 1
  for (int i = 0; i < (c < 64 ? 4 : 2) * N; i++) {
    uint32_t v; asm volatile("ld.volatile.shared.u32 %0, [%1];" : "=r"(v) : "r"(stop) : "memory");
    if (v) break;
    mbar_arrive_tx(bar, CH);
    auto src = [&](int i) { return w.w[c < 64 ? i / N : i / N * 2] + (c & 63) * 81920 + (i % N) * CH; };
    bulk_g2s(buf, src(i), CH, bar);
    if (WAH && i + WAH < (c < 64 ? 4 : 2) * N) l2_prefetch(src(i + WAH), CH);
    mbar_wait(bar, i & 1);
  }
}
struct Maps { CUtensorMap q, k, v, o, o32, x, ao; };
struct ArgsA {
  const bf16* x; const bf16* mem0; char* comm; uint32_t* flags; const bf16* wr; const bf16* wi; const char* wq; const char* wo;
  int layer; int ta[4], tb[4], tc[2];
};

#define VP 4
#define HELD 0x2557
#define PRE 4
#define VPRE0 3
#define VPRE1 5
#define R0 2
#define TRK 30
#define TEXP 200
#define TRD 0
#define TKV 300
#define KB1 5
#define W2D 0
#define WD 4
#define VPW 1
#define P1F 3
#define W0D 0
#define XD 0
#define TSF 2
#define XP 0
#define PW 1
#define VXE 0
#define LA 0
#define KB2 10
#define KB3 13
#define TSE 7
#define PRP 0
#define R1 2
#define OBF 1
#define LS0 0x002220222200ull
#define LS1 0x00220000ull
#define RRP -1
#define RCP 6
#define PS0 32
#define PS1 4
#define DEP0 0
#define DEP1 1
#define PIN 1
#define F0 3
#define W1N 12
#define XLATE 0
#define XST 0
#define XF 5
#define W1D 0
constexpr int C_WV = 0;
constexpr int C_WO = 81920;
constexpr int C_KV = 163840;
constexpr int C_M  = C_KV + 24576;
constexpr int C_QK = C_M + 10240;
constexpr int C_VP = C_QK + 4096;
constexpr int C_S  = C_VP + 4096;
constexpr int C_O  = C_S + 2048;
constexpr int C_R  = C_O + 2048;
constexpr int C_T  = C_R + 256;
constexpr int S_BAR = 229376;
constexpr int S_END = S_BAR + 256;
enum { BAR_QK = 2, BAR_O = 3, BAR_H = 4, BAR_X = 5, BAR_W = 7  , BAR_E = 9, BAR_M1 = 10  , BAR_M3 = 12, BAR_M2 = 13   };
constexpr int B_W = 0, B_S = 8, B_W2 = 16, B_KV = 24, B_WV = 40, B_WO = 48, B_M0 = 56;
constexpr int G2_OFF = 0x130000, TS_OFF = 0x11000;

#define FEN() asm volatile("pmevent 0;" ::: "memory")
#define SCHED(x, c) asm volatile("{.reg .pred p; setp.eq.u32 p, %0, %1; @p exit;}" ::"r"(x), "r"(0x7fff0001u + 2 * (c)) : "memory")
DEVINL uint32_t g1page(uint32_t L) { L = ((L & 7) | ((L & 24) << 2)) << 1; return (L | (__popc(L & 0xb2) & 1)) << 12; }
DEVINL void spin_until(uint32_t t) {
  asm volatile("{.reg .pred p; .reg .b32 c; .reg .b64 w;\nS0: mov.u64 w, %%clock64; cvt.u32.u64 c, w; sub.u32 c, %0, c; setp.lt.u32 p, c, 16384; @p bra.uni S0;}" ::"r"(t) : "memory");
}
DEVINL uint32_t wait_until(uint32_t t, uint32_t z) { uint32_t r;
  asm volatile("{.reg .pred p; .reg .b32 c,x,y; .reg .b64 w;\nT0: .branchtargets L0, L1, L2, L3, L4, L5, L6, L7, L8, L9, L10;\n mov.u32 x, %2;\n"
               "mov.u64 w, %%clock64; cvt.u32.u64 c, w; sub.u32 c, %1, c; setp.ge.u32 p, c, 16384; @p bra.uni L0;\n"
               "S0: mov.u64 w, %%clock64; cvt.u32.u64 c, w; sub.u32 c, %1, c; setp.gt.s32 p, c, 40; @p bra.uni S0;\n"
               "mad.lo.s32 c, c, 37, 1200; shr.s32 c, c, 8; max.s32 c, c, 0;\nbrx.idx.uni c, T0;\n"
               "L10: mul.lo.u32 x, x, x; L9: mul.lo.u32 x, x, x; L8: mul.lo.u32 x, x, x; L7: mul.lo.u32 x, x, x; L6: mul.lo.u32 x, x, x; L5: mul.lo.u32 x, x, x; L4: mul.lo.u32 x, x, x; L3: mul.lo.u32 x, x, x; L2: mul.lo.u32 x, x, x; L1: mul.lo.u32 x, x, x; L0: mov.u32 %0, x;}" : "=r"(r) : "r"(t), "r"(z) : "memory"); return r;
}
DEVINL void gtime(uint32_t& G16, uint32_t& C) {
  asm volatile("{.reg .b64 w; .reg .b32 g,g0,a;\n mov.u64 w, %%clock64; cvt.u32.u64 %1, w; mov.u64 w, %%globaltimer; cvt.u32.u64 g0, w; mul.lo.u32 a, g0, -11;\n"
               "mov.u64 w, %%globaltimer; cvt.u32.u64 g, w; add.u32 a, a, g; mov.u64 w, %%globaltimer; cvt.u32.u64 g, w; add.u32 a, a, g; mov.u64 w, %%globaltimer; cvt.u32.u64 g, w; add.u32 a, a, g; mov.u64 w, %%globaltimer; cvt.u32.u64 g, w; add.u32 a, a, g; mov.u64 w, %%globaltimer; cvt.u32.u64 g, w; add.u32 a, a, g; mov.u64 w, %%globaltimer; cvt.u32.u64 g, w; add.u32 a, a, g; mov.u64 w, %%globaltimer; cvt.u32.u64 g, w; add.u32 a, a, g; mov.u64 w, %%globaltimer; cvt.u32.u64 g, w; add.u32 a, a, g; mov.u64 w, %%globaltimer; cvt.u32.u64 g, w; add.u32 a, a, g; mov.u64 w, %%globaltimer; cvt.u32.u64 g, w; add.u32 a, a, g; mov.u64 w, %%globaltimer; cvt.u32.u64 g, w; add.u32 a, a, g; \n mul.lo.u32 a, a, 341; shr.u32 a, a, 8; mad.lo.u32 %0, g0, 16, a;}" : "=r"(G16), "=r"(C)::"memory");
}
DEVINL uint32_t pack_tag(float lo, float hi, uint32_t tg) {
  const uint32_t w = pack_bf16(lo, __uint_as_float(tg | 0x3F800000u)), a = __float_as_uint(hi) + (tg ^ 0x10000u); uint32_t r;
  asm("lop3.b32 %0, %1, %2, 0xFFFE0000, 0xE4;" : "=r"(r) : "r"(a), "r"(w)); return r;
}
DEVINL float ex2v(float x) { float y; asm volatile("ex2.approx.ftz.f32 %0, %1;" : "=f"(y) : "f"(x)); return y; }
DEVINL void load_kv(uint32_t sb, int h, int j, int s) {
  asm volatile("{.reg .pred p; elect.sync _|p, 0xffffffff;\n fence.proxy.async.global;\n @p mbarrier.arrive.expect_tx.shared::cta.b64 _, [%2], 12288;\n"
               " @p cp.async.bulk.shared::cluster.global.mbarrier::complete_tx::bytes [%0], [%1], 12288, [%2];}"
               ::"r"(sb + C_KV + (s & 1) * 12288), "l"(g_kv + (size_t)(s * 32 + h) * 16384 + j * 4096), "r"(sb + S_BAR + B_KV + (s & 1) * 8) : "memory");
}

constexpr __host__ __device__ int digsum(unsigned long long v, int n) { int r = 0; for (int i = 0; i < n; i++) r += (v >> (4 * i)) & 15; return r; }
template <int KH>
DEVINL void chain_mma(uint32_t sb0, const ArgsA& args) {
  const int lane = threadIdx.x & 31, mg = (threadIdx.x >> 5) & 3, mi = lane >> 3, r = lane & 7;
  const uint32_t aW = opaque(sb0 + (uint32_t)(((mi >> 1) * 8 + r) * 128 + (((mg + 4 * (mi & 1)) ^ r) << 4)));
  const uint32_t aL = opaque(sb0 + lane * 16);
  const uint32_t aLm = opaque(sb0 + mg * 512 + lane * 16);
#define sb (launder(aL) & ~511u)
  constexpr int OV = C_WV + KH * 40960, OM = C_M + KH * 5120, NF = KH ? 16 : 24;
  auto owo = [](int f) { return C_WO + (KH + 2 * (f >> 3)) * 16384 + (f & 7) * 2048; };
  auto held = [](int k) { return (HELD >> k) & 1; };
  auto rank = [](int k) { return __popc(HELD & ((1 << k) - 1)); };
  uint32_t wq[20][4], wk[20][4];
  mbar_wait(sb + S_BAR + B_W, 0);
#pragma unroll
  for (int k = 0; k < 12; k++) { ldsm4t(wq[k], aW + OV + k * 2048); ldsm4t(wk[k], aW + C_WO + KH * 40960 + k * 2048); }
  bar_arrive(BAR_H, 288);
  mbar_wait(sb + S_BAR + B_W2, 0);
#pragma unroll
  for (int k = 12; k < 20; k++) { ldsm4t(wq[k], aW + OV + k * 2048); ldsm4t(wk[k], aW + C_WO + KH * 40960 + k * 2048); }
  bar_sync(BAR_E, 384);
  mbar_wait(sb + S_BAR + B_WV, 0);
  uint32_t sx = args.layer << 16;
#pragma unroll 1
  while (true) {
    uint32_t v[20][4], b[10][4];
    {
      const uint32_t o = launder(aLm) - sb, on = (sx >> 16) != (uint32_t)args.layer;
      const char* p = args.comm + lds32(sb + C_T + KH * 1024 + 4 + (o >> 1));
      constexpr int NB = KH ? VPRE1 : VPRE0;
      const uint32_t zero = (uint32_t)(uintptr_t)p & 1, tt = lds32(sb + C_R + 48) + args.tb[0]; uint32_t av = aW;
#pragma unroll
      for (int k = 0; k < 20; k++) if (held(k) && rank(k) < NB) { ldsm4t(v[k], av + OV + k * 2048); if (rank(k) % VPW == VPW - 1 && rank(k) < NB - 1) av = aW + (v[k][0] & zero); }
      p += wait_until(tt, zero);
      uint4 a = ldg_rlx128(p);
      __syncwarp();
#pragma unroll
      for (int k = 0; k < 20; k++) if (held(k) && rank(k) >= NB) { ldsm4t(v[k], av + OV + k * 2048); if ((rank(k) - NB) % VPW == VPW - 1) av = aW + (v[k][0] & zero); }
      SCHED(o ^ on, 29);
      if (on) sts128(aLm + OM, a);
      if (__builtin_expect(__any_sync(~0u, on && (((a.x ^ sx) | (a.z ^ sx)) & 0x10000u)), 0)) {
        int lim = 0;
        do a = ldg_rlx128(p); while (__any_sync(~0u, (((a.x ^ sx) | (a.z ^ sx)) & 0x10000u) && ++lim < POLL_LIMIT));
        sts128(aLm + OM, a);
      }
      bar_sync(BAR_W + KH, 128);
      ldsm4t(b[0], aL + OM); ldsm4t(b[1], aL + OM + 512);
    }
    float cq[4], ck[4], cv[4];
    static_for<0, 20>([&](auto I) {
      constexpr int k = I.value, p = k >> 1;
      const uint32_t b0 = b[p][(k & 1) * 2], b1 = b[p][(k & 1) * 2 + 1];
      if (k == 0) { mma16816z(cv, v[0], b0, b1); mma16816z(cq, wq[k], b0, b1); mma16816z(ck, wk[k], b0, b1); }
      else { if (k < 20 - VP) mma16816(cv, v[k], b0, b1); mma16816(cq, wq[k], b0, b1); mma16816(ck, wk[k], b0, b1); }
      if (k == KB1) bar_sync(BAR_M1 + KH, 160);
      if (k == KB2) bar_sync(BAR_M2 + KH, 160);
      if (k == KB3) bar_sync(BAR_M3, 320);
      static_for<2, 10>([&](auto J) {
        constexpr int q = J.value, st = q < 4 ? 0 : q < 6 ? KB1 : q < 8 ? KB2 : KB3;
        if constexpr (k == (2 * q - 3 > st ? 2 * q - 3 : st)) ldsm4t(b[q], aL + OM + q * 512); });
      if constexpr (k + 3 < 20 - VP && !((HELD >> (k + 3)) & 1)) ldsm4t(v[k + 3], aW + OV + (k + 3) * 2048);
      if (k >= 20 - VP && k < 20 - VP + PRE && !held(k)) ldsm4t(v[k], aW + OV + k * 2048);
      if (P1F && (k & 1) && k >= P1F && k < 19) FEN();
    });
    stsm4(aLm + C_QK + KH * 2048, pack_bf16(cq[0], cq[1]), pack_bf16(cq[2], cq[3]), pack_bf16(ck[0], ck[1]), pack_bf16(ck[2], ck[3]));
    bar_arrive(BAR_QK, 384);
    FEN();
    const uint32_t l8 = (launder(aL) & 511) >> 1, px = lds32(sb + C_R + 80);
#pragma unroll
    for (int k = 20 - VP + PRE; k < 20; k++) if (!held(k)) ldsm4t(v[k], aW + OV + k * 2048);
#pragma unroll
    for (int k = 20 - VP; k < 20; k++) {
      const int p = k >> 1, q = k - 20 + VP; const uint32_t b0 = b[p][(k & 1) * 2], b1 = b[p][(k & 1) * 2 + 1];
      if (q % 3 == 0) mma16816(cv, v[k], b0, b1); else if (q == 1) mma16816z(cq, v[k], b0, b1); else if (q == 2) mma16816z(ck, v[k], b0, b1);
      else if (q % 3 == 1) mma16816(cq, v[k], b0, b1); else mma16816(ck, v[k], b0, b1);
    }
    if (VP >= 3) {
#pragma unroll
      for (int i = 0; i < 4; i++) cv[i] += cq[i] + ck[i];
    }
    { const uint32_t vx = pack_bf16(cv[0], cv[1]), vy = pack_bf16(cv[2], cv[3]);
      const uint32_t av = aLm - l8 + C_VP + KH * 256;
      stasync64(av + 2048 + px, vx, vy, sb + S_BAR + B_S + px);
      sts64(av, vx, vy);
      __syncwarp();
      if (l8 == 0) mbar_arrive(sb + S_BAR + B_S); }
    sx += 0x10000;
    if ((sx >> 16) == args.layer + 64u) break;
    uint32_t w[NF][4];
    {
      const uint32_t zero = px & 1; uint32_t a = aW;
      const bool tsw = KH == 1 && __any_sync(~0u, launder(aLm) == aL); uint2 ts = make_uint2(0, 0); uint4 cal = make_uint4(0, 0, 0, 0);
      if ((sx >> 16) == args.layer + 1u) mbar_wait(sb + S_BAR + B_WO, 0);
#pragma unroll
      for (int f = 0; f < 8 + XP; f++) { ldsm4t(w[f], a + owo(f));
        if (KH == 1 && f == TSF && tsw) { ts = ldg_rlx64(args.comm + TS_OFF + l8); cal = lds128(sb + C_R + 64); }
      if (KH == 1 && f == TSE && tsw) {
        const uint32_t d0 = ts.x - cal.x, d1 = ts.y - cal.x;
        const int dt = (int)__reduce_max_sync(~0u, max(d0 < 32768u ? d0 : 0u, d1 < 32768u ? d1 : 0u));
        sts32(sb + C_R + 48, cal.y + min((dt * cal.z) >> 16, 8192u));
      }
        uint32_t d = w[f][0] & zero;
#pragma unroll
        for (int q = 0; q < (f == 0 ? TRD : 0); q++) d *= d;
        if (f % PW == PW - 1) a = aW + d; }
    }
    const uint32_t go = lds32(sb + C_T + KH * 1024 + ((launder(aLm) - sb) >> 1)), ar = ((launder(aL) >> 1) & 24) + sb + (go & 1);
    SCHED(ar, 30);
    bar_sync(BAR_O, 384);
    uint32_t ob[16];
#pragma unroll
    for (int p = 0; p < 4; p++) ldsm4t(ob + 4 * p, aL + C_O + p * 512);
    uint2 rr;
    if (RRP < 0) rr = lds64(ar + C_R + 128);
    if (OBF) FEN();
    float r0, r1; uint32_t y0, y1;
    static_for<0, NF>([&](auto I) {
      constexpr int f = I.value, k = f & 7; const uint32_t* A = w[f];
      if (k == 0) mma16816z(cq, A, ob[0], ob[1]); else if (k == 1) mma16816z(ck, A, ob[2], ob[3]);
      else if (k & 1) mma16816(ck, A, ob[2 * k], ob[2 * k + 1]); else mma16816(cq, A, ob[2 * k], ob[2 * k + 1]);
      if (f == RRP) rr = lds64(ar + C_R + 128);
      if (f == RCP) { r0 = rcp(__uint_as_float(rr.x)); r1 = rcp(__uint_as_float(rr.y)); }
      if constexpr (f & 1) {
        constexpr unsigned long long LS = KH ? LS1 : LS0; constexpr int pr = f >> 1, n = (LS >> (4 * pr)) & 15;
        constexpr int PS = KH ? PS1 : PS0, q0 = 8 + XP + digsum(LS, pr) + digsum(PS, f >> 3), m = (PS >> (4 * (f >> 3))) & 15;
        if constexpr (n > 0) { const uint32_t a = (f < 8 && !DEP0) || !DEP1 ? aW : aW + ((f < 8 ? ob[2 * k] : A[0]) & go & 1);
#pragma unroll
          for (int q = q0; q < q0 + n; q++) ldsm4t(w[q], a + owo(q)); }
        if constexpr (k == 7) { if (n > 0) FEN();
          y0 = pack_tag((cq[0] + ck[0]) * r0, (cq[1] + ck[1]) * r1, sx & 0x10000u); y1 = pack_bf16((cq[2] + ck[2]) * r0, (cq[3] + ck[3]) * r1);
          stg_rlx64(args.comm + go + (f < 8 ? 0 : f < 16 ? 0x30000 : 0x100000), y0, y1);
          if constexpr (m > 0) { FEN(); uint32_t a = aW;
            if constexpr (KH == 1 && W1N > 0) { uint32_t d = y1 & go & 1;
#pragma unroll
              for (int q = 0; q < W1N; q++) d *= d;
              a += d; }
#pragma unroll
            for (int q = q0 + n; q < q0 + n + m; q++) ldsm4t(w[q], a + owo(q)); } }
        if (f >= 8 && k == 3 && PIN) SCHED(y0 & y1 & go, 40 + f);
        else if (f >= F0 || n > 0) FEN();
      }
    });
  }
}

#undef sb
DEVINL void chain_helper(uint32_t sb, uint32_t px, int h, int j, const ArgsA& args, const Maps& tm) {
  const int c = 2 * h + j;
  const uint32_t bW = sb + S_BAR + B_W, bS = sb + S_BAR + B_S, bKV = sb + S_BAR + B_KV;
  const uint32_t lane0 = opaque(threadIdx.x & 31);
  const uint32_t warp = __reduce_max_sync(~0u, (threadIdx.x >> 5) & 3);
  { const int tid = threadIdx.x - 256;
    auto boxes = [&](int n0, int n1) {
#pragma unroll 1
      for (int n = n0; n < n1; n++) {
        const int m = n < 20 ? n & 1 : n < 26 || (n >= 32 && n < 36) ? 2 : 3, q = n < 20 ? n >> 1 : n < 26 ? n - 20 : n < 36 ? n - 26 : n - 30, i = (q & 1) * 5 + (q >> 1);
        w_tma(sb + (m & 1) * C_WO + i * 8192, &tm.q + m, m < 3 ? h * 128 + j * 64 : j * 320 + (i >> 1) * 64, m < 3 ? i * 64 : h * 128 + ((i & 1) ^ j) * 64, bW + (m < 2 ? (n < 12 ? 0 : B_W2) : m == 2 ? B_WV : B_WO));
        if (n == 31) bar_sync(BAR_E, 384);
      } };
    if (warp == 0) { w_expect(bW + B_M0, 10240); w_bulk(sb + C_T + 4096, args.mem0, 10240, bW + B_M0); w_expect(bW, 98304); w_expect(bW + B_W2, 65536); w_expect(bW + B_WV, 81920); w_expect(bW + B_WO, 81920); }
#pragma unroll 1
    for (int ps = 0;; ps++) {
    if (warp == 0) boxes(ps * 20, ps * 20 + 20);
    if (ps) break;
    uint32_t G0, C0; gtime(G0, C0);
    if (warp == 0) sts64(sb + C_R + 96, G0, C0);
    { const uint32_t g = lane0 >> 2, t = lane0 & 3;
      sts128(sb + C_T + 2048 + tid * 16, make_uint4(g1page(c >> 1) + (c & 1) * 2048 + (warp == 0 ? 0 : warp == 1 ? 0x30000 : 0x100000) + ((g >> 2) * 4 + t) * 64 + (g & 3) * 16,
                                                    g1page(((t >> 1) + (g >> 2) * 2) * 4 + warp) + G2_OFF + (c >> 4) * 1024 + (t & 1) * 512 + (c & 15) * 32 + (g & 3) * 8,
                                                    g1page((h & 3) * 4 + (warp == 2 ? 2 : 1)) + G2_OFF + (warp == 1 ? 1024 : warp == 3 ? 2048 : 0) + lane0 * 16, (g & 1) ? 0x3F800000u : 0x00003F80u)); }
    sts32(sb + C_R + 80, px); sts32(sb + C_R + 48, C0 - 65536);
#pragma unroll
    for (int kh = 0; kh < 2; kh++)
      sts64(sb + C_T + kh * 1024 + tid * 8, g1page(j * 16 + kh * 8 + (tid >> 4)) + (tid & 8) * 256 + h * 64 + (tid & 7) * 8, g1page((h & 3) * 4) + G2_OFF + kh * 2048 + tid * 16);
    if (warp == 0) bar_sync(BAR_H, 288);
    else {
      mbar_wait(bW + B_M0, 0);
#pragma unroll 1
      for (int q = warp - 1; q < 20; q += 3) { uint32_t v[4]; ldsm4t(v, sb + C_T + 4096 + (lane0 & 7) * 1280 + (q * 4 + (lane0 >> 3)) * 16); stsm4(sb + C_M + q * 512 + lane0 * 16, v[0], v[1], v[2], v[3]); }
      bar_sync(BAR_E, 384);
    }
    }
    if (warp == 3) {
      if (tid == 96) LOG(c, 250);
      flag_wait_warp(args.flags + F_KV + h * 32, 2);
      load_kv(sb, h, j, 0); load_kv(sb, h, j, 1); if (tid == 96) LOG(c, 251);
    }
  }
  auto calib = [&]() { uint32_t G, C; gtime(G, C);
    const uint2 o = lds64(sb + C_R + 96); const float rt = (float)(C - o.y) * rcp((float)(G - o.x));
    sts128(sb + C_R + 32, make_uint4(G, C, __float2uint_rn(rt * 65536.f) & 0xffffu, __float_as_uint(rcp(rt)))); __syncwarp(); };
  auto export_ld = [&](uint32_t (*e)[4], uint32_t lane) {
    uint32_t k1[2][4]; uint2 a[4], b[4];
    const uint32_t ak = sb + C_QK + 256 + (lane >> 4) * 512 + (lane & 15) * 16, av = sb + C_VP + (lane >> 3) * 512 + (lane & 7) * 8, tg = (args.layer ^ 1) << 16;
#pragma unroll
    for (int i = 0; i < 2; i++) { ldsm4t(e[i], ak + i * 1024); ldsm4t(k1[i], ak + i * 1024 + 2048); }
#pragma unroll
    for (int i = 0; i < 4; i++) { a[i] = lds64(av + i * 64); b[i] = lds64(av + i * 64 + 256); }
#pragma unroll
    for (int i = 0; i < 4; i++) { e[0][i] = hadd2bf(e[0][i], k1[0][i]); e[1][i] = hadd2bf(e[1][i], k1[1][i]); e[2][i] = hadd2bf(a[i].x, b[i].x); e[3][i] = hadd2bf(a[i].y, b[i].y); }
#pragma unroll
    for (int i = 0; i < 8; i++) e[i >> 1][(i & 1) * 2] = (e[i >> 1][(i & 1) * 2] & ~0x10000u) | tg;
  };
  auto export_st = [&](const uint32_t (*e)[4], int s, uint32_t lane) {
    char* dst = g_kvm + ((s * 32 + h) * 4096 + j * 1024 + lane * 16);
#pragma unroll
    for (int i = 0; i < 4; i++) stg_rlx128(dst + (i >> 1) * 2048 + (i & 1) * 512, e[i][0], e[i][1], e[i][2], e[i][3]);
    stg_rlx32(args.flags + F_KM + h * 32 + j, s + 1);
  };
  auto staged = [&]() { if (warp == 2) bar_arrive(BAR_M3, 320); else if (warp == 1) { bar_arrive(BAR_M2, 160); bar_arrive(BAR_M2 + 1, 160); } else bar_arrive(BAR_M1 + (warp >> 1), 160); };
  if (warp == 0) calib();
  staged();
  int kv_ok = 1;
  uint32_t vx[4][4];
  auto load_vx = [&](int s, uint32_t lane) {
    const uint32_t aVx = sb + C_KV + (s & 1) * 12288 + 4096 + (warp >> 1) * (j ? -4096 : 4096) + (warp & 1) * 1024 + lane * 16, zero = lane >> 5;
#pragma unroll
    for (int i = 0; i < 4; i++) { const uint4 q = lds128(aVx + (i & 1) * 2048 + (i >> 1) * 512); vx[i][0] = q.x ^ zero; vx[i][1] = q.z ^ zero; vx[i][2] = q.y ^ zero; vx[i][3] = q.w ^ zero; }
  };
  uint2 kb[4];
  auto prep = [&](int s, uint32_t lane) {
    if (s < 63) mbar_wait(bKV + (s & 1) * 8, (s >> 1) & 1);
    const uint32_t aK = sb + C_KV + (s & 1) * 12288 + j * 8192 + warp * 1024 + lane * 16;
#pragma unroll
    for (int i = 0; i < 4; i++) kb[i] = lds64(aK + ((warp ^ i) >> 1) * 512 + ((warp ^ i) & 1) * 8);
    if (VXE == 1) load_vx(s, lane);
    asm volatile("{.reg .pred p; setp.eq.u32 p, %2, 32; @p mbarrier.arrive.expect_tx.shared::cta.b64 _, [%0], %1;}" ::"r"(bS), "r"(s < 63 ? 3072 : 2048), "r"(warp * 32 + lane) : "memory");
  };
  prep(0, lane0);
#pragma unroll 1
  for (int s = 0;; s++) {
    const uint32_t ph = s & 1;
    const uint32_t lane = __shfl_sync(~0u, lane0, lane0);
    const uint32_t mi = lane >> 3, r = lane & 7;
    const uint32_t aQ = sb + C_QK + (mi & 1) * 2048 + ((mi >> 1) * 8 + r) * 16;
    const uint32_t aKm = sb + C_QK + 256 + warp * 512 + (lane >> 4) * 2048 + (lane & 15) * 16;
    const uint32_t aH = sb + C_S + warp * 256 + lane * 8, aR = aH + 1024 + px;
    SCHED(aQ ^ aR ^ aKm, 60);
    if (warp == 0) {
      const uint4 cal = lds128(sb + C_R + 32);
      bar_sync(BAR_M3, 320);
      sts32(sb + C_R + 52, 0);
      const uint32_t E = clk(), e16 = cal.x + (uint32_t)__float2int_rn((float)(int)(E - cal.y) * __uint_as_float(cal.w));
      stg_rlx32(args.comm + TS_OFF + c * 4, e16); sts128(sb + C_R + 64, make_uint4(e16, E, cal.z, 0));
    }
    if (s == 63) { bar_sync(BAR_QK, 384); mbar_wait(bS, 1); if (warp == 3) { uint32_t e[4][4]; export_ld(e, lane); export_st(e, 63, lane); } break; }
    {
      uint32_t qa[4][4], km[4]; float s0[4], s1[4], s2[4];
      bar_sync(BAR_QK, 384);
      ldsm4t(qa[0], aQ + warp * 512); ldsm4t(km, aKm); ldsm4t(qa[1], aQ + (warp ^ 1) * 512); ldsm4t(qa[2], aQ + (warp ^ 2) * 512); ldsm4t(qa[3], aQ + (warp ^ 3) * 512);
      mma16816z(s0, qa[0], kb[0].x, kb[0].y); mma16816z(s2, qa[0], km[0], km[1]); mma16816z(s1, qa[1], kb[1].x, kb[1].y);
      FEN();
      mma16816(s2, qa[0], km[2], km[3]); mma16816(s0, qa[2], kb[2].x, kb[2].y); mma16816(s1, qa[3], kb[3].x, kb[3].y);
      const uint32_t w0 = pack_bf16((s0[0] + s0[2]) + (s1[0] + s1[2]), (s0[1] + s0[3]) + (s1[1] + s1[3]));
      const uint32_t w1 = pack_bf16(s2[0] + s2[2], s2[1] + s2[3]);
      stasync64(aR, w0, w1, bS + px);
      sts64(aH, w0, w1);
    }
    {
      uint32_t sl[5];
      const uint32_t a8 = sb + lane * 8, av = a8 + C_VP + warp * 1024;
      const uint32_t aO = sb + C_O + ((warp >> 1) * 64 + (warp & 1) * 16 + (mi & 1) * 32 + (mi >> 1) * 8 + r) * 16, aU = sb + C_R + (lane & 28);
      uint4 vq[4];
      if (VXE == 2) { const uint32_t aVx = sb + C_KV + ph * 12288 + 4096 + (warp >> 1) * (j ? -4096 : 4096) + (warp & 1) * 1024 + lane * 16;
#pragma unroll
        for (int i = 0; i < 4; i++) vq[i] = lds128(aVx + (i & 1) * 2048 + (i >> 1) * 512); }
      bar_sync(BAR_X, 128);
      { uint2 t[4];
#pragma unroll
        for (int u = 0; u < 4; u++) t[u] = lds64(a8 + C_S + u * 256);
        if (VXE == 0) load_vx(s, lane);
        if (VXE == 2) { FEN(); const uint32_t zero = lane >> 5;
#pragma unroll
          for (int i = 0; i < 4; i++) { vx[i][0] = vq[i].x ^ zero; vx[i][1] = vq[i].z ^ zero; vx[i][2] = vq[i].y ^ zero; vx[i][3] = vq[i].w ^ zero; } }
#pragma unroll
        for (int u = 0; u < 4; u++) sl[u] = t[u].x;
        sl[4] = pack_bf16((bf_lo(t[0].y) + bf_lo(t[1].y)) + (bf_lo(t[2].y) + bf_lo(t[3].y)), (bf_hi(t[0].y) + bf_hi(t[1].y)) + (bf_hi(t[2].y) + bf_hi(t[3].y))); }
      mbar_wait(bS, ph);
      uint32_t vm[2][4];
      { uint2 t[4];
#pragma unroll
        for (int u = 0; u < 4; u++) t[u] = lds64(a8 + C_S + 1024 + u * 256);
#pragma unroll
        for (int u = 0; u < 4; u++) sl[u] = hadd2bf(sl[u], t[u].x);
        sl[4] = hadd2bf(hadd2bf(hadd2bf(sl[4], t[0].y), t[1].y), hadd2bf(t[2].y, t[3].y)); }
      uint32_t m2 = hmax2bf(hmax2bf(hmax2bf(sl[0], sl[1]), hmax2bf(sl[2], sl[3])), sl[4]);
      const uint32_t x1 = __shfl_xor_sync(~0u, m2, 1), x2 = __shfl_xor_sync(~0u, m2, 2), x3 = __shfl_xor_sync(~0u, m2, 3);
#pragma unroll
      for (int i = 0; i < 4; i++) { const uint2 q = lds64(av + i * 256); vm[i >> 1][(i & 1) * 2] = q.x; vm[i >> 1][(i & 1) * 2 + 1] = q.y; }
      float sv[10];
#pragma unroll
      for (int u = 0; u < 5; u++) { sv[2 * u] = bf_lo(sl[u]) * SM_SCALE; sv[2 * u + 1] = bf_hi(sl[u]) * SM_SCALE; }
      FEN();
      m2 = hmax2bf(hmax2bf(m2, x1), hmax2bf(x2, x3));
      const float mx = fmaxf(bf_lo(m2), bf_hi(m2));
      float o0[4], o1[4];
#pragma unroll
      for (int i = 0; i < 10; i++) sv[i] = fmaf(mx, -SM_SCALE, sv[i]);
      sv[8] = ex2v(sv[8]); sv[9] = ex2v(sv[9]);
#pragma unroll
      for (int i = 0; i < 8; i++) sv[i] = ex2v(sv[i]);
      { const uint32_t p = pack_bf16(sv[8], sv[9]); mma16816z(o0, vm[0], p, p); mma16816z(o1, vm[1], p, p); }
      { const uint32_t p0 = pack_bf16(sv[0], sv[1]), p1 = pack_bf16(sv[2], sv[3]); mma16816(o0, vx[0], p0, p1); mma16816(o1, vx[2], p0, p1); }
      { const uint32_t p0 = pack_bf16(sv[4], sv[5]), p1 = pack_bf16(sv[6], sv[7]); mma16816(o0, vx[1], p0, p1); mma16816(o1, vx[3], p0, p1); }
      float su = (((sv[8] + sv[9]) + ((sv[0] + sv[1]) + (sv[2] + sv[3]))) + (sv[4] + sv[5])) + (sv[6] + sv[7]);
      { const float a1 = __shfl_xor_sync(~0u, su, 1), a2 = __shfl_xor_sync(~0u, su, 2), a3 = __shfl_xor_sync(~0u, su, 3); su = (su + a1) + (a2 + a3); }
      sts32(aU + 128, __float_as_uint(su));
      stsm4(aO, pack_bf16(o0[0], o0[1]), pack_bf16(o0[2], o0[3]), pack_bf16(o1[0], o1[1]), pack_bf16(o1[2], o1[3]));
      bar_sync(BAR_O, 384);
    }
    const uint32_t t0 = lds32(sb + C_R + 48);
    const uint4 xo = lds128(sb + C_T + 2048 + warp * 512 + lane * 16);
    const uint32_t tag = (s + args.layer + 1) & 1, tm = 0u - tag;
    auto gather = [&](auto NL, uint32_t z) {
      constexpr int n = NL.value;
      const char* p = args.comm + (xo.z + z);
      const uint32_t aMw = sb + C_M + 2048 + (warp == 3 ? 5120 : warp * 1024) + lane * 16;
      int lim = 0; bool bad;
      do { uint4 a[n]; uint32_t m = 0; ++lim;
#pragma unroll
        for (int i = 0; i < n; i++) a[i] = ldg_rlx128(p + (i & 1) * 512 + (i >> 1) * 2048);
#pragma unroll
        for (int i = 0; i < n; i++) { sts128(aMw + (i & 1) * 512 + (i >> 1) * 5120, a[i]); m |= launder((a[i].x ^ tm) | (a[i].z ^ tm)); }
        bad = __any_sync(~0u, (m & 0x10000u) && lim < POLL_LIMIT);
      } while (bad);
      staged();
      if (lane == 0 && warp < 3) { EV(6 + warp, clk() - t0); EV(9 + warp, lim); }
    };
    if (warp == 3) {
      if (lane == 0) { LOGS(c, s); LOGV(c, 192 + (s >> 1), clk());
      }
      uint32_t rdy = 0, e[4][4];
      if (((s + 2) >> 1) >= kv_ok) rdy = ldg_rlx32(args.flags + F_KV + h * 32 + lane);
      spin_until(t0 + args.tc[0]);
      export_ld(e, lane);
      if (XST == 0) export_st(e, s, lane);
      prep(s + 1, lane);
      gather(IC<2>{}, wait_until(t0 + args.tb[1], lane >> 5));
      if (XST == 1) export_st(e, s, lane);
      if (s < 61) {
        spin_until(t0 + args.tc[1]);
        if (((s + 2) >> 1) >= kv_ok) {
          for (int n = 0; (kv_ok = __clz(__brev(~__ballot_sync(~0u, rdy >= 2)))) <= ((s + 2) >> 1) && n < POLL_LIMIT; n++) rdy = ldg_rlx32(args.flags + F_KV + h * 32 + lane);
          asm volatile("fence.acquire.gpu;" ::: "memory");
        }
        load_kv(sb, h, j, s + 2);
      }
    } else {
    if (warp == 2) calib();
    if (warp < 2 || !(c & 16)) {
      const char* p = args.comm + xo.x; char* g2w = args.comm + xo.y;
      const uint32_t s0 = (lane & 8) ? 0u : xo.w, s1 = (lane & 8) ? xo.w : 0u;
      int lim = 0; bool bad;
      p += wait_until(t0 + args.ta[warp == 0 ? 0 : warp == 2 ? 3 : 1 + ((c >> 4) & 1)], lane >> 5);
      do {
        uint4 a[4]; float z0[4], z1[4], y[4];
#pragma unroll
        for (int i = 0; i < 4; i++) a[i] = ldg_rlx128(p + i * 512);
        ++lim;
        { const uint32_t A[4] = {a[0].x, a[0].y, a[0].z, a[0].w}; mma16816z(z0, A, s0, s1); }
        { const uint32_t A[4] = {a[1].x, a[1].y, a[1].z, a[1].w}; mma16816z(z1, A, s0, s1); }
        { const uint32_t A[4] = {a[2].x, a[2].y, a[2].z, a[2].w}; mma16816(z0, A, s0, s1); }
        { const uint32_t A[4] = {a[3].x, a[3].y, a[3].z, a[3].w}; mma16816(z1, A, s0, s1); }
        const uint32_t m0 = launder((a[0].x ^ tm) | (a[0].z ^ tm)), m1 = launder((a[1].x ^ tm) | (a[1].z ^ tm)), m2 = launder((a[2].x ^ tm) | (a[2].z ^ tm)), m3 = launder((a[3].x ^ tm) | (a[3].z ^ tm));
        bad = __any_sync(~0u, ((launder(m0 | m1 | m2) | m3) & 0x10000u) && lim < POLL_LIMIT);
#pragma unroll
        for (int i = 0; i < 4; i++) y[i] = z0[i] + z1[i];
        const bool odd = lane & 1; const float k0 = odd ? y[2] : y[0], k1 = odd ? y[3] : y[1], e0 = odd ? y[0] : y[2], e1 = odd ? y[1] : y[3];
        const float o0 = __shfl_xor_sync(~0u, e0, 1) + __shfl_xor_sync(~0u, e0, 17), o1 = __shfl_xor_sync(~0u, e1, 1) + __shfl_xor_sync(~0u, e1, 17);
        const float q0 = k0 + __shfl_xor_sync(~0u, k0, 16), q1 = k1 + __shfl_xor_sync(~0u, k1, 16);
        const uint32_t w0 = pack_tag(odd ? o0 : q0, odd ? o1 : q1, tag << 16), w1 = pack_bf16(odd ? q0 : o0, odd ? q1 : o1);
        if (!bad) stg_rlx64(g2w, w0, w1);
      } while (bad);
      if (lane == 0 && warp == 0) LOGV(c, 128 + s, lim);
      if (lane == 0) { EV(warp, clk() - t0); EV(3 + warp, lim); }
    }
    prep(s + 1, lane);
    { const uint32_t z = wait_until(t0 + args.tb[warp + 1], lane >> 5); if (warp == 0) gather(IC<2>{}, z); else gather(IC<4>{}, z); }
    }
  }
}

#define PF0 14
#define PFD 2
#define PDT 10
#define NPROBE 3
#define OPACE 500
constexpr int G_ST = 163840;
constexpr int B_FULL = 64, B_EMPTY = 96, B_RB = 128, B_WD = 136, B_ROLE = 144, B_PROG = 152, B_WF = 160  , B_DUM = 200;
enum { BAR_T = 1  , BAR_G = 3  , BAR_V = 5   };
DEVINL uint64_t mkdesc(uint32_t a, uint32_t lbo, uint32_t sbo, uint32_t sw) { return (uint64_t)((a & 0x3FFFF) >> 4) | ((uint64_t)(lbo >> 4) << 16) | ((uint64_t)(sbo >> 4) << 32) | ((uint64_t)sw << 62); }
DEVINL void wgmma_n128(float* d, uint64_t a, uint64_t b, int acc) {
  asm volatile("{.reg .pred p; setp.ne.b32 p, %66, 0; wgmma.mma_async.sync.aligned.m64n128k16.f32.bf16.bf16 {%0,%1,%2,%3,%4,%5,%6,%7,%8,%9,%10,%11,%12,%13,%14,%15,%16,%17,%18,%19,%20,%21,%22,%23,%24,%25,%26,%27,%28,%29,%30,%31,%32,%33,%34,%35,%36,%37,%38,%39,%40,%41,%42,%43,%44,%45,%46,%47,%48,%49,%50,%51,%52,%53,%54,%55,%56,%57,%58,%59,%60,%61,%62,%63}, %64, %65, p, 1, 1, 0, 1;}"
               : "+f"(d[0]),"+f"(d[1]),"+f"(d[2]),"+f"(d[3]),"+f"(d[4]),"+f"(d[5]),"+f"(d[6]),"+f"(d[7]),"+f"(d[8]),"+f"(d[9]),"+f"(d[10]),"+f"(d[11]),"+f"(d[12]),"+f"(d[13]),"+f"(d[14]),"+f"(d[15]),"+f"(d[16]),"+f"(d[17]),"+f"(d[18]),"+f"(d[19]),"+f"(d[20]),"+f"(d[21]),"+f"(d[22]),"+f"(d[23]),"+f"(d[24]),"+f"(d[25]),"+f"(d[26]),"+f"(d[27]),"+f"(d[28]),"+f"(d[29]),"+f"(d[30]),"+f"(d[31]),"+f"(d[32]),"+f"(d[33]),"+f"(d[34]),"+f"(d[35]),"+f"(d[36]),"+f"(d[37]),"+f"(d[38]),"+f"(d[39]),"+f"(d[40]),"+f"(d[41]),"+f"(d[42]),"+f"(d[43]),"+f"(d[44]),"+f"(d[45]),"+f"(d[46]),"+f"(d[47]),"+f"(d[48]),"+f"(d[49]),"+f"(d[50]),"+f"(d[51]),"+f"(d[52]),"+f"(d[53]),"+f"(d[54]),"+f"(d[55]),"+f"(d[56]),"+f"(d[57]),"+f"(d[58]),"+f"(d[59]),"+f"(d[60]),"+f"(d[61]),"+f"(d[62]),"+f"(d[63]) : "l"(a), "l"(b), "r"(acc));
}
DEVINL void wgmma_n80(float* d, uint64_t a, uint64_t b, int acc) {
  asm volatile("{.reg .pred p; setp.ne.b32 p, %42, 0; wgmma.mma_async.sync.aligned.m64n80k16.f32.bf16.bf16 {%0,%1,%2,%3,%4,%5,%6,%7,%8,%9,%10,%11,%12,%13,%14,%15,%16,%17,%18,%19,%20,%21,%22,%23,%24,%25,%26,%27,%28,%29,%30,%31,%32,%33,%34,%35,%36,%37,%38,%39}, %40, %41, p, 1, 1, 0, 1;}"
               : "+f"(d[0]),"+f"(d[1]),"+f"(d[2]),"+f"(d[3]),"+f"(d[4]),"+f"(d[5]),"+f"(d[6]),"+f"(d[7]),"+f"(d[8]),"+f"(d[9]),"+f"(d[10]),"+f"(d[11]),"+f"(d[12]),"+f"(d[13]),"+f"(d[14]),"+f"(d[15]),"+f"(d[16]),"+f"(d[17]),"+f"(d[18]),"+f"(d[19]),"+f"(d[20]),"+f"(d[21]),"+f"(d[22]),"+f"(d[23]),"+f"(d[24]),"+f"(d[25]),"+f"(d[26]),"+f"(d[27]),"+f"(d[28]),"+f"(d[29]),"+f"(d[30]),"+f"(d[31]),"+f"(d[32]),"+f"(d[33]),"+f"(d[34]),"+f"(d[35]),"+f"(d[36]),"+f"(d[37]),"+f"(d[38]),"+f"(d[39]) : "l"(a), "l"(b), "r"(acc));
}

template <int N, int NST>
DEVINL void gemm_tile(float* acc, uint32_t sb, uint32_t px, int wg, uint32_t u0, int rot, bool lead, int wph, bool hand) {
  const uint64_t db = N == 128 ? mkdesc(sb, 81920, 1024, 1) : mkdesc(sb, 32768, 256, 3);
#pragma unroll
  for (int i = 0; i < N / 2; i++) acc[i] = 0.f;
  bar_sync(BAR_T + wg, 256);
#pragma unroll 1
  for (int st = 0; st < NST; st++) {
    const uint32_t u = u0 + st, slot = u & 3, ks = (st + rot >= NST ? st + rot - NST : st + rot) * 8;
    if (wph >= 0) mbar_wait(sb + S_BAR + B_WF + (N == 128 ? st * 8 : 0), wph);
    mbar_wait(sb + S_BAR + B_FULL + slot * 8, (u >> 2) & 1);
    const uint64_t da = mkdesc(sb + G_ST + slot * 16384, 16, 1024, 1);
    asm volatile("wgmma.fence.sync.aligned;" ::: "memory");
#pragma unroll
    for (int k = 0; k < 8; k++) {
      const uint64_t a = da + (k >> 2) * 512 + (k & 3) * 2;
      if (N == 128) wgmma_n128(acc, a, db + (ks + k) * 128, 1); else wgmma_n80(acc, a, db + (ks + k) * 32, 1);
    }
    asm volatile("wgmma.commit_group.sync.aligned;" ::: "memory");
    if (hand && st == NST - 1) bar_arrive(BAR_T + (wg ^ 1), 256);
    if (st > 0) {
      asm volatile("wgmma.wait_group.sync.aligned 1;" ::: "memory");
      if (lead) { const uint32_t e = sb + S_BAR + B_EMPTY + ((u - 1) & 3) * 8; mbar_arrive(e); mbar_arrive_remote(e + px); }
    }
  }
  asm volatile("wgmma.wait_group.sync.aligned 0;" ::: "memory");
  if (lead) { const uint32_t e = sb + S_BAR + B_EMPTY + ((u0 + NST - 1) & 3) * 8; mbar_arrive(e); mbar_arrive_remote(e + px); }
}
DEVINL void wg_publish(int wg) { bar_sync(BAR_G + wg, 160); }
DEVINL uint32_t km_known(uint32_t sb) { uint32_t v; asm volatile("ld.volatile.shared.u32 %0, [%1];" : "=r"(v) : "r"(sb + S_BAR + B_PROG) : "memory"); return __reduce_min_sync(~0u, v); }
DEVINL void km_load(uint4* f, const char* p) {
#pragma unroll
  for (int G = 0; G < 4; G++) f[G] = ldg_rlx128(p + G * 512);
}
DEVINL void km_check(uint4* f, const char* p, uint32_t tg) {
  int n = 0;
#pragma unroll 1
  while (__any_sync(~0u, (((f[0].x ^ tg) | (f[0].z ^ tg) | (f[1].x ^ tg) | (f[1].z ^ tg) | (f[2].x ^ tg) | (f[2].z ^ tg) | (f[3].x ^ tg) | (f[3].z ^ tg)) & 0x10000u) && ++n < POLL_LIMIT)) km_load(f, p);
}
DEVINL void km_watcher(uint32_t sb, const uint32_t* p) {
  uint32_t v = 0;
#pragma unroll 1
  for (int n = 0; n < 16 * POLL_LIMIT && v < 64; n++) {
    const uint2 q = ldg_rlx64(p);
    if (min(q.x, q.y) != v) { v = min(q.x, q.y); asm volatile("st.volatile.shared.u32 [%0], %1;" ::"r"(sb + S_BAR + B_PROG), "r"(v) : "memory"); }
    __nanosleep(v < 61 ? 300 : 20);
  }
}

DEVINL void load_keys(uint4 (*kf)[4], const char* kp, int part, int hf, int on) {
#pragma unroll
  for (int i = 0; i < 8; i++) kf[2 * part + (i >> 2)][i & 3] = ldg128_ef_if(kp + part * hf * 2048 + ((i >> 1) & 1) * 12288 + (i >> 2) * 1024 + (i & 1) * 512, on && (part || hf));
}
DEVINL void attend(const float* acc, uint4 (*kf)[4], uint4* kmf, uint4* op, const char* kvp, const char* mp, bf16* orow, int lane, int hf, int wg, uint32_t sb, int tile, bool& pend, uint32_t tg) {
  const int g = lane >> 2, t = lane & 3;
  float sc[5][4];
#pragma unroll
  for (int k = 0; k < 8; k++) {
    uint32_t qa[4];
#pragma unroll
    for (int i = 0; i < 4; i++) { const float* a = acc + 32 * (k >> 2) + 4 * (k & 3) + 16 * (i >> 1) + 2 * (i & 1); qa[i] = pack_bf16(a[0], a[1]); }
#pragma unroll
    for (int kt = 0; kt < 5; kt++) {
      const uint4 b = kt < 4 ? kf[kt][k >> 1] : kmf[k >> 1];
      if (k == 0) mma16816z(sc[kt], qa, b.x, b.y); else if (k & 1) mma16816(sc[kt], qa, b.z, b.w); else mma16816(sc[kt], qa, b.x, b.y);
    }
  }
  FEN();
  bar_arrive(BAR_T + (wg ^ 1), 256);
  FEN();
  uint32_t go; asm volatile("{.reg .pred p,q; setp.ne.u32 q, %1, 0; bar.red.and.pred p, %2, 128, q; selp.u32 %0, 1, 0, p;}" : "=r"(go) : "r"((uint32_t)(tile < 30 && lds32(sb + S_BAR + B_PROG) > tile * 2 + 5)), "r"(BAR_V + wg) : "memory");
  if (pend) {
#pragma unroll
    for (int q = 0; q < 4; q++) { *(uint4*)(orow - 128 * 4096 + q * 32) = op[2 * q]; *(uint4*)(orow - 120 * 4096 + q * 32) = op[2 * q + 1]; }
    wg_publish(wg);
  }
  pend = __any_sync(~0u, go);
  uint4 vf[2][8], vm[4];
  const char* vp = kvp + 4096 + (g >> 1) * 512 + ((g & 1) * 4 + t) * 16;
  km_load(vm, mp + 2048);
  if (pend) km_load(kmf, mp + 4 * 32 * 4096);
#pragma unroll
  for (int part = 0; part < 2; part++) {
#pragma unroll
    for (int i = 0; i < 8; i++) vf[part][i] = ldg128_ef_if(vp + part * hf * 2048 + (i >> 2) * 4096 + (i & 3) * 128, part || hf);
    load_keys(kf, kvp + 4 * 32 * 16384 + lane * 16, part, hf, tile < 30);
  }
  const float NINF = __int_as_float(0xff800000);
  if (!hf) {
#pragma unroll
    for (int i = 0; i < 8; i++) sc[i >> 2][i & 3] = NINF;
  }
  if (2 * t > g) { sc[2][0] = NINF; sc[3][2] = NINF; }
  if (2 * t + 1 > g) { sc[2][1] = NINF; sc[3][3] = NINF; }
  float m0 = fmaxf(sc[4][0], sc[4][1]), m1 = fmaxf(fmaxf(sc[4][2], sc[4][3]), fmaxf(sc[3][2], sc[3][3]));
#pragma unroll
  for (int kt = 0; kt < 3; kt++) { m0 = fmaxf(m0, fmaxf(sc[kt][0], sc[kt][1])); m1 = fmaxf(m1, fmaxf(sc[kt][2], sc[kt][3])); }
  m0 = fmaxf(fmaxf(m0, __shfl_xor_sync(~0u, m0, 1)), fmaxf(__shfl_xor_sync(~0u, m0, 2), __shfl_xor_sync(~0u, m0, 3)));
  m1 = fmaxf(fmaxf(m1, __shfl_xor_sync(~0u, m1, 1)), fmaxf(__shfl_xor_sync(~0u, m1, 2), __shfl_xor_sync(~0u, m1, 3)));
  m0 *= -SM_SCALE; m1 *= -SM_SCALE;
  float s0 = 0.f, s1 = 0.f; uint32_t p[5][2];
#pragma unroll
  for (int kt = 0; kt < 5; kt++) {
    const float a = kt == 3 ? 0.f : ex2(fmaf(sc[kt][0], SM_SCALE, m0)), b = kt == 3 ? 0.f : ex2(fmaf(sc[kt][1], SM_SCALE, m0)), c = ex2(fmaf(sc[kt][2], SM_SCALE, m1)), d = ex2(fmaf(sc[kt][3], SM_SCALE, m1));
    s0 += a + b; s1 += c + d; p[kt][0] = pack_bf16(a, b); p[kt][1] = pack_bf16(c, d);
  }
  s0 = (s0 + __shfl_xor_sync(~0u, s0, 1)) + (__shfl_xor_sync(~0u, s0, 2) + __shfl_xor_sync(~0u, s0, 3));
  s1 = (s1 + __shfl_xor_sync(~0u, s1, 1)) + (__shfl_xor_sync(~0u, s1, 2) + __shfl_xor_sync(~0u, s1, 3));
  s0 = rcp(s0); s1 = rcp(s1);
  km_check(vm, mp + 2048, tg);
#pragma unroll
  for (int grp = 0; grp < 4; grp++) {
    float o[4][4];
#pragma unroll
    for (int L = 0; L < 4; L++) {
      mma1688z(o[L], p[4][0], p[4][1], L == 0 ? vm[grp].x : L == 1 ? vm[grp].y : L == 2 ? vm[grp].z : vm[grp].w);
#pragma unroll
      for (int kh = 0; kh < 2; kh++) {
        const uint4 w = vf[kh][(grp >> 1) * 4 + L]; const uint32_t A[4] = {p[2 * kh][0], p[2 * kh][1], p[2 * kh + 1][0], p[2 * kh + 1][1]};
        if (grp & 1) mma16816(o[L], A, w.z, w.w); else mma16816(o[L], A, w.x, w.y);
      }
    }
    op[2 * grp] = make_uint4(pack_bf16(o[0][0] * s0, o[0][1] * s0), pack_bf16(o[1][0] * s0, o[1][1] * s0), pack_bf16(o[2][0] * s0, o[2][1] * s0), pack_bf16(o[3][0] * s0, o[3][1] * s0));
    op[2 * grp + 1] = make_uint4(pack_bf16(o[0][2] * s1, o[0][3] * s1), pack_bf16(o[1][2] * s1, o[1][3] * s1), pack_bf16(o[2][2] * s1, o[2][3] * s1), pack_bf16(o[3][2] * s1, o[3][3] * s1));
  }
}

DEVINL void gemm_consumer(uint32_t sb, uint32_t px, int wg, int pr, int rank, const ArgsA& args) {
  const int lane = opaque(threadIdx.x & 31), w = __reduce_max_sync(~0u, (threadIdx.x >> 5) & 3);
  const bool lead = lane == 0 && w == 0;
  const int rot5 = pr % 5, h = 2 * pr + rank;
  if (wg == 1) bar_arrive(BAR_T, 256);
  if (threadIdx.x == 0) LOG(64 + pr * 2 + rank, 250);
  bool pend = false; uint4 op[8], kf[4][4], kmf[4];
#pragma unroll
  for (int i = 0; i < 16; i++) op[i & 7] = kmf[i & 3] = kf[i >> 2][i & 3] = make_uint4(0, 0, 0, 0);
#pragma unroll 1
  for (int it = wg; it < (pr < 16 ? 64 : 32); it += 2) {
    const int tile = it & 31, seg = tile * 2 + (w >> 1);
    float acc[64];
    gemm_tile<128, 5>(acc, sb, px, wg, it * 5, rot5, lead, tile < 2 ? it >> 5 : -1, it < 32);
    if (it < 32) {
      if (tile >= 30 && lead) mbar_arrive(sb + S_BAR + B_WD);
      char* dst = g_kv + (size_t)(seg * 32 + pr) * 16384 + (w & 1) * 2048 + lane * 16;
      if (rank == 0) {
#pragma unroll
        for (int G = 0; G < 4; G++)
#pragma unroll
          for (int hh = 0; hh < 2; hh++) {
            const float* a = acc + 32 * (G >> 1) + 8 * (G & 1) + 2 * hh;
            *(uint4*)(dst + (G >> 1) * 12288 + hh * 1024 + (G & 1) * 512) = make_uint4(pack_bf16(a[0], a[1]), pack_bf16(a[16], a[17]), pack_bf16(a[4], a[5]), pack_bf16(a[20], a[21]));
          }
      } else {
#pragma unroll
        for (int i = 0; i < 8; i++) {
          const float* a = acc + (i >> 2) * 32 + (i & 3) * 4;
          *(uint4*)(dst + 4096 + (i >> 2) * 4096 + (i & 3) * 512) = make_uint4(movm(pack_bf16(a[0], a[1])), movm(pack_bf16(a[2], a[3])), movm(pack_bf16(a[16], a[17])), movm(pack_bf16(a[18], a[19])));
        }
      }
      wg_publish(wg);
      if ((threadIdx.x & 127) == 0) LOG(64 + pr * 2 + rank, tile);
      if (tile >= 28 && tile < 30 && pr < 16) {
        flag_wait_warp(args.flags + F_KV + h * 32 + 16 + (lane & 1), 2);
        const char* kp = g_kv + (size_t)((wg * 2 + (w >> 1)) * 32 + h) * 16384 + lane * 16;
        load_keys(kf, kp, 0, w & 1, 1); load_keys(kf, kp, 1, w & 1, 1);
      }
    } else {
      const char* kvp = g_kv + (size_t)(seg * 32 + h) * 16384;
      const char* mp = g_kvm + (size_t)(seg * 32 + h) * 4096 + lane * 16;
      bf16* orow = g_o + (size_t)(tile * 64 + w * 16 + (lane >> 2)) * 4096 + h * 128 + (lane & 3) * 8;
      if ((threadIdx.x & 127) == 96) LOG(64 + pr * 2 + rank, 64 + tile);
      if (!pend) {
        int n = 0;
        while (km_known(sb) <= seg && ++n < 16 * POLL_LIMIT) {}
        km_load(kmf, mp);
      }
      km_check(kmf, mp, (args.layer ^ 1) << 16);
      if ((threadIdx.x & 127) == 96) LOG(64 + pr * 2 + rank, 96 + tile);
      attend(acc, kf, kmf, op, kvp, mp, orow, lane, w & 1, wg, sb, tile, pend, (args.layer ^ 1) << 16);
      if (!pend) {
#pragma unroll
        for (int q = 0; q < 4; q++) { *(uint4*)(orow + q * 32) = op[2 * q]; *(uint4*)(orow + 8 * 4096 + q * 32) = op[2 * q + 1]; }
        wg_publish(wg);
      }
      if ((tile >> 1) == 5) flag_wait_warp(args.flags + F_KV + h * 32 + 30 + (lane & 1), 2);
      if ((threadIdx.x & 127) == 0) LOG(64 + pr * 2 + rank, 32 + tile);
    }
  }
  if (pr >= 16) {
    const int kq = (pr - 16) >> 2, cg = 2 * (pr & 3) + rank;
#pragma unroll 1
    for (int tile = wg; tile < 32; tile += 2) {
      float acc[40];
      gemm_tile<80, 8>(acc, sb, px, wg, 160 + tile * 8, (pr & 3) * 2, lead, tile < 2 ? 1 : -1, true);
      const bool odd = lane & 1;
      bf16* dst = g_part + (size_t)(kq * 2048 + tile * 64 + w * 16 + (lane >> 2)) * 640 + cg * 80 + (lane & 1) * 8 + (lane & 2) * 2;
#pragma unroll
      for (int q = 0; q < 5; q++)
#pragma unroll
        for (int hh = 0; hh < 2; hh++) {
          const uint32_t A = pack_bf16(acc[8 * q + 2 * hh], acc[8 * q + 2 * hh + 1]), B = pack_bf16(acc[8 * q + 4 + 2 * hh], acc[8 * q + 5 + 2 * hh]);
          const uint32_t x = __shfl_xor_sync(~0u, odd ? A : B, 1);
          *(uint2*)(dst + hh * 8 * 640 + q * 16) = odd ? make_uint2(x, B) : make_uint2(A, x);
        }
      wg_publish(wg);
      if ((threadIdx.x & 127) == 0) LOG(64 + pr * 2 + rank, 32 + tile);
    }
  }
  if (wg == 0) bar_sync(BAR_T, 256);
}

DEVINL void gemm_producer(uint32_t sb, int pr, int rank, const ArgsA& args, const Maps& tm) {
  const uint32_t bWF = sb + S_BAR + B_WF; const int cta = 2 * pr + rank, rot5 = pr % 5, kq = (pr - 16) >> 2;
  uint32_t u = 0;
#pragma unroll 1
  for (int it = -1; it < 64; it++) {
    const int tile = it & 31; const bool op = it >= 32 && pr >= 16;
    if (it == 0 && args.layer) pdl_wait();
    if (it == PDT) pdl_launch();
    if (it == 32 && op) {
      mbar_wait(sb + S_BAR + B_WD, 0);
      w_expect(bWF, 163840);
#pragma unroll 1
      for (int i = 0; i < 20; i++) { w_tma(sb + i * 8192, &tm.o32, (cta & 7) * 80 + (i >> 2) * 16, kq * 1024 + (i & 3) * 256, bWF); __nanosleep(OPACE); }
    }
    if (op || (it == 0 && !args.layer)) { flag_wait_warp(args.flags + (op ? F_O + tile * 4 + kq : F_X), op ? 8 : 128); fence_proxy_async(); }
    else if (it >= 0 && it < 62) w_prefetch((const char*)g_xn + ((tile + 2) & 31) * 81920 + (cta & 31) * 2560, 2560);
#pragma unroll 1
    for (int st = 0; st < (op ? 8 : 5); st++) {
      if (it >= 0) {
        const uint32_t slot = u & 3, full = sb + S_BAR + B_FULL + slot * 8;
        mbar_wait(sb + S_BAR + B_EMPTY + slot * 8, ((u >> 2) & 1) ^ 1);
        w_expect(full, 16384);
        const int ks = st + rot5 >= 5 ? st + rot5 - 5 : st + rot5;
        w_tma_mc(sb + G_ST + slot * 16384 + rank * 8192, op ? &tm.ao : &tm.x, (op ? kq * 1024 + ((st + (pr & 3) * 2) & 7) * 128 : ks * 128) + rank * 64, tile * 64, full);
        u++;
      }
      const int ws = it < 0 ? st : pr < 16 ? (int)u - 160 : -1;
      if (ws >= 0 && ws < 5) {
        const int r = (ws + rot5 >= 5 ? ws + rot5 - 5 : ws + rot5) * 2; w_expect(bWF + ws * 8, 32768);
#pragma unroll 1
        for (int i = 0; i < 4; i++) w_tma(sb + (i & 1) * 81920 + (r + (i >> 1)) * 8192, it < 0 ? (rank ? &tm.v : &tm.k) : &tm.q, (it < 0 ? pr : cta) * 128 + (i & 1) * 64, (r + (i >> 1)) * 64, bWF + ws * 8);
      }
      if (it >= PF0 && it < PF0 + 16) {
        const int q = (it - PF0) * 5 + st; const char* src = (rank ? args.wo : args.wq) + (pr * 80 + q) * 2048;
        if (q == 0) w_expect(sb + S_BAR + B_DUM, 163840);
        w_bulk(sb + S_END, src, 1024, sb + S_BAR + B_DUM); w_bulk(sb + S_END, src + 1024, 1024, sb + S_BAR + B_DUM);
      }
      if (pr < 16 && it >= 32 - PFD && it < 64 - PFD && st < 4)
        w_prefetch(g_kv + (size_t)((it + PFD - 32) * 64 + cta + (st >> 1) * 32) * 16384 + (st & 1) * 8192, 8192);
    }
  }
  mbar_wait(sb + S_BAR + B_DUM, 0);
#pragma unroll 1
  for (int i = 0; i < 4; i++, u++) mbar_wait(sb + S_BAR + B_EMPTY + (u & 3) * 8, ((u >> 2) & 1) ^ 1);
}

DEVINL void gemm_publisher(int wg, int pr, int rank, const ArgsA& args) {
#pragma unroll 1
  for (int i = 0; i < 32; i++) {
    const int tile = (i & 15) * 2 + wg;
    bar_sync(BAR_G + wg, 160);
    if ((threadIdx.x & 31) == 0) {
      flag_add(args.flags + (i < 16 ? F_KV + pr * 32 + tile : pr < 16 ? F_O + tile * 4 + (pr >> 2) : F_P + tile * 32));
    }
    __syncwarp();
  }
}

DEVINL void filter_prep(uint32_t* sm, int part, const ArgsA& args) {
  const int tid = threadIdx.x, lane = tid & 31, w = tid >> 5;
  const unsigned short* wr = (const unsigned short*)args.wr; const unsigned short* wi = (const unsigned short*)args.wi;
#pragma unroll 1
  for (int it = part; it < 32; it += 4) {
#pragma unroll 1
    for (int rr = 0; rr < 8; rr += 2) {
      uint32_t a[2][11], b[2][11];
#pragma unroll
      for (int r = 0; r < 2; r++) {
        const int pos = it * 64 + w * 8 + rr + r, th = (pos >> 2) & 127, v = (pos >> 9) * 4 + (pos & 3);
        const int o = ((th >> 3) + 16 * ((th & 7) + (v & 8)) + 256 * (v & 7)) * 321 + lane;
#pragma unroll
        for (int c = 0; c < 11; c++) if (c < 10 || lane == 0) { a[r][c] = wr[o + c * 32]; b[r][c] = wi[o + c * 32]; }
      }
#pragma unroll
      for (int r = 0; r < 2; r++)
#pragma unroll
        for (int c = 0; c < 11; c++) if (c < 10 || lane == 0) sm[(c * 32 + lane) * 65 + w * 8 + rr + r] = a[r][c] | (b[r][c] << 16);
    }
    bar_sync(1, 256);
#pragma unroll 2
    for (int i = tid; i < 64 * 321; i += 256) g_wt[(i >> 6) * 2048 + it * 64 + (i & 63)] = sm[(i >> 6) * 65 + (i & 63)];
    bar_sync(1, 256);
  }
  if (tid == 0) flag_add(args.flags + F_W);
}

__global__ void __cluster_dims__(2, 1, 1) __launch_bounds__(384, 1)
layer_a_kernel(const __grid_constant__ Maps tm, const __grid_constant__ ArgsA args) {
  extern __shared__ __align__(1024) char smraw[];
  const uint32_t sb = (smem_u32(smraw) + 1023) & ~1023u;
  uint32_t rank; asm volatile("mov.u32 %0, %%cluster_ctarank;" : "=r"(rank));
  rank = __reduce_max_sync(~0u, rank);
  const uint32_t px = __reduce_max_sync(~0u, mapa(sb, rank ^ 1) - sb);
  if (args.layer == 0) LOGK(0, 0);
  uint32_t smid; asm volatile("mov.u32 %0, %%smid;" : "=r"(smid));
  const uint32_t b = sb + S_BAR;
  if (threadIdx.x == 320) {
    mbar_init(b + B_W, 1); mbar_init(b + B_W2, 1); mbar_init(b + B_WV, 1); mbar_init(b + B_WO, 1); mbar_init(b + B_M0, 1); mbar_init(b + B_S, 9); mbar_init(b + B_KV, 1); mbar_init(b + B_KV + 8, 1);
    for (int i = 0; i < 4; i++) { mbar_init(b + B_FULL + i * 8, 1); mbar_init(b + B_EMPTY + i * 8, 2); }
    for (int i = 0; i < 5; i++) mbar_init(b + B_WF + i * 8, 1);
    mbar_init(b + B_WD, 2); mbar_init(b + B_RB, 1); mbar_init(b + B_DUM, 1); sts32(b + B_PROG, 0);
    mbar_arrive_tx(b + B_RB, 8);
    asm volatile("fence.mbarrier_init.release.cluster;" ::: "memory");
  }
  __syncwarp();
  asm volatile("barrier.cluster.arrive.relaxed.aligned;" ::: "memory");
  uint32_t role = 0;
  const bool ln = args.layer == 0 && blockIdx.x < 128 && threadIdx.x < 256;
  const size_t off = (size_t)(blockIdx.x * 16 + (threadIdx.x >> 4)) * 640 + (threadIdx.x & 15) * 8;
  uint4 xr[5];
#pragma unroll
  for (int i = 0; i < 5; i++) xr[i] = ldg128_if(args.x + off + i * 128, ln);
  if (rank == 0 && threadIdx.x >= 256 && threadIdx.x < 320) {
    if (args.layer == 0) {
      uint32_t* p = (uint32_t*)(args.comm + 0x20000 + (threadIdx.x < 288 ? 0x1000 : 0) + (blockIdx.x >> 1) * 32);
      if ((threadIdx.x & 31) < 8) p[threadIdx.x & 31] = 0;
      __syncwarp();
      if ((threadIdx.x & 31) == 0) {
        uint32_t v, best = ~0u;
#pragma unroll 1
        for (int i = 0; i < NPROBE; i++) { const uint32_t t0 = clk(); asm volatile("atom.relaxed.gpu.global.add.u32 %0, [%1], 1;" : "=r"(v) : "l"(p) : "memory"); asm volatile("st.volatile.shared.u32 [%0], %1;" ::"r"(b + 216), "r"(v) : "memory"); best = min(best, clk() - t0); }
        sts32(b + 208 + ((threadIdx.x >> 5) & 1) * 4, best);
      }
      bar_sync(1, 64);
    }
    if (threadIdx.x == 256) {
      int d;
      if (args.layer == 0) { d = (int)(lds32(b + 208) - lds32(b + 212)); g_side[smid & 254] = d; g_side[(smid & 254) + 1] = d; } else d = g_side[smid & 255];
      uint32_t* cnt = args.flags + F_ROLE;
      if (d < 0) { role = atomicAdd(cnt, 1); if (role >= 32) role = 32 + atomicAdd(cnt + 1, 1); }
      else { role = 32 + atomicAdd(cnt + 1, 1); if (role >= 66) role = atomicAdd(cnt, 1); }
    }
    __syncwarp();
  }
  asm volatile("barrier.cluster.wait.aligned;" ::: "memory");
  if (rank == 0 && threadIdx.x == 256) { stasync64(b + B_ROLE, role, 0, b + B_RB); stasync64(b + B_ROLE + px, role, 0, b + B_RB + px); }
  if (ln) {
    float f[40];
#pragma unroll
    for (int i = 0; i < 5; i++) unpack8(xr[i], f + 8 * i);
    ln_row(f);
#pragma unroll
    for (int i = 0; i < 5; i++) *(uint4*)(g_xn + off + i * 128) = pack8(f + 8 * i);
    bar_sync(2, 256);
    if (threadIdx.x == 0) flag_add(args.flags + F_X);
  }
  __syncwarp();
  mbar_wait(b + B_RB, 0);
  role = __reduce_max_sync(~0u, lds32(b + B_ROLE));
  if (threadIdx.x == 352 && args.layer == 0) g_role[smid & 255] = role * 2 + rank;
  if (role != 32) pdl_launch();
  const int wg = __reduce_max_sync(~0u, threadIdx.x >> 7);
  auto U = [](uint32_t x) { return __reduce_max_sync(~0u, opaque(x)); };
  if (wg < 2) {
    asm volatile("setmaxnreg.inc.sync.aligned.u32 224;");
    if (role >= 32) {
      if (role >= 64) { if (args.layer == 0) { filter_prep((uint32_t*)smraw, (role - 64) * 2 + rank, args); if (threadIdx.x == 0) LOG(role * 2 + rank, 0); } }
      else gemm_consumer(U(sb), U(px), U(wg), U(role - 32), U(rank), args);
    } else { if (wg == 0) chain_mma<0>(sb, args); else chain_mma<1>(sb, args); }
  } else {
    asm volatile("setmaxnreg.dec.sync.aligned.u32 56;");
    if (role >= 32) {
      if (role < 64) {
        const uint32_t w = U(threadIdx.x >> 5);
        if (w == 8) gemm_producer(U(sb), U(role - 32), U(rank), args, tm);
        else if (w < 11) gemm_publisher(w - 9, role - 32, rank, args);
        else if (threadIdx.x == 352 && role < 48) km_watcher(sb, args.flags + F_KM + (2 * (role - 32) + rank) * 32);
      }
    } else chain_helper(U(sb), U(px), U(role), U(rank), args, tm);
  }
}

DEVINL float2 cadd(float2 a, float2 b) { return make_float2(a.x + b.x, a.y + b.y); }
DEVINL float2 csub(float2 a, float2 b) { return make_float2(a.x - b.x, a.y - b.y); }
DEVINL float2 cmul(float2 a, float2 b) { return make_float2(fmaf(a.x, b.x, -a.y * b.y), fmaf(a.x, b.y, a.y * b.x)); }
DEVINL float2 cmulc(float2 a, float2 b) { return make_float2(fmaf(a.x, b.x, a.y * b.y), fmaf(a.y, b.x, -a.x * b.y)); }
template <int INV> DEVINL float2 ctw(float2 a, float2 w) { return INV ? cmulc(a, w) : cmul(a, w); }
template <int INV> DEVINL float2 rot(float2 a) { return INV ? make_float2(-a.y, a.x) : make_float2(a.y, -a.x); }
template <int INV> DEVINL void fft4(float2& a, float2& b, float2& c, float2& d) {
  const float2 s0 = cadd(a, c), d0 = csub(a, c), s1 = cadd(b, d), d1 = rot<INV>(csub(b, d));
  a = cadd(s0, s1); b = cadd(d0, d1); c = csub(s0, s1); d = csub(d0, d1);
}
template <int INV> DEVINL float2 w8(float2 a) { const float h = 0.70710678118654752f; const float2 r = rot<INV>(a); return make_float2((a.x + r.x) * h, (a.y + r.y) * h); }
template <int INV> DEVINL void fft8(float2* x) {
  fft4<INV>(x[0], x[2], x[4], x[6]); fft4<INV>(x[1], x[3], x[5], x[7]);
  const float2 e0 = x[0], e1 = x[2], e2 = x[4], e3 = x[6], o0 = x[1], o1 = w8<INV>(x[3]), o2 = rot<INV>(x[5]), o3 = rot<INV>(w8<INV>(x[7]));
  x[0] = cadd(e0, o0); x[1] = cadd(e1, o1); x[2] = cadd(e2, o2); x[3] = cadd(e3, o3);
  x[4] = csub(e0, o0); x[5] = csub(e1, o1); x[6] = csub(e2, o2); x[7] = csub(e3, o3);
}
template <int INV> DEVINL void fft16(float2* x) {
  const float c = 0.92387953251128674f, s = 0.38268343236508977f;
  const float2 w1 = make_float2(c, -s), w3 = make_float2(s, -c);
#pragma unroll
  for (int i = 0; i < 4; i++) fft4<INV>(x[i], x[i + 4], x[i + 8], x[i + 12]);
  x[5] = ctw<INV>(x[5], w1); x[9] = w8<INV>(x[9]); x[13] = ctw<INV>(x[13], w3);
  x[6] = w8<INV>(x[6]); x[10] = rot<INV>(x[10]); x[14] = rot<INV>(w8<INV>(x[14]));
  x[7] = ctw<INV>(x[7], w3); x[11] = rot<INV>(w8<INV>(x[11])); x[15] = ctw<INV>(x[15], make_float2(-c, s));
#pragma unroll
  for (int k = 0; k < 4; k++) fft4<INV>(x[4 * k], x[4 * k + 1], x[4 * k + 2], x[4 * k + 3]);
#pragma unroll
  for (int k = 0; k < 4; k++)
#pragma unroll
    for (int m = k + 1; m < 4; m++) { const float2 t = x[4 * k + m]; x[4 * k + m] = x[4 * m + k]; x[4 * m + k] = t; }
}
template <int INV> DEVINL void fft5(float2& x0, float2& x1, float2& x2, float2& x3, float2& x4) {
  const float c1 = 0.30901699437494742f, c2 = -0.80901699437494742f, s1 = 0.95105651629515357f, s2 = 0.58778525229247313f;
  const float2 a1 = cadd(x1, x4), a2 = cadd(x2, x3), b1 = rot<INV>(csub(x1, x4)), b2 = rot<INV>(csub(x2, x3));
  const float2 p1 = make_float2(fmaf(c1, a1.x, fmaf(c2, a2.x, x0.x)), fmaf(c1, a1.y, fmaf(c2, a2.y, x0.y)));
  const float2 p2 = make_float2(fmaf(c2, a1.x, fmaf(c1, a2.x, x0.x)), fmaf(c2, a1.y, fmaf(c1, a2.y, x0.y)));
  const float2 q1 = make_float2(fmaf(s1, b1.x, s2 * b2.x), fmaf(s1, b1.y, s2 * b2.y));
  const float2 q2 = make_float2(fmaf(s2, b1.x, -s1 * b2.x), fmaf(s2, b1.y, -s1 * b2.y));
  x0 = cadd(x0, cadd(a1, a2)); x1 = cadd(p1, q1); x4 = csub(p1, q1); x2 = cadd(p2, q2); x3 = csub(p2, q2);
}
template <int INV> DEVINL void fft20(const float2* in, float2* out) {
  float2 t[4][5];
#pragma unroll
  for (int a = 0; a < 4; a++) {
#pragma unroll
    for (int b = 0; b < 5; b++) t[a][b] = in[(5 * a + 4 * b) % 20];
    fft5<INV>(t[a][0], t[a][1], t[a][2], t[a][3], t[a][4]);
  }
#pragma unroll
  for (int d = 0; d < 5; d++) {
    fft4<INV>(t[0][d], t[1][d], t[2][d], t[3][d]);
#pragma unroll
    for (int c = 0; c < 4; c++) out[(5 * c + 16 * d) % 20] = t[c][d];
  }
}
constexpr int ZP = 336;
struct RowSmem { float2 T[320 * 17]; uint32_t Z[16 * ZP]; float2 tw[320]; float2 tp[160]; };
DEVINL float2 cis(int k, int n) {
  float sn, cs; __sincosf((float)(2 * k > n ? k - n : k) * (-6.283185307179586f / (float)n), &sn, &cs); return make_float2(cs, sn);
}
DEVINL void row_tables(RowSmem& sm) {
  const int t = threadIdx.x;
  sm.tw[t] = cis((t >> 4) * (t & 15), 320);
  if (t < 160) sm.tp[t] = cis(t, 640);
}

#define WCH 10240
#define WST 2
#define CREG 80
#define IREG 88
#define YPT 1
#define R1E 1
#define IDRY 0
#define CDRY 0
#define RDRY 1

__global__ void __launch_bounds__(320, 1) rows_fwd_kernel(const bf16* __restrict__ xin, const uint32_t* flags) {
  extern __shared__ __align__(1024) char smraw[]; RowSmem& sm = *(RowSmem*)smraw;
  const int tid = threadIdx.x, wp = __reduce_max_sync(~0u, tid >> 5), nr = blockIdx.x < 124 ? 16 : 8, s0 = blockIdx.x < 124 ? blockIdx.x * 16 : 992 + blockIdx.x * 8;
  const uint32_t* flag = flags + F_P + (s0 >> 6) * 32;
  LOGK(1 + 3 * (xin == g_x), 0);
  if (R1E) pdl_launch();
  if (tid == 0) l2_prefetch(xin + s0 * 640, nr * 1280);
  row_tables(sm);
#pragma unroll 1
  for (int live = !RDRY || wp != 1 || __any_sync(~0u, ldg_rlx32(flag) >= 32); live < 2; live++) {
    if (live) {
      if (wp == 0) { uint32_t v; int n = 0;
        while (true) { asm volatile("ld.acquire.gpu.global.u32 %0, [%1];" : "=r"(v) : "l"(flag) : "memory"); if (__all_sync(~0u, v >= 32 || ++n >= 8 * POLL_LIMIT)) break; __nanosleep(v ? 20 : 200); } }
      __syncthreads();
      if (!R1E) pdl_launch();
      LOGK(1 + 3 * (xin == g_x), 1);
    }
    if (wp * 2 < nr) {
      const int row = tid >> 4, j = tid & 15; const size_t off = (size_t)(s0 + row) * 640 + j * 8;
      float f[40]; uint4 in[5][5];
#pragma unroll
      for (int i = 0; i < 5; i++) {
#pragma unroll
        for (int q = 0; q < 4; q++) in[i][q] = ldg128_if(g_part + q * 2048 * 640 + off + i * 128, live);
        in[i][4] = ldg128_if(xin + off + i * 128, live);
      }
#pragma unroll
      for (int i = 0; i < 5; i++) {
        float a[8], b[8], c[8], d[8];
        unpack8(in[i][0], a); unpack8(in[i][1], b); unpack8(in[i][2], c); unpack8(in[i][3], d);
#pragma unroll
        for (int e = 0; e < 8; e++) a[e] = (a[e] + b[e]) + (c[e] + d[e]);
        const uint4 o = pack8(a), x = in[i][4];
        const uint4 r = make_uint4(hadd2bf(o.x, x.x), hadd2bf(o.y, x.y), hadd2bf(o.z, x.z), hadd2bf(o.w, x.w));
        stg128_if(g_x + off + i * 128, r, live); unpack8(r, f + 8 * i);
      }
      ln_row(f);
#pragma unroll
      for (int i = 0; i < 5; i++) *(uint4*)(sm.Z + row * ZP + i * 64 + j * 4) = pack8(f + 8 * i);
      __syncwarp();
      float2 z[20], y[20];
#pragma unroll
      for (int n1 = 0; n1 < 20; n1++) { const uint32_t w = sm.Z[row * ZP + n1 * 16 + j]; z[n1] = make_float2(bf_lo(w), bf_hi(w)); }
      fft20<0>(z, y);
#pragma unroll
      for (int k1 = 1; k1 < 20; k1++) y[k1] = cmul(y[k1], sm.tw[k1 * 16 + j]);
#pragma unroll
      for (int k1 = 0; k1 < 20; k1++) sm.T[(k1 * 16 + j) * 17 + row] = y[k1];
    }
    if (live) __syncthreads();
    const int up = (tid >> 4) & 1, row = tid & 15, k1 = wp ? (up ? 20 - wp : wp) : up * 10;
    float2 x[16];
#pragma unroll
    for (int n2 = 0; n2 < 16; n2++) x[n2] = sm.T[(k1 * 16 + n2) * 17 + row];
    float2 tp[8];
#pragma unroll
    for (int k2 = 0; k2 < 8; k2++) tp[k2] = sm.tp[k1 + 20 * k2];
    fft16<0>(x);
    uint32_t* ya = g_y + s0 + row + k1 * 2048; uint32_t* yb = g_y + s0 + row + (320 - k1) * 2048;
    const int on = live && row < nr;
    stg32_if(g_y + s0 + row + 160 * 2048, pack_f16(2.f * x[8].x, -2.f * x[8].y), on && k1 == 0);
    const int src = (tid & 31) ^ (wp ? 16 : 0); uint32_t wa[8], wb[8];
#pragma unroll
    for (int k2 = 0; k2 < 8; k2++) {
      const float2 c = k1 ? x[15 - k2] : x[(16 - k2) & 15], b = make_float2(__shfl_sync(~0u, c.x, src), __shfl_sync(~0u, c.y, src)), a = x[k2];
      const float2 E = make_float2(a.x + b.x, a.y - b.y), O = cmul(make_float2(a.y + b.y, b.x - a.x), tp[k2]);
      wa[k2] = pack_f16(E.x + O.x, E.y + O.y); wb[k2] = pack_f16(E.x - O.x, O.y - E.y);
    }
#pragma unroll
    for (int k2 = 0; k2 < 8; k2++) { stg32_if(ya + k2 * 20 * 2048, wa[k2], on); stg32_if(yb - k2 * 20 * 2048, wb[k2], on); }
  }
  LOGK(1 + 3 * (xin == g_x), 2);
  if (blockIdx.x == gridDim.x - 1) pdl_wait();
}

__global__ void __maxnreg__(CREG) cols_kernel(int layer) {
  extern __shared__ __align__(1024) char smraw[];
  const int sub = threadIdx.x >> 7, tid = threadIdx.x & 127, col = blockIdx.x * 3 + sub, k1 = tid >> 3, j0 = tid & 7;
  float2* sm = (float2*)smraw + sub * (16 * 152);
  float2* tw = (float2*)smraw + 3 * 16 * 152;
  LOGK(2 + 3 * layer, 0);
  pdl_launch();
  uint32_t* y = g_y + col * 2048 + tid;
  uint4 wf[4];
  flag_wait_warp(g_flags + F_W, 4);
#pragma unroll
  for (int i = 0; i < 4; i++) wf[i] = ldg_cg128(g_wt + col * 2048 + i * 512 + tid * 4);
  if (YPT) {
#pragma unroll
    for (int i = 0; i < 4; i++) asm volatile("cp.async.cg.shared.global [%0], [%1], 16;" ::"r"(smem_u32(sm) + tid * 16), "l"(g_y + col * 2048 + min(i * 512 + tid * 4, 1916)) : "memory");
  }
#pragma unroll 1
  for (int i = threadIdx.x; i < 2176; i += 384) {
    const int a = i < 2048 ? i >> 7 : (i - 2048) >> 3, b = i < 2048 ? i & 127 : i & 7;
    tw[i < 2048 ? a * 136 + b : 2176 + a * 9 + b] = cis(i < 2048 ? a * b : a * b * 16, 2048);
  }
  asm volatile("cp.async.wait_all;" ::: "memory");
  float2* reg = sm + k1 * 152;
#pragma unroll 1
  for (int live = !CDRY || __any_sync(~0u, threadIdx.x >= 32 || ldg_rlx32(g_flags + layer * F_LAYER + F_P + 31 * 32) >= CDRY); live < 2; live++)
#pragma unroll
  for (int it = 0; it < 4; it++) {
    float2 x[16];
    if (it == 0) {
      if (live) { __syncthreads(); pdl_wait(); LOGK(2 + 3 * layer, 1); }
#pragma unroll
      for (int i = 0; i < 16; i++) { const uint32_t w = ldg32_if(y + i * 128, live); x[i] = __half22float2(*(const __half2*)&w); }
    } else {
      const float2* in = it == 3 ? sm + tid : reg + j0; const int is = it == 1 ? 8 : it == 2 ? 9 : 152;
#pragma unroll
      for (int i = 0; i < 16; i++) x[i] = in[i * is];
    }
    fft16<0>(x);
    if (it == 3) {
      const float sc = 1.f / 4096.f;
#pragma unroll
      for (int i = 0; i < 16; i++) stg32_if(y + i * 128, pack_bf16(x[i].y * sc, x[i].x * sc), live);
    } else {
      const float2* t = it == 0 ? tw + tid : it == 1 ? tw + 2176 + j0 : tw + k1 * 136 + j0; const int ts = it == 0 ? 136 : it == 1 ? 9 : 8;
      float2* o = it == 0 ? sm + tid : reg + j0; const int os = it == 0 ? 152 : it == 1 ? 9 : 8;
#pragma unroll
      for (int k = 0; k < 16; k++) if (k > 0 || it == 2) x[k] = cmul(x[k], t[k * ts]);
      __syncwarp();
#pragma unroll
      for (int k = 0; k < 16; k++) o[k * os] = x[k];
      if (it == 1) {
        __syncwarp();
        float2* r9 = reg + j0 * 9;
#pragma unroll
        for (int i = 0; i < 16; i++) x[i] = r9[(i & 8) * 9 + (i & 7)];
#pragma unroll
        for (int h = 0; h < 2; h++) {
          fft8<0>(x); fft8<0>(x + 8);
          if (h == 0) {
#pragma unroll
            for (int i = 0; i < 16; i++) {
              const uint32_t w = (i & 3) == 0 ? wf[i >> 2].x : (i & 3) == 1 ? wf[i >> 2].y : (i & 3) == 2 ? wf[i >> 2].z : wf[i >> 2].w;
              const float2 v = cmul(x[i], make_float2(bf_lo(w), bf_hi(w))); x[i] = make_float2(v.y, v.x);
            }
          }
        }
        const float2* t9 = tw + 2176 + j0 * 9;
#pragma unroll
        for (int i = 0; i < 16; i++) if (i & 7) x[i] = cmul(x[i], t9[(i & 8) * 9 + (i & 7)]);
#pragma unroll
        for (int i = 0; i < 16; i++) r9[(i & 8) * 9 + (i & 7)] = x[i];
        __syncwarp();
      } else if (live) bar_sync(sub + 1, 128);
    }
  }
  LOGK(2 + 3 * layer, 2);
}

__global__ void __maxnreg__(IREG) rows_inv_kernel(bf16* __restrict__ xout, int do_ln, const __grid_constant__ Wts w) {
  extern __shared__ __align__(1024) char smraw[]; RowSmem& sm = *(RowSmem*)smraw;
  const int tid = threadIdx.x, s0 = blockIdx.x * 16, wp = __reduce_max_sync(~0u, tid >> 5);
  LOGK(3 + 3 * !do_ln, 0);
  const uint32_t ctl = smem_u32(smraw) + 72 * 1024;
  if (tid == 0) sts32(ctl + 8, 0);
  __syncthreads();
  if (wp == 10) { if (WCH && do_ln && tid == 320) weight_warm<WCH ? WCH : 16>(w, ctl + 1024, ctl, ctl + 8); return; }
  if (tid == 0) l2_prefetch(g_x + s0 * 640, 20480);
  row_tables(sm);
  const size_t off = (size_t)(s0 + ((tid >> 4) & 15)) * 640 + (tid & 15) * 8;
#pragma unroll 1
  for (int live = wp != 1 || (!IDRY && do_ln < 2); live < 2; live++) {
    if (live) {
      bar_sync(1, 320);
      pdl_wait();
      pdl_launch();
      if (WST == 0 && tid == 0) sts32(ctl + 8, 1);
      LOGK(3 + 3 * !do_ln, 1);
    }
    uint4 xr[5];
    {
      const int up = (tid >> 4) & 1, row = tid & 15, k1 = wp ? (up ? 20 - wp : wp) : up * 10;
      const uint32_t* ya = g_y + s0 + row + k1 * 2048; const uint32_t* yb = g_y + s0 + row + (320 - k1) * 2048;
      uint32_t wa[8], wb[8];
#pragma unroll
      for (int k2 = 0; k2 < 8; k2++) { wa[k2] = ldg32_if(ya + k2 * 20 * 2048, live); wb[k2] = ldg32_if(yb - k2 * 20 * 2048, live); }
      const uint32_t wm = ldg32_if(g_y + s0 + row + 160 * 2048, live && k1 == 0);
#pragma unroll
      for (int i = 0; i < 5; i++) xr[i] = ldg128_if(g_x + off + i * 128, live && wp < 8);
      stg32_if(g_flags + blockIdx.x * 320 + tid, 0, live && !do_ln && blockIdx.x * 320 + tid < 2 * F_LAYER);
      if (k1 == 0) { wa[0] &= 0xffffu; wb[0] &= 0xffffu; }
      float2 x[16], r[8];
#pragma unroll
      for (int k2 = 0; k2 < 8; k2++) {
        const float2 a = make_float2(bf_lo(wa[k2]), bf_hi(wa[k2])), b = make_float2(bf_lo(wb[k2]), bf_hi(wb[k2]));
        const float2 E = make_float2(a.x + b.x, a.y - b.y), O = cmulc(make_float2(a.x - b.x, a.y + b.y), sm.tp[k1 + 20 * k2]);
        x[k2] = make_float2(E.x - O.y, E.y + O.x); r[k2] = make_float2(E.x + O.y, O.x - E.y);
      }
      if (k1 == 0) r[0] = make_float2(2.f * bf_lo(wm), -2.f * bf_hi(wm));
      const int src = (tid & 31) ^ (wp ? 16 : 0);
#pragma unroll
      for (int i = 8; i < 16; i++) { const float2 c = k1 ? r[15 - i] : r[(16 - i) & 7]; x[i] = make_float2(__shfl_sync(~0u, c.x, src), __shfl_sync(~0u, c.y, src)); }
      fft16<1>(x);
#pragma unroll
      for (int n2 = 0; n2 < 16; n2++) sm.T[(k1 * 16 + n2) * 17 + row] = x[n2];
    }
    if (live) { bar_sync(1, 320); if (WST == 1 && tid == 0) sts32(ctl + 8, 1); }
    if (wp < 8) {
      const int row = tid >> 4, n2 = tid & 15;
      float2 z[20], y[20];
#pragma unroll
      for (int k1 = 0; k1 < 20; k1++) { const float2 t = sm.T[(k1 * 16 + n2) * 17 + row]; z[k1] = k1 ? cmulc(t, sm.tw[k1 * 16 + n2]) : t; }
      fft20<1>(z, y);
      const float sc = 1.f / 640.f;
#pragma unroll
      for (int n1 = 0; n1 < 20; n1++) sm.Z[row * ZP + n1 * 16 + n2] = pack_bf16(y[n1].x * sc, y[n1].y * sc);
      __syncwarp();
      if (WST == 2 && live && tid == 0) sts32(ctl + 8, 1);
      float f[40];
#pragma unroll
      for (int i = 0; i < 5; i++) {
        const uint4 o = *(const uint4*)(sm.Z + row * ZP + i * 64 + n2 * 4), x = xr[i];
        xr[i] = make_uint4(hadd2bf(o.x, x.x), hadd2bf(o.y, x.y), hadd2bf(o.z, x.z), hadd2bf(o.w, x.w));
      }
#pragma unroll
      for (int i = 0; i < 5; i++) { stg128_if(xout + off + i * 128, xr[i], live); unpack8(xr[i], f + 8 * i); }
      if (do_ln) {
        ln_row(f);
#pragma unroll
        for (int i = 0; i < 5; i++) stg128_if(g_xn + off + i * 128, pack8(f + 8 * i), live);
      }
    }
  }
  LOGK(3 + 3 * !do_ln, 2);
}

typedef CUresult (*EncFn)(CUtensorMap*, CUtensorMapDataType, cuuint32_t, void*, const cuuint64_t*, const cuuint64_t*, const cuuint32_t*, const cuuint32_t*,
                          CUtensorMapInterleave, CUtensorMapSwizzle, CUtensorMapL2promotion, CUtensorMapFloatOOBfill);
static void make_map(EncFn fn, CUtensorMap* m, const void* p, uint64_t cols, uint64_t rows, uint32_t bc, uint32_t br, CUtensorMapSwizzle sw) {
  cuuint64_t gd[2] = {cols, rows}, gs[1] = {cols * 2}; cuuint32_t bd[2] = {bc, br}, es[2] = {1, 1};
  fn(m, CU_TENSOR_MAP_DATA_TYPE_BFLOAT16, 2, (void*)p, gd, gs, bd, es, CU_TENSOR_MAP_INTERLEAVE_NONE, sw, CU_TENSOR_MAP_L2_PROMOTION_L2_128B, CU_TENSOR_MAP_FLOAT_OOB_FILL_NONE);
}
template <class... P, class... A>
static void launch(void (*k)(P...), int grid, int block, int smem, bool pdl, A... a) {
  cudaLaunchConfig_t cfg = {}; cfg.gridDim = dim3(grid); cfg.blockDim = dim3(block); cfg.dynamicSmemBytes = smem; cfg.stream = cudaStreamPerThread;
  cudaLaunchAttribute at[1]; at[0].id = cudaLaunchAttributeProgrammaticStreamSerialization; at[0].val.programmaticStreamSerializationAllowed = 1;
  cfg.attrs = at; cfg.numAttrs = pdl ? 1 : 0;
  cudaLaunchKernelEx(&cfg, k, a...);
}
static const int tune_t[10] = {1370, 1725, 1845, 1970, 2170, 2490, 2590, 2710, 2050, 2420}; constexpr int dev_stop = 100, dev_pdl = 1;

extern "C" void kernel_launch(void* const* d_in, const int* in_sizes, int n_in, void* d_out, int out_size) {
  const bf16 *x = (const bf16*)d_in[0], *mem0 = (const bf16*)d_in[1], *Wq = (const bf16*)d_in[2], *Wk = (const bf16*)d_in[3], *Wv = (const bf16*)d_in[4], *Wo = (const bf16*)d_in[5];
  const bf16 *wr = (const bf16*)d_in[8], *wi = (const bf16*)d_in[9];
  constexpr int SM_A = S_END + 2048, SM_R = sizeof(RowSmem), SM_C = 114 * 1024, SM_I = 96 * 1024;
  void *p_xn, *p_o, *p_x, *p_comm, *p_flags, *fn; cudaDriverEntryPointQueryResult qr;
  cudaGetSymbolAddress(&p_xn, g_xn); cudaGetSymbolAddress(&p_o, g_o); cudaGetSymbolAddress(&p_x, g_x); cudaGetSymbolAddress(&p_comm, g_comm); cudaGetSymbolAddress(&p_flags, g_flags);
  cudaGetDriverEntryPoint("cuTensorMapEncodeTiled", &fn, cudaEnableDefault, &qr);
  cudaFuncSetAttribute(layer_a_kernel, cudaFuncAttributeMaxDynamicSharedMemorySize, SM_A);
  cudaFuncSetAttribute(rows_fwd_kernel, cudaFuncAttributeMaxDynamicSharedMemorySize, SM_R);
  cudaFuncSetAttribute(rows_inv_kernel, cudaFuncAttributeMaxDynamicSharedMemorySize, SM_I);
  cudaFuncSetAttribute(cols_kernel, cudaFuncAttributeMaxDynamicSharedMemorySize, SM_C);
  cudaFuncSetAttribute(rows_fwd_kernel, cudaFuncAttributePreferredSharedMemoryCarveout, 100);
  cudaFuncSetAttribute(cols_kernel, cudaFuncAttributePreferredSharedMemoryCarveout, 100);
  cudaFuncSetAttribute(rows_inv_kernel, cudaFuncAttributePreferredSharedMemoryCarveout, 100);
  Maps tm; EncFn enc = (EncFn)fn;
  make_map(enc, &tm.q, Wq, 4096, 640, 64, 64, CU_TENSOR_MAP_SWIZZLE_128B); make_map(enc, &tm.k, Wk, 4096, 640, 64, 64, CU_TENSOR_MAP_SWIZZLE_128B);
  make_map(enc, &tm.v, Wv, 4096, 640, 64, 64, CU_TENSOR_MAP_SWIZZLE_128B); make_map(enc, &tm.o, Wo, 640, 4096, 64, 64, CU_TENSOR_MAP_SWIZZLE_128B);
  make_map(enc, &tm.o32, Wo, 640, 4096, 16, 256, CU_TENSOR_MAP_SWIZZLE_32B);
  make_map(enc, &tm.x, p_xn, 640, 2048, 64, 64, CU_TENSOR_MAP_SWIZZLE_128B); make_map(enc, &tm.ao, p_o, 4096, 2048, 64, 64, CU_TENSOR_MAP_SWIZZLE_128B);
  char* comm = (char*)(((uintptr_t)p_comm + (2 << 20) - 1) & ~(uintptr_t)((2 << 20) - 1));
  const bool pdl = dev_pdl;
#define L0PDL 0
  for (int l = 0; l < 2; l++) {
    ArgsA a{x, mem0, comm, (uint32_t*)p_flags + l * F_LAYER, wr, wi, (const char*)Wq, (const char*)Wo, l, {tune_t[0], tune_t[1], tune_t[2], tune_t[3]}, {tune_t[4], tune_t[5], tune_t[6], tune_t[7]}, {tune_t[8], tune_t[9]}};
    const Wts w = {{(const char*)Wk, (const char*)Wq, (const char*)Wv, (const char*)Wo}};
    if (dev_stop > 4 * l + 0) launch(layer_a_kernel, 132, 384, SM_A, pdl && (l || L0PDL), tm, a);
    if (dev_stop > 4 * l + 1) launch(rows_fwd_kernel, 132, 320, SM_R, pdl, l ? (const bf16*)p_x : x, (const uint32_t*)a.flags);
    if (dev_stop > 4 * l + 2) launch(cols_kernel, 107, 384, SM_C, pdl, l);
    if (dev_stop > 4 * l + 3) launch(rows_inv_kernel, 128, 352, SM_I, pdl, l ? (bf16*)d_out : (bf16*)p_x, l == 0, w);
  }
}
```
